```python
import torch

def _softmax(x, axis=-1):
    return torch.softmax(x, dim=axis)

def _gelu(x):
    return torch.nn.functional.gelu(x, approximate='tanh')

def _silu(x):
    return torch.nn.functional.silu(x)

def _sigmoid(x):
    return torch.sigmoid(x)

def _layernorm(x, axis=-1, eps=1e-05):
    m = x.mean(dim=axis, keepdim=True)
    v = x.var(dim=axis, keepdim=True, unbiased=False)
    return (x - m) / torch.sqrt(v + eps)

def _scatter_add(tgt, idx, src, axis=0):
    return tgt.clone().index_add_(axis, idx, src)

def _segment_sum(src, seg, n):
    out = torch.zeros((n,) + src.shape[1:], dtype=src.dtype)
    return out.index_add_(0, seg, src)

def _pad(x, pw):
    flat = tuple((v for pair in reversed(pw) for v in pair))
    return torch.nn.functional.pad(x, flat)
kernel_name = 'interleave_layers__ssm_conv_h3__memory_aug_recurrent_mem_tr__prompt'

def setup_inputs():

    _w = lambda a: (lambda t: t.to(torch.bfloat16) if t.is_floating_point() else t)(torch.as_tensor(a))

    def _A_setup():
        B, S, D = (1, 2048, 576)
        ks = 4
        return {'q': _w((lambda *s: torch.randn(*s, dtype=torch.bfloat16) * 0.05)(B, S, D)), 'k': _w((lambda *s: torch.randn(*s, dtype=torch.bfloat16) * 0.2)(B, S, D)), 'v': _w((lambda *s: torch.randn(*s, dtype=torch.bfloat16) * 0.2)(B, S, D)), 'shift_k': _w((lambda *s: torch.randn(*s, dtype=torch.bfloat16) * 0.2)(D, ks) * 0.5), 'ssm_k': _w((lambda *s: torch.randn(*s, dtype=torch.bfloat16) * 0.4)(D, S) * (1.0 / S ** 0.5)), 'ssm_D': _w((lambda *s: torch.randn(*s, dtype=torch.bfloat16) * 0.2)(D))}
    _A_in = _A_setup()

    def _B_setup():
        B, S, Dm = (1, 2048, 576)
        H, Dh = (32, 128)
        M, seg = (8, 32)
        seg = min(seg, S)
        S = S // seg * seg
        return {'x': _w((lambda *s: torch.randn(*s, dtype=torch.bfloat16) * 0.05)(B, S, Dm)), 'mem0': _w((lambda *s: torch.randn(*s, dtype=torch.bfloat16) * 0.2)(B, M, Dm)), 'Wq': _w((lambda *s: torch.randn(*s, dtype=torch.bfloat16) * 1.6)(Dm, H, Dh) * Dm ** (-0.5)), 'Wk': _w((lambda *s: torch.randn(*s, dtype=torch.bfloat16) * 1.6)(Dm, H, Dh) * Dm ** (-0.5)), 'Wv': _w((lambda *s: torch.randn(*s, dtype=torch.bfloat16) * 0.2)(Dm, H, Dh) * Dm ** (-0.5)), 'Wo': _w((lambda *s: torch.randn(*s, dtype=torch.bfloat16) * 0.2)(H, Dh, Dm) * (H * Dh) ** (-0.5)), 'seg_len': seg}
    _B_in = _B_setup()
    return {'A_q': _A_in['q'], 'A_k': _A_in['k'], 'A_v': _A_in['v'], 'A_shift_k': _A_in['shift_k'], 'A_ssm_k': _A_in['ssm_k'], 'A_ssm_D': _A_in['ssm_D'], 'B_x': _B_in['x'], 'B_mem0': _B_in['mem0'], 'B_Wq': _B_in['Wq'], 'B_Wk': _B_in['Wk'], 'B_Wv': _B_in['Wv'], 'B_Wo': _B_in['Wo'], 'B_seg_len': _B_in['seg_len']}

def reference(A_q, A_k, A_v, A_shift_k, A_ssm_k, A_ssm_D, B_x, B_mem0, B_Wq, B_Wk, B_Wv, B_Wo, B_seg_len):

    def _A_ref(q, k, v, shift_k, ssm_k, ssm_D):
        B, S, D = q.shape
        ks = shift_k.shape[-1]
        k_pad = _pad(k, ((0, 0), (ks - 1, 0), (0, 0)))
        k_shift = torch.zeros_like(k)
        for t in range(ks):
            k_shift = k_shift + k_pad[:, t:t + S, :] * shift_k[:, ks - 1 - t][None, None, :]
        kv = k_shift * v
        L = 2 * S
        kv_pad = _pad(kv, ((0, 0), (0, S), (0, 0)))
        kf_pad = _pad(ssm_k, ((0, 0), (0, S)))
        kv_f = (lambda x, axes=(-2, -1): torch.fft.rfft2(x.float(), dim=axes))(kv_pad[:, None, :, :], axes=(1, 2))
        kf_f = (lambda x, axes=(-2, -1): torch.fft.rfft2(x.float(), dim=axes))(kf_pad[:, None, :], axes=(1, 2))
        kf_f = (lambda x, *d: x.permute(*d))(kf_f, 1, 2, 0)
        y_f = kv_f * kf_f[None, :, :, :]
        y = (lambda x, s, axes=(-2, -1): torch.fft.irfft2(x, s=s, dim=axes).to(torch.bfloat16))(y_f, (1, L), axes=(1, 2))[:, 0, :S, :]
        y = y + kv * ssm_D[None, None, :]
        return q * y

    def _B_ref(x, mem0, Wq, Wk, Wv, Wo, seg_len):
        B, S, Dm = x.shape
        H, Dh = (Wq.shape[1], Wq.shape[2])
        M = mem0.shape[1]
        scale = Dh ** (-0.5)
        n_seg = S // seg_len
        L = M + seg_len
        idx = torch.arange(L)
        mask = (idx[:, None] < M) | (idx[:, None] >= idx[None, :])
        mem = mem0
        outs = []
        for s in range(n_seg):
            xs = x[:, s * seg_len:(s + 1) * seg_len, :].clone()
            h = torch.concatenate([mem, xs], axis=1)
            q = torch.einsum('btd,dhe->bhte', h, Wq)
            k = torch.einsum('btd,dhe->bhte', h, Wk)
            v = torch.einsum('btd,dhe->bhte', h, Wv)
            scores = torch.einsum('bhqe,bhke->bhqk', q, k) * scale
            scores = torch.where(mask[None, None], scores, -1000000000.0)
            p = _softmax(scores, axis=-1)
            o = torch.einsum('bhqk,bhke->bhqe', p, v)
            o = torch.einsum('bhte,hed->btd', o, Wo)
            mem = o[:, :M, :].clone()
            outs.append(o[:, M:, :])
        return torch.concatenate(outs, axis=1)
    x = A_q
    x = x + _A_ref(_layernorm(x, axis=-1), A_k, A_v, A_shift_k, A_ssm_k, A_ssm_D)
    x = x + _B_ref(_layernorm(x, axis=-1), B_mem0, B_Wq, B_Wk, B_Wv, B_Wo, B_seg_len)
    x = x + _A_ref(_layernorm(x, axis=-1), A_k, A_v, A_shift_k, A_ssm_k, A_ssm_D)
    x = x + _B_ref(_layernorm(x, axis=-1), B_mem0, B_Wq, B_Wk, B_Wv, B_Wo, B_seg_len)
    return x
```

```cpp
#include <cuda_runtime.h>
#include <cuda_bf16.h>
#include <stdint.h>

namespace {

constexpr int SEQ = 2048, DM = 576, NSEG = 64;
#define LAG_V 5
#define XCV_V 3
#define RV_V 2100
#define RVS_V 120
#define RQ_V 2550
#define RQ1_V 150
#define RQ2_V 150
#define RK_V 120
#define GX_V 1450
constexpr int LAG = LAG_V;
constexpr int NT = NSEG + LAG;
constexpr int OXRING = 8;
static_assert(LAG >= 3 && LAG < OXRING, "pipeline lag");
__host__ __device__ constexpr uint32_t red_delay(int c) {
  return c < 3 ? RV_V + c * RVS_V : RQ_V + (c & 1 ? 0 : RK_V) + (c > 4 ? RQ1_V : 0) + (c > 6 ? RQ2_V : 0);
}
constexpr uint32_t D_GX = GX_V;
constexpr int X_TRIGV = XCV_V;
constexpr uint32_t SB0 = 1024;
constexpr bool OXF_LATE = true;
constexpr float SM_SCALE = 0.08838834764831845f * 1.4426950408889634f;
constexpr uint32_t SENT = 0xFFFFFFFFu;
constexpr uint32_t SPIN_LIMIT = 1u << 21;

constexpr int FL_XS = 0;
constexpr int FL_ACC = (NT + 2) * 32;
constexpr int FL_OX = FL_ACC + 128 * 32;
constexpr int FL_SEL = FL_OX + (NT + 1) * 32;
constexpr int FL_INIT = FL_SEL + 96 * 4;
constexpr int FL_Y = FL_INIT + 32;
constexpr int FL_KV = FL_Y + 512;
constexpr int FL_TOTAL = FL_KV + 128;

__device__ __align__(1024) uint4 g_y[256 * DM];
__device__ __align__(1024) uint4 g_kv[256 * DM];
__device__ __align__(1024) float4 g_acc[2 * 256 * 36 * 32];
__device__ __align__(1024) uint4 g_xs[(NT + 1) * 8 * 580];
__device__ __align__(1024) uint4 g_ox[OXRING * 512 * 8 * 8];
__device__ __align__(1024) uint4 g_xchg[(288 + 10 + 1) * 512];
__device__ __align__(1024) uint32_t g_flagsets[2 * FL_TOTAL];
__device__ uint32_t g_epoch;
#define PROF_T(slot) do {} while (0)
#define PROF_END() do {} while (0)
#define PROF_V(cond, slot, val) do { (void)(val); } while (0)
#define PROF_G(slot) do {} while (0)
#define PROF_A(idx, val) do { (void)(val); } while (0)
#define PROF_BEGIN() do {} while (0)
#define PROF_MID() do {} while (0)

__device__ __forceinline__ uint32_t pack_bf16(float lo, float hi) {
  uint32_t r; asm("cvt.rn.bf16x2.f32 %0, %1, %2;" : "=r"(r) : "f"(hi), "f"(lo)); return r;
}
__device__ __forceinline__ float bf_lo(uint32_t w) { return __uint_as_float(w << 16); }
__device__ __forceinline__ float bf_hi(uint32_t w) { return __uint_as_float(w & 0xFFFF0000u); }
__device__ __forceinline__ uint32_t mapa(uint32_t a, uint32_t r) {
  uint32_t o; asm("mapa.shared::cluster.u32 %0, %1, %2;" : "=r"(o) : "r"(a), "r"(r)); return o;
}
__device__ __forceinline__ void mbar_init(uint32_t bar, uint32_t cnt) {
  asm volatile("mbarrier.init.shared::cta.b64 [%0], %1;" :: "r"(bar), "r"(cnt) : "memory");
}
__device__ __forceinline__ void mbar_expect(uint32_t bar, uint32_t bytes) {
  asm volatile("mbarrier.arrive.expect_tx.shared::cta.b64 _, [%0], %1;" :: "r"(bar), "r"(bytes) : "memory");
}
__device__ __forceinline__ void mbar_arrive(uint32_t bar) {
  asm volatile("mbarrier.arrive.shared::cta.b64 _, [%0];" :: "r"(bar) : "memory");
}
__device__ __forceinline__ void mbar_arrive_if0(uint32_t sel, uint32_t bar) {
  asm volatile("{\n.reg .pred p;\nsetp.eq.u32 p, %1, 0;\n@p mbarrier.arrive.shared::cta.b64 _, [%0];\n}" :: "r"(bar), "r"(sel) : "memory");
}
__device__ __forceinline__ void mbar_expect_if0(uint32_t sel, uint32_t bar, uint32_t bytes) {
  asm volatile("{\n.reg .pred p;\nsetp.eq.u32 p, %1, 0;\n@p mbarrier.arrive.expect_tx.shared::cta.b64 _, [%0], %2;\n}" :: "r"(bar), "r"(sel), "r"(bytes) : "memory");
}
__device__ __forceinline__ void mbar_wait_lim(uint32_t bar, uint32_t par) {
  asm volatile(
    "{\n.reg .pred p;\n.reg .u32 c;\nmov.u32 c, 0;\n"
    "W_%=:\n"
    "mbarrier.try_wait.parity.shared::cta.b64 p, [%0], %1;\n"
    "@p bra D_%=;\n"
    "add.u32 c, c, 1;\nsetp.lt.u32 p, c, %2;\n@p bra W_%=;\ntrap;\n"
    "D_%=:\n}\n" :: "r"(bar), "r"(par), "n"(SPIN_LIMIT) : "memory");
}
__device__ __forceinline__ void mbar_wait(uint32_t bar, uint32_t par) {
  asm volatile(
    "{\n.reg .pred p;\n"
    "W_%=:\n"
    "mbarrier.try_wait.parity.shared::cta.b64 p, [%0], %1;\n"
    "@!p bra W_%=;\n}\n" :: "r"(bar), "r"(par) : "memory");
}
template <int ID, int N> __device__ __forceinline__ void bar_sync() { asm volatile("bar.sync %0, %1;" :: "n"(ID), "n"(N) : "memory"); }
template <int ID, int N> __device__ __forceinline__ void bar_arrive() { asm volatile("bar.arrive %0, %1;" :: "n"(ID), "n"(N) : "memory"); }
__device__ __forceinline__ void bar_sync_r(int id, int n) { asm volatile("bar.sync %0, %1;" :: "r"(id), "r"(n) : "memory"); }
__device__ __forceinline__ void bar_arrive_r(int id, int n) { asm volatile("bar.arrive %0, %1;" :: "r"(id), "r"(n) : "memory"); }
__device__ __forceinline__ void cluster_sync() {
  asm volatile("barrier.cluster.arrive.aligned;\nbarrier.cluster.wait.aligned;" ::: "memory");
}
__device__ __forceinline__ void fence_async_smem() { asm volatile("fence.proxy.async.shared::cta;" ::: "memory"); }
__device__ __forceinline__ void fence_async_global() { asm volatile("fence.proxy.async.global;" ::: "memory"); }
__device__ __forceinline__ uint4 ld_poll(const uint4* p) {
  uint4 v;
  asm volatile("ld.relaxed.gpu.global.v4.u32 {%0,%1,%2,%3}, [%4];" : "=r"(v.x), "=r"(v.y), "=r"(v.z), "=r"(v.w) : "l"(p) : "memory");
  return v;
}
__device__ __forceinline__ uint32_t rd_clock() { uint32_t c; asm volatile("mov.u32 %0, %%clock;" : "=r"(c) :: "memory"); return c; }
__device__ __forceinline__ void spin_until(uint32_t when) {
  asm volatile("{\n.reg .pred p;\n.reg .b64 c;\n.reg .s32 lo;\nS_%=:\nmov.u64 c, %%clock64;\ncvt.u32.u64 lo, c;\nsub.s32 lo, lo, %0;\n"
               "setp.lt.s32 p, lo, 0;\n@p bra.uni S_%=;\n}" :: "r"(when) : "memory");
}
__device__ __forceinline__ uint32_t near_page(uint4* pair) {
  uint32_t best0 = ~0u, best1 = ~0u;
  const int lane = threadIdx.x & 31;
  if (lane < 4) asm volatile("st.relaxed.gpu.global.v4.u32 [%0], {%1,%1,%1,%1};" :: "l"(pair + (lane >> 1) * 256 + (lane & 1)), "r"(SENT) : "memory");
  __syncwarp();
#pragma unroll 1
  for (int r = 0; r < 8; r++) {
    if (r >= 4 && !(r & 1) && __all_sync(0xffffffffu, max(best0, best1) - min(best0, best1) > 110u && min(best0, best1) < 420u)) break;
    uint32_t t0, t1, v;
    asm volatile("mov.u32 %0, %%clock;" : "=r"(t0) :: "memory");
    asm volatile("{\n.reg .pred p;\nsetp.eq.u32 p, %2, 0;\nmov.u32 %0, 0;\n@p atom.relaxed.gpu.global.exch.b32 %0, [%1], %3;\n}"
                 : "=&r"(v) : "l"(pair + (r & 1) * 256), "r"(lane), "r"(SENT) : "memory");
    asm volatile("{\n.reg .pred p;\nsetp.ne.u32 p, %1, 0x9E3779B9;\nmov.u32 %0, %2;\n@p mov.u32 %0, %%clock;\n}" : "=&r"(t1) : "r"(v), "r"(t0 - 1) : "memory");
    if (r & 1) best1 = min(best1, t1 - t0); else best0 = min(best0, t1 - t0);
  }
  return best1 < best0;
}
__device__ __forceinline__ void st_gpu4(uint4* p, uint32_t a, uint32_t b, uint32_t c, uint32_t d) {
  asm volatile("st.relaxed.gpu.global.v4.u32 [%0], {%1,%2,%3,%4};" :: "l"(p), "r"(a), "r"(b), "r"(c), "r"(d) : "memory");
}
__device__ __forceinline__ void st_gpu1(uint32_t* p, uint32_t a) {
  asm volatile("st.relaxed.gpu.global.u32 [%0], %1;" :: "l"(p), "r"(a) : "memory");
}
__device__ __forceinline__ void st_gpu1_if(bool c, uint32_t* p, uint32_t a) {
  asm volatile("{\n.reg .pred p;\nsetp.ne.u32 p, %2, 0;\n@p st.relaxed.gpu.global.u32 [%0], %1;\n}" :: "l"(p), "r"(a), "r"((uint32_t)c) : "memory");
}
__device__ __forceinline__ void flag_wait(const uint32_t* p, uint32_t target) {
  uint32_t v, n = 0;
  do {
    asm volatile("ld.acquire.gpu.global.u32 %0, [%1];" : "=r"(v) : "l"(p) : "memory");
    if (++n > SPIN_LIMIT) __trap();
  } while (v < target);
}
__device__ __forceinline__ void warp_flag_wait(const uint32_t* p, uint32_t target) {
  uint32_t v, n = 0;
  do {
    asm volatile("ld.acquire.gpu.global.u32 %0, [%1];" : "=r"(v) : "l"(p) : "memory");
    if (++n > SPIN_LIMIT) __trap();
  } while (__any_sync(0xffffffffu, v < target));
}
__device__ __forceinline__ void flag_add(uint32_t* p) {
  asm volatile("red.release.gpu.global.add.u32 [%0], 1;" :: "l"(p) : "memory");
}
__device__ __forceinline__ void bulk_g2s(uint32_t dst, const void* src, uint32_t bytes, uint32_t bar) {
  asm volatile("cp.async.bulk.shared::cluster.global.mbarrier::complete_tx::bytes [%0], [%1], %2, [%3];"
               :: "r"(dst), "l"(src), "r"(bytes), "r"(bar) : "memory");
}
__device__ __forceinline__ void bulk_g2s_mc(uint32_t dst, const void* src, uint32_t bytes, uint32_t bar, uint16_t mask) {
  asm volatile("cp.async.bulk.shared::cluster.global.mbarrier::complete_tx::bytes.multicast::cluster [%0], [%1], %2, [%3], %4;"
               :: "r"(dst), "l"(src), "r"(bytes), "r"(bar), "h"(mask) : "memory");
}
__device__ __forceinline__ void bulk_s2s(uint32_t dst, uint32_t src, uint32_t bytes, uint32_t bar) {
  asm volatile("cp.async.bulk.shared::cluster.shared::cta.mbarrier::complete_tx::bytes [%0], [%1], %2, [%3];"
               :: "r"(dst), "r"(src), "r"(bytes), "r"(bar) : "memory");
}
__device__ __forceinline__ void bulk_s2g(void* dst, uint32_t src, uint32_t bytes) {
  asm volatile("cp.async.bulk.global.shared::cta.bulk_group [%0], [%1], %2;" :: "l"(dst), "r"(src), "r"(bytes) : "memory");
}
__device__ __forceinline__ void bulk_commit_wait() {
  asm volatile("cp.async.bulk.commit_group;\ncp.async.bulk.wait_group 0;" ::: "memory");
}
__device__ __forceinline__ void st_async4(uint32_t a, float x, float y, float z, float w, uint32_t bar) {
  asm volatile("st.async.shared::cluster.mbarrier::complete_tx::bytes.v4.f32 [%0], {%1,%2,%3,%4}, [%5];"
               :: "r"(a), "f"(x), "f"(y), "f"(z), "f"(w), "r"(bar) : "memory");
}
__device__ __forceinline__ bool elect_one() {
  uint32_t p; asm volatile("{\n.reg .pred p;\nelect.sync _|p, 0xffffffff;\nselp.u32 %0, 1, 0, p;\n}" : "=r"(p)); return p;
}
__device__ __forceinline__ void st_async2(uint32_t a, float x, float y, uint32_t bar) {
  asm volatile("st.async.shared::cluster.mbarrier::complete_tx::bytes.v2.f32 [%0], {%1,%2}, [%3];"
               :: "r"(a), "f"(x), "f"(y), "r"(bar) : "memory");
}
__device__ __forceinline__ void ldsm4(uint32_t& r0, uint32_t& r1, uint32_t& r2, uint32_t& r3, uint32_t a) {
  asm volatile("ldmatrix.sync.aligned.m8n8.x4.shared.b16 {%0,%1,%2,%3}, [%4];" : "=r"(r0), "=r"(r1), "=r"(r2), "=r"(r3) : "r"(a) : "memory");
}
__device__ __forceinline__ void ldsm4t(uint32_t& r0, uint32_t& r1, uint32_t& r2, uint32_t& r3, uint32_t a) {
  asm volatile("ldmatrix.sync.aligned.m8n8.x4.trans.shared.b16 {%0,%1,%2,%3}, [%4];" : "=r"(r0), "=r"(r1), "=r"(r2), "=r"(r3) : "r"(a) : "memory");
}
__device__ __forceinline__ void stsm4(uint32_t a, uint32_t r0, uint32_t r1, uint32_t r2, uint32_t r3) {
  asm volatile("stmatrix.sync.aligned.m8n8.x4.shared.b16 [%0], {%1,%2,%3,%4};" :: "r"(a), "r"(r0), "r"(r1), "r"(r2), "r"(r3) : "memory");
}
__device__ __forceinline__ void stsm4t(uint32_t a, uint32_t r0, uint32_t r1, uint32_t r2, uint32_t r3) {
  asm volatile("stmatrix.sync.aligned.m8n8.x4.trans.shared.b16 [%0], {%1,%2,%3,%4};" :: "r"(a), "r"(r0), "r"(r1), "r"(r2), "r"(r3) : "memory");
}
__device__ __forceinline__ float4 lds4f(uint32_t a) {
  float4 v; asm volatile("ld.shared.v4.f32 {%0,%1,%2,%3}, [%4];" : "=f"(v.x), "=f"(v.y), "=f"(v.z), "=f"(v.w) : "r"(a) : "memory"); return v;
}
__device__ __forceinline__ float2 lds2f(uint32_t a) {
  float2 v; asm volatile("ld.shared.v2.f32 {%0,%1}, [%2];" : "=f"(v.x), "=f"(v.y) : "r"(a) : "memory"); return v;
}
__device__ __forceinline__ uint32_t lds1(uint32_t a) {
  uint32_t v; asm volatile("ld.shared.u32 %0, [%1];" : "=r"(v) : "r"(a) : "memory"); return v;
}
__device__ __forceinline__ void sts4(uint32_t a, uint4 v) {
  asm volatile("st.shared.v4.u32 [%0], {%1,%2,%3,%4};" :: "r"(a), "r"(v.x), "r"(v.y), "r"(v.z), "r"(v.w) : "memory");
}
__device__ __forceinline__ void sts4f(uint32_t a, float x, float y, float z, float w) {
  asm volatile("st.shared.v4.f32 [%0], {%1,%2,%3,%4};" :: "r"(a), "f"(x), "f"(y), "f"(z), "f"(w) : "memory");
}
__device__ __forceinline__ void sts1(uint32_t a, uint32_t v) { asm volatile("st.shared.u32 [%0], %1;" :: "r"(a), "r"(v) : "memory"); }
__device__ __forceinline__ void mma16816(float (&d)[4], uint32_t a0, uint32_t a1, uint32_t a2, uint32_t a3, uint32_t b0, uint32_t b1) {
  asm volatile("mma.sync.aligned.m16n8k16.row.col.f32.bf16.bf16.f32 {%0,%1,%2,%3}, {%4,%5,%6,%7}, {%8,%9}, {%0,%1,%2,%3};"
               : "+f"(d[0]), "+f"(d[1]), "+f"(d[2]), "+f"(d[3]) : "r"(a0), "r"(a1), "r"(a2), "r"(a3), "r"(b0), "r"(b1));
}
__device__ __forceinline__ void mma1688(float (&d)[4], uint32_t a0, uint32_t a1, uint32_t b0) {
  asm volatile("mma.sync.aligned.m16n8k8.row.col.f32.bf16.bf16.f32 {%0,%1,%2,%3}, {%4,%5}, {%6}, {%0,%1,%2,%3};"
               : "+f"(d[0]), "+f"(d[1]), "+f"(d[2]), "+f"(d[3]) : "r"(a0), "r"(a1), "r"(b0));
}
__device__ __forceinline__ float rcp(float x) { float r; asm("rcp.approx.ftz.f32 %0, %1;" : "=f"(r) : "f"(x)); return r; }
__device__ __forceinline__ float sqr(float x) { float r; asm("sqrt.approx.f32 %0, %1;" : "=f"(r) : "f"(x)); return r; }
__device__ __forceinline__ float ex2(float x) { float r; asm("ex2.approx.ftz.f32 %0, %1;" : "=f"(r) : "f"(x)); return r; }

__host__ __device__ constexpr uint64_t mkdesc(uint32_t off, uint32_t lbo, uint32_t sbo, uint32_t sw) {
  return (uint64_t)((SB0 + off) >> 4) | ((uint64_t)(lbo >> 4) << 16) | ((uint64_t)(sbo >> 4) << 32) | ((uint64_t)sw << 62);
}
__device__ __forceinline__ void wg_fence() { asm volatile("wgmma.fence.sync.aligned;" ::: "memory"); }
__device__ __forceinline__ void wg_commit() { asm volatile("wgmma.commit_group.sync.aligned;" ::: "memory"); }
template <int N> __device__ __forceinline__ void wg_wait() { asm volatile("wgmma.wait_group.sync.aligned %0;" :: "n"(N) : "memory"); }
template <int N> __device__ __forceinline__ void reg_fence(float (&d)[N]) {
#pragma unroll
  for (int i = 0; i < N; i++) asm volatile("" : "+f"(d[i]) :: "memory");
}

#define F4(d, o) "+f"(d[o]), "+f"(d[o + 1]), "+f"(d[o + 2]), "+f"(d[o + 3])
template <int SC> __device__ __forceinline__ void wg_rs(float (&d)[12], const uint32_t* a, uint64_t db, int ob) {
  asm volatile("{\n.reg .pred p;\n.reg .b64 b;\nsetp.ne.b32 p, %17, 0;\nadd.s64 b, %16, %18;\n"
    "wgmma.mma_async.sync.aligned.m64n24k16.f32.bf16.bf16 {%0,%1,%2,%3,%4,%5,%6,%7,%8,%9,%10,%11}, {%12,%13,%14,%15}, b, p, 1, 1, 1;\n}\n"
    : F4(d, 0), F4(d, 4), F4(d, 8) : "r"(a[0]), "r"(a[1]), "r"(a[2]), "r"(a[3]), "l"(db), "n"(SC), "l"((uint64_t)ob));
}
template <int SC> __device__ __forceinline__ void wg_rs(float (&d)[16], const uint32_t* a, uint64_t db, int ob) {
  asm volatile("{\n.reg .pred p;\n.reg .b64 b;\nsetp.ne.b32 p, %21, 0;\nadd.s64 b, %20, %22;\n"
    "wgmma.mma_async.sync.aligned.m64n32k16.f32.bf16.bf16 {%0,%1,%2,%3,%4,%5,%6,%7,%8,%9,%10,%11,%12,%13,%14,%15}, {%16,%17,%18,%19}, b, p, 1, 1, 1;\n}\n"
    : F4(d, 0), F4(d, 4), F4(d, 8), F4(d, 12) : "r"(a[0]), "r"(a[1]), "r"(a[2]), "r"(a[3]), "l"(db), "n"(SC), "l"((uint64_t)ob));
}
template <int SC> __device__ __forceinline__ void wg_rs(float (&d)[20], const uint32_t* a, uint64_t db, int ob) {
  asm volatile("{\n.reg .pred p;\n.reg .b64 b;\nsetp.ne.b32 p, %25, 0;\nadd.s64 b, %24, %26;\n"
    "wgmma.mma_async.sync.aligned.m64n40k16.f32.bf16.bf16 {%0,%1,%2,%3,%4,%5,%6,%7,%8,%9,%10,%11,%12,%13,%14,%15,%16,%17,%18,%19}, {%20,%21,%22,%23}, b, p, 1, 1, 1;\n}\n"
    : F4(d, 0), F4(d, 4), F4(d, 8), F4(d, 12), F4(d, 16) : "r"(a[0]), "r"(a[1]), "r"(a[2]), "r"(a[3]), "l"(db), "n"(SC), "l"((uint64_t)ob));
}
template <int SC, int TB> __device__ __forceinline__ void wg_ss(float (&d)[8], uint64_t da, int oa, uint64_t db, int ob) {
  asm volatile("{\n.reg .pred p;\n.reg .b64 a, b;\nsetp.ne.b32 p, %10, 0;\nadd.s64 a, %8, %12;\nadd.s64 b, %9, %13;\n"
    "wgmma.mma_async.sync.aligned.m64n16k16.f32.bf16.bf16 {%0,%1,%2,%3,%4,%5,%6,%7}, a, b, p, 1, 1, 1, %11;\n}\n"
    : F4(d, 0), F4(d, 4) : "l"(da), "l"(db), "n"(SC), "n"(TB), "l"((uint64_t)oa), "l"((uint64_t)ob));
}
template <int SC, int TB> __device__ __forceinline__ void wg_ss(float (&d)[12], uint64_t da, int oa, uint64_t db, int ob) {
  asm volatile("{\n.reg .pred p;\n.reg .b64 a, b;\nsetp.ne.b32 p, %14, 0;\nadd.s64 a, %12, %16;\nadd.s64 b, %13, %17;\n"
    "wgmma.mma_async.sync.aligned.m64n24k16.f32.bf16.bf16 {%0,%1,%2,%3,%4,%5,%6,%7,%8,%9,%10,%11}, a, b, p, 1, 1, 1, %15;\n}\n"
    : F4(d, 0), F4(d, 4), F4(d, 8) : "l"(da), "l"(db), "n"(SC), "n"(TB), "l"((uint64_t)oa), "l"((uint64_t)ob));
}
template <int SC, int TB> __device__ __forceinline__ void wg_ss(float (&d)[16], uint64_t da, int oa, uint64_t db, int ob) {
  asm volatile("{\n.reg .pred p;\n.reg .b64 a, b;\nsetp.ne.b32 p, %18, 0;\nadd.s64 a, %16, %20;\nadd.s64 b, %17, %21;\n"
    "wgmma.mma_async.sync.aligned.m64n32k16.f32.bf16.bf16 {%0,%1,%2,%3,%4,%5,%6,%7,%8,%9,%10,%11,%12,%13,%14,%15}, a, b, p, 1, 1, 1, %19;\n}\n"
    : F4(d, 0), F4(d, 4), F4(d, 8), F4(d, 12) : "l"(da), "l"(db), "n"(SC), "n"(TB), "l"((uint64_t)oa), "l"((uint64_t)ob));
}
template <int SC, int TB> __device__ __forceinline__ void wg_ss(float (&d)[20], uint64_t da, int oa, uint64_t db, int ob) {
  asm volatile("{\n.reg .pred p;\n.reg .b64 a, b;\nsetp.ne.b32 p, %22, 0;\nadd.s64 a, %20, %24;\nadd.s64 b, %21, %25;\n"
    "wgmma.mma_async.sync.aligned.m64n40k16.f32.bf16.bf16 {%0,%1,%2,%3,%4,%5,%6,%7,%8,%9,%10,%11,%12,%13,%14,%15,%16,%17,%18,%19}, a, b, p, 1, 1, 1, %23;\n}\n"
    : F4(d, 0), F4(d, 4), F4(d, 8), F4(d, 12), F4(d, 16) : "l"(da), "l"(db), "n"(SC), "n"(TB), "l"((uint64_t)oa), "l"((uint64_t)ob));
}

template <int NB>
__device__ __forceinline__ void load_rows(uint32_t dst, const __nv_bfloat16* src, int pitch, int nrows, int tid, int nthr) {
  for (int i0 = tid; i0 < nrows * 8; i0 += nthr * NB) {
    uint4 v[NB];
#pragma unroll
    for (int u = 0; u < NB; u++) {
      const int i = i0 + u * nthr, r = i >> 3;
      if (i < nrows * 8) v[u] = __ldg((const uint4*)(src + (size_t)r * pitch + (i & 7) * 8));
    }
#pragma unroll
    for (int u = 0; u < NB; u++) {
      const int i = i0 + u * nthr, r = i >> 3;
      if (i < nrows * 8) sts4(dst + r * 128 + (((i & 7) ^ (r & 7)) << 4), v[u]);
    }
  }
}
template <int NK> __device__ __forceinline__ void load_afrags(uint32_t* a, uint32_t tile, int w, int lane) {
  int i = lane >> 3, r = lane & 7;
  uint32_t base = tile + ((i >> 1) * 8 + r) * 128 + (((2 * w + (i & 1)) ^ r) << 4);
#pragma unroll
  for (int kk = 0; kk < NK; kk++) ldsm4t(a[4 * kk], a[4 * kk + 1], a[4 * kk + 2], a[4 * kk + 3], base + kk * 2048);
}

constexpr uint32_t Q_WO = 0;
constexpr uint32_t Q_WL = 49152;
constexpr uint32_t Q_X = 61440;
constexpr uint32_t Q_GS = 9280;
constexpr uint32_t Q_STG = 154240;
constexpr uint32_t Q_SIN = 178816;
constexpr uint32_t Q_OX = 191616;
constexpr uint32_t Q_PX = 208000;
constexpr uint32_t Q_OB = 216192;
constexpr int Q_KR = 33;
constexpr uint32_t BARS = 228352;
constexpr uint32_t B_MEMOK = BARS;
constexpr uint32_t Q_REDO = BARS + 8;
constexpr uint32_t B_XFULL = BARS + 72;
constexpr uint32_t B_XEMPTY = BARS + 224;
constexpr uint32_t B_GCP = 220288;
constexpr uint32_t B_SM = BARS + 152;
constexpr uint32_t B_REF = BARS + 256;
constexpr uint32_t Q_SET = BARS + 360;
constexpr uint32_t Q_SEL = BARS + 304;
constexpr uint32_t Q_REF = BARS + 288;
constexpr uint32_t B_O = BARS + 168;
constexpr uint32_t B_P = BARS + 240;
constexpr uint32_t B_XS = BARS + 200;
constexpr uint32_t B_OXREADY = BARS + 184;
constexpr uint32_t B_OXFREE = BARS + 192;
constexpr uint32_t SM_BYTES = 2 * 2 * 1280, SX_BYTES = 2 * 3840;
constexpr int W_KR = 29;
constexpr uint32_t W_RING = 0;
constexpr uint32_t W_WS = 196608;
constexpr uint32_t W_FT = 0;
constexpr uint32_t W_FO = 18688;
constexpr uint32_t W_RS = 49152;
constexpr uint32_t W_ST = 40960;
constexpr int CT_A = 2, CT_B = 6, CT_C = 11;
static_assert(36 * CT_C <= 36 * CT_B + 192, "kv stages");
constexpr uint32_t C_U = 256 + 4096;
constexpr uint32_t C_CH = C_U + 64 + 8192 + 96;
constexpr uint32_t B_FULL = BARS;
constexpr uint32_t B_EMPTY = BARS + 128;
constexpr uint32_t B_FT = BARS + 160;
constexpr uint32_t Q_M0 = BARS + 256;
constexpr uint32_t SMEM_TOTAL = BARS + 896 + 3072;

struct Params {
  const __nv_bfloat16 *x0, *wq, *wk, *wv, *wo, *mem0, *ck, *cv, *shift, *ssm_k, *ssm_d;
  __nv_bfloat16* out;
  uint4 *part, *memx;
  uint64_t d_x, d_wl, d_qk, d_wo, d_ob, d_ring, d_ws;
};

#define g_flags (g_flagsets + lds1(sb + Q_SET))

__device__ __forceinline__ int rd_cid() { uint32_t v; asm volatile("mov.u32 %0, %%clusterid.x;" : "=r"(v)); return v; }
__device__ __forceinline__ int rd_rank() { uint32_t v; asm volatile("mov.u32 %0, %%cluster_ctarank;" : "=r"(v)); return v; }
__device__ __forceinline__ int rd_lane() { uint32_t v; asm volatile("mov.u32 %0, %%laneid;" : "=r"(v)); return v; }
__device__ __forceinline__ int rd_warp() { uint32_t v; asm volatile("mov.u32 %0, %%tid.x;" : "=r"(v)); return __shfl_sync(0xffffffffu, v >> 5, 0); }

template <int TRIG, int NA>
__device__ __forceinline__ void proj_pass(float (&acc)[NA], const uint32_t* a, uint32_t sb, uint64_t db, uint64_t dwl, bool wait, uint32_t par, int lane, int t) {
#pragma unroll
  for (int k = 0; k < 36; k++) {
    if (TRIG >= 0 && k % 4 == 0) {
      if (wait) {
        mbar_wait(sb + B_GCP + 2 * k, par);
        if (k == 0) PROF_T(0);
        if (k == 4 * TRIG) mbar_arrive_if0(lane, sb + B_XEMPTY);
      }
      wg_fence();
    }
    if (k == 0) { if (TRIG < 0) wg_fence(); wg_rs<0>(acc, a, db, 0); }
    else if (k % 12 != 11) wg_rs<1>(acc, a + 4 * (k - k / 12), db, 16 * k);
    else wg_ss<1, 1>(acc, dwl, 128 * (k / 12), db, 16 * k);
  }
  wg_commit();
}
__device__ __forceinline__ void wo_tile(const Params& P, uint64_t da, uint32_t pof, int i) {
  float d[8];
  wg_fence();
  wg_ss<0, 0>(d, da, 0, P.d_ob, 0);
#pragma unroll
  for (int k = 1; k < 8; k++) wg_ss<1, 0>(d, da, 128 * k, P.d_ob, 16 * k);
  wg_commit();
  uint4* dst = (uint4*)((char*)P.part + ((pof & ~15u) + ((pof << (11 - i)) & 4096) + i * 8192));
  asm volatile("" : "+l"(dst));
  wg_wait<0>();
  reg_fence(d);
  st_gpu4(dst, pack_bf16(d[0], d[1]), pack_bf16(d[4], d[5]), pack_bf16(d[2], d[3]), pack_bf16(d[6], d[7]));
}
template <bool ISV>
__device__ __forceinline__ void head_loop(uint32_t sb, const Params& P, const uint32_t* a, int lane, int w, int wg, int rank, uint32_t pof) {
  constexpr int NG = ISV ? 5 : 3;
  const uint64_t dwl = P.d_wl + wg * 384;
  const uint32_t stg = sb + Q_STG + wg * 12288 + 2 * w * 768;
  const uint32_t stm = stg + (lane >> 4) * 6144 + ((lane >> 3) & 1) * 768 + (lane & 7) * 16;
#pragma unroll 1
  for (int t = 0; t <= NT; t++) {
    const uint32_t par = t & 1;
    uint32_t pk[2 * NG - 4] = {};
    float m[4 * NG];
    mbar_wait(sb + B_XFULL, par);
#pragma unroll 1
    for (int pass = 0;; pass++) {
      proj_pass<ISV ? X_TRIGV : 9>(m, a, sb, P.d_x + (pass == 2 ? NG * (Q_GS / 16) : 0), dwl, pass == 0, par, lane, t);
      bool redo = false;
      if (pass == 0) { mbar_wait(sb + B_MEMOK, par); redo = __any_sync(0xffffffffu, lds1(sb + Q_REDO) == t); }
      wg_wait<0>();
      reg_fence(m);
      if (pass == 2) break;
      if (redo) continue;
      pass = 1;
      PROF_T(2);
      stsm4(stm, pack_bf16(m[0], m[1]), pack_bf16(m[2], m[3]), pack_bf16(m[4], m[5]), pack_bf16(m[6], m[7]));
      if (ISV) { if (t > 0) bar_arrive<6, 384>(); } else fence_async_smem();
#pragma unroll
      for (int i = 0; i < 2 * NG - 4; i++) pk[i] = pack_bf16(m[8 + 2 * i], m[9 + 2 * i]);
      if (ISV) {
        mbar_arrive_if0(lane, sb + B_XEMPTY + 8);
        if (t > 0) {
          pof ^= 2048;
          uint64_t da = P.d_wo + (1 - wg) * 1024;
#pragma unroll 1
          for (int i = 1 - wg; i < 3; i += 2, da += 2048) {
            mbar_wait(sb + B_O, par ^ 1);
            if (i < 2) PROF_T(14);
            wo_tile(P, da, pof, i);
          }
          if (wg) PROF_T(15);
          bar_sync<2, 384>();
        }
        mbar_wait(sb + B_XFULL + 8, par);
      } else {
        if (t > 0) {
          bar_sync<6, 288>();
          float s[20];
          const uint64_t dq = P.d_qk + wg * 384;
          wg_fence();
          wg_ss<0, 1>(s, dq, 0, dq, 768);
#pragma unroll
          for (int i = 1; i < 4; i++) wg_ss<1, 1>(s, dq, 96 * i, dq, 768 + 96 * i);
          wg_commit();
          const uint32_t sd0 = mapa(sb + Q_SIN + (rank * 5 + (w ? 2 * w : wg)) * 1280 + lane * 16, w ? wg : 2), sb0 = mapa(sb + B_SM, w ? wg : 2);
          wg_wait<0>();
          reg_fence(s);
          if (w < 3) {
            if (w) bar_sync<4, 192>();
            st_async4(sd0, s[0], s[1], s[4], s[5], sb0);
            st_async4(sd0 + 512, s[8], s[9], s[12], s[13], sb0);
            if (w != 1) st_async2(sd0 + 1024 - lane * 8, s[16], s[17], sb0);
            if (w == 0) { PROF_T(4); bar_sync<4, 192>(); }
            if (w < 2) {
              const uint32_t sd1 = mapa(sb + Q_SIN + (rank * 5 + 2 * w + 1) * 1280 + lane * 16, wg), sb1 = mapa(sb + B_SM, wg);
              st_async4(sd1, s[2], s[3], s[6], s[7], sb1);
              if (w == 1) st_async4(sd1 + 512, s[10], s[11], s[14], s[15], sb1);
            }
          }
        }
        mbar_arrive_if0(lane, sb + B_XEMPTY);
      }
    }
    if (ISV) {
      PROF_T(10);
#pragma unroll
      for (int h = 0; h < 2; h++) {
        stsm4(stg + h * 768 + 128 + lane * 16, pk[h], pk[(2 + h) % (2 * NG - 4)], pk[(4 + h) % (2 * NG - 4)], pack_bf16(m[2 * h], m[2 * h + 1]));
        stsm4(stg + 6144 + h * 768 + 128 + lane * 16, pack_bf16(m[4 + 2 * h], m[5 + 2 * h]), pack_bf16(m[8 + 2 * h], m[9 + 2 * h]),
              pack_bf16(m[(12 + 2 * h) % (4 * NG)], m[(13 + 2 * h) % (4 * NG)]), pack_bf16(m[(16 + 2 * h) % (4 * NG)], m[(17 + 2 * h) % (4 * NG)]));
      }
      if (t < NT) bar_arrive<7, 384>();
    } else {
      PROF_T(6);
#pragma unroll
      for (int h = 0; h < 2; h++)
        stsm4(stg + h * 768 + 128 + lane * 16, pk[h], pack_bf16(m[2 * h], m[2 * h + 1]), pack_bf16(m[4 + 2 * h], m[5 + 2 * h]), pack_bf16(m[8 + 2 * h], m[9 + 2 * h]));
      if (t > 0) {
        pof ^= 2048;
        uint64_t da = P.d_wo + (1 - wg) * 1024;
#pragma unroll 1
        for (int i = 1 - wg; i < 4; i += 2, da += 2048) {
          if (i < 3) {
            mbar_wait(sb + B_O, par ^ 1);
            if (i < 2) PROF_T(14);
            wo_tile(P, da, pof, i);
            if (i == 2) PROF_T(15);
          }
          bar_sync<1, 256>();
        }
      }
      mbar_arrive_if0(lane, sb + B_XEMPTY + 8);
      float e[16];
      mbar_wait(sb + B_XFULL + 8, par);
      proj_pass<-1>(e, a, sb, P.d_x + 6 * (Q_GS / 16), dwl, false, par, lane, t);
      wg_wait<0>();
      reg_fence(e);
      PROF_T(10);
#pragma unroll
      for (int h = 0; h < 2; h++)
        stsm4(stg + 6144 + h * 768 + 128 + lane * 16, pack_bf16(e[2 * h], e[2 * h + 1]), pack_bf16(e[4 + 2 * h], e[5 + 2 * h]),
              pack_bf16(e[8 + 2 * h], e[9 + 2 * h]), pack_bf16(e[12 + 2 * h], e[13 + 2 * h]));
    }
    PROF_T(12);
  }
}
__device__ __forceinline__ void head_main(uint32_t sb, const Params& P) {
  const int lane = threadIdx.x & 31, warp = rd_warp(), w = warp & 3, wg = warp >> 2, rank = rd_rank();
  load_rows<35>(sb + Q_X + wg * 71680, (rank == 2 ? P.wv + wg * 64 : (wg ? P.wk : P.wq) + rank * 64) + rd_cid() * 128, 4096, 560, threadIdx.x & 127, 128);
  bar_sync_r(8 + wg, 128);
  PROF_G(7);
  uint32_t a[4 * Q_KR];
#pragma unroll
  for (int i = 0; i < 3; i++) load_afrags<11>(a + 44 * i, sb + Q_X + wg * 71680 + i * 24576, w, lane);
  uint32_t pof;
  {
    const int dcta = (w * 8 + (lane >> 2)) * 3 + rank;
    uint4 f;
    uint32_t n = 0;
    do {
      f = ld_poll((const uint4*)(g_flags + FL_SEL) + dcta);
      if (++n > SPIN_LIMIT) __trap();
    } while (__any_sync(0xffffffffu, !f.x || !f.y || !f.z));
    pof = (dcta * 1536 + rd_cid() * 4 + (lane & 3)) * 16 | (f.x - 1) << 1 | (f.y - 1) << 2 | (f.z - 1) << 3;
  }
  fence_async_smem();
  cluster_sync();
  PROF_G(8);
  if (rank == 2) head_loop<true>(sb, P, a, lane, w, wg, rank, pof); else head_loop<false>(sb, P, a, lane, w, wg, rank, pof);
  cluster_sync();
}

__device__ __forceinline__ uint32_t ref_time(uint32_t sb, int t) {
  mbar_wait(sb + B_REF, t & 1);
  return lds1(sb + Q_REF);
}
__device__ __forceinline__ uint32_t next_tick() {
  uint64_t g0, g1;
  asm volatile("mov.u64 %0, %%globaltimer;" : "=l"(g0) :: "memory");
#pragma unroll 1
  for (int n = 0; n < 8; n++) {
    asm volatile("mov.u64 %0, %%globaltimer;" : "=l"(g1) :: "memory");
    if (__any_sync(0xffffffffu, (uint32_t)g1 != (uint32_t)g0)) break;
  }
  return (uint32_t)g1;
}
__device__ __forceinline__ uint32_t poll4(uint4 (&v)[4], const uint4* src) {
#pragma unroll
  for (int j = 0; j < 4; j++) v[j] = ld_poll(src + j * 32);
  uint32_t n = 0;
  while (__any_sync(0xffffffffu, max(__vimax3_u32(v[0].x, v[1].x, v[2].x), v[3].x) == SENT)) {
#pragma unroll
    for (int j = 0; j < 4; j++) if (v[j].x == SENT) v[j] = ld_poll(src + j * 32);
    if (++n > SPIN_LIMIT) __trap();
  }
  return n;
}

__device__ __forceinline__ void load_scores(float (&s)[10], uint32_t sa, int lane) {
  const uint32_t sb2 = sa + 6400;
  const float4 a0 = lds4f(sa), a1 = lds4f(sa + 512), b0 = lds4f(sb2), b1 = lds4f(sb2 + 512);
  const float2 a2 = lds2f(sa + 1024 - lane * 8), b2 = lds2f(sb2 + 1024 - lane * 8);
  s[0] = a0.x + b0.x; s[1] = a0.y + b0.y; s[2] = a0.z + b0.z; s[3] = a0.w + b0.w;
  s[4] = a1.x + b1.x; s[5] = a1.y + b1.y; s[6] = a1.z + b1.z; s[7] = a1.w + b1.w;
  s[8] = a2.x + b2.x; s[9] = a2.y + b2.y;
}
__device__ __forceinline__ float softmax_num(float (&s)[10]) {
  float mx = fmaxf(fmaxf(fmaxf(s[0], s[1]), fmaxf(s[2], s[3])), fmaxf(fmaxf(s[4], s[5]), fmaxf(s[6], s[7])));
  mx = fmaxf(mx, fmaxf(s[8], s[9]));
  mx = fmaxf(mx, __shfl_xor_sync(0xffffffffu, mx, 1));
  mx = fmaxf(mx, __shfl_xor_sync(0xffffffffu, mx, 2));
  mx *= -SM_SCALE;
#pragma unroll
  for (int i = 0; i < 10; i++) s[i] = ex2(fmaf(s[i], SM_SCALE, mx));
  return ((s[0] + s[1]) + (s[2] + s[3])) + ((s[4] + s[5]) + (s[6] + s[7])) + (s[8] + s[9]);
}

__device__ __forceinline__ void head_aux(uint32_t sb, const Params& P) {
  const int tid = threadIdx.x & 127, w = rd_warp() & 3, rank = rd_rank(), head = __shfl_sync(0xffffffffu, rd_cid(), 0);
  {
    uint4 v[6];
#pragma unroll
    for (int i = 0; i < 6; i++)
      v[i] = __ldg((const uint4*)((rank == 2 ? P.wv + (i / 3) * 64 : (i < 3 ? P.wq : P.wk) + rank * 64) + head * 128 +
                                  (size_t)((i % 3) * 192 + 176 + (tid >> 3)) * 4096 + (tid & 7) * 8));
#pragma unroll 1
    for (int i = 0; i < 3; i++) {
      uint4 a[4], b[4];
#pragma unroll
      for (int u = 0; u < 4; u++) {
        const int r = u * 32 + (tid >> 2);
        const uint4* src = (const uint4*)(P.wo + (size_t)(head * 128 + (r & 64) + (r & 7) * 8 + ((r >> 3) & 7)) * DM + (rank == 2 ? i : 4 - rank + 2 * i) * 64) + (tid & 3) * 2;
        a[u] = __ldg(src); b[u] = __ldg(src + 1);
      }
#pragma unroll
      for (int u = 0; u < 4; u++) {
        const int r = u * 32 + (tid >> 2);
        const uint32_t dst = sb + Q_WO + i * 16384 + r * 128 + ((((tid & 3) * 2) ^ (r & 7) ^ ((head >> 2) & 1)) << 4);
        sts4(dst, make_uint4(__byte_perm(a[u].x, a[u].y, 0x5410), __byte_perm(a[u].z, a[u].w, 0x5410), __byte_perm(b[u].x, b[u].y, 0x5410), __byte_perm(b[u].z, b[u].w, 0x5410)));
        sts4(dst ^ 16, make_uint4(__byte_perm(a[u].x, a[u].y, 0x7632), __byte_perm(a[u].z, a[u].w, 0x7632), __byte_perm(b[u].x, b[u].y, 0x7632), __byte_perm(b[u].z, b[u].w, 0x7632)));
      }
    }
#pragma unroll
    for (int i = 0; i < 6; i++) sts4(sb + Q_WL + i * 2048 + (tid >> 3) * 128 + (((tid & 7) ^ ((tid >> 3) & 7)) << 4), v[i]);
  }
  fence_async_smem();
  PROF_G(2);
  cluster_sync();
  mbar_wait(sb + B_XEMPTY + 8, 0);
#pragma unroll 1
  for (int t = 1; t <= NT; t++) {
    const uint32_t par = (t - 1) & 1;
    {
      const int lane = rd_lane();
      mbar_expect_if0(lane > 2 || w + 4 * lane > 8, sb + B_GCP + 8 * (w + 4 * lane), 2048);
#pragma unroll 1
      for (int c = w; c < 9; c += 4) {
        const uint32_t chk = sb + Q_X + c * 1024 + lane * 32 + (lane >> 2) * 4;
        mbar_wait(sb + B_GCP + 8 * c, par ^ 1);
        PROF_T(c == 0 ? 1 : c == 1 ? 3 : c == 2 ? 5 : c < 6 ? 13 + c : c == 6 ? 13 : c == 7 ? 7 : 21);
        const bool k = __any_sync(0xffffffffu, max(__vimax3_u32(lds1(chk), lds1(chk + Q_GS), lds1(chk ^ 16)), lds1((chk ^ 16) + Q_GS)) == SENT);
        if (k) {
          uint4 v[4];
          poll4(v, P.memx + c * 512 + (t & 1) * 128 + lds1(sb + Q_SEL + 4 * c) / 16 + lane);
#pragma unroll
          for (int j = 0; j < 4; j++) sts4(sb + Q_X + c * 1024 + (j >> 1) * Q_GS + (j & 1) * 512 + lane * 16, v[j]);
          fence_async_smem();
          sts1(sb + Q_REDO, t);
          __syncwarp();
        }
        PROF_A(c, (uint32_t)k);
      }
      mbar_arrive_if0(lane, sb + B_MEMOK);
    }
    if (rank == 2) {
      uint32_t vf[4][10], p[5];
      float s[10], o[4][4];
      const int lane = rd_lane(), l = w & 1, tile = w >> 1;
      const uint32_t ob = sb + Q_OB + (l ^ ((head >> 1) & 1)) * 2048 + tile * 1024;
      const uint32_t obl = ob + (lane >> 2) * 128 + (lane & 3) * 16;
      const uint32_t vb = sb + Q_STG + tile * 12288 + l * 6144 + (lane & 7) * 16;
      const uint32_t ax = vb + ((lane >> 3) & 1) * 768 + (lane >> 4) * 128 + 128;
      bar_sync<7, 384>();
      if (!OXF_LATE) mbar_wait(sb + B_OXFREE, par ^ 1);
#pragma unroll
      for (int i = 0; i < 4; i++) {
        ldsm4(vf[i][0], vf[i][1], vf[i][2], vf[i][3], ax + i * 1536);
        ldsm4(vf[i][4], vf[i][5], vf[i][6], vf[i][7], ax + i * 1536 + 256);
      }
      bar_sync<6, 384>();
      ldsm4(vf[0][8], vf[0][9], vf[1][8], vf[1][9], vb + (lane >> 3) * 768);
      ldsm4(vf[2][8], vf[2][9], vf[3][8], vf[3][9], vb + (lane >> 3) * 768 + 3072);
      mbar_wait(sb + B_SM, par);
      PROF_T(20);
      load_scores(s, sb + Q_SIN + l * 1280 + lane * 16, lane);
      const float sum = softmax_num(s);
#pragma unroll
      for (int j = 0; j < 5; j++) p[j] = pack_bf16(s[2 * j], s[2 * j + 1]);
      float z[4] = {0.f, 0.f, 0.f, 0.f};
#pragma unroll
      for (int i = 0; i < 4; i++) { o[i][0] = o[i][1] = o[i][2] = o[i][3] = 0.f; mma16816(o[i], vf[i][0], vf[i][1], vf[i][2], vf[i][3], p[1], p[2]); }
      const float shi = __uint_as_float(__float_as_uint(sum) & 0xFFFF0000u);
      mma1688(z, 0x3F803F80u, 0x3F803F80u, pack_bf16(sum - shi, shi));
#pragma unroll
      for (int i = 0; i < 4; i++) mma1688(o[i], vf[i][8], vf[i][9], p[0]);
#pragma unroll
      for (int i = 0; i < 4; i++) mma16816(o[i], vf[i][4], vf[i][5], vf[i][6], vf[i][7], p[3], p[4]);
      const float r0 = rcp(z[0]), r1 = rcp(z[1]);
      const uint4 u0 = make_uint4(pack_bf16(o[0][0] * r0, o[0][2] * r0), pack_bf16(o[1][0] * r0, o[1][2] * r0),
                                  pack_bf16(o[2][0] * r0, o[2][2] * r0), pack_bf16(o[3][0] * r0, o[3][2] * r0));
      const uint4 u1 = make_uint4(pack_bf16(o[0][1] * r1, o[0][3] * r1), pack_bf16(o[1][1] * r1, o[1][3] * r1),
                                  pack_bf16(o[2][1] * r1, o[2][3] * r1), pack_bf16(o[3][1] * r1, o[3][3] * r1));
      PROF_T(8);
      sts4(obl, u0);
      sts4(obl + 64, u1);
      fence_async_smem();
      __syncwarp();
      mbar_arrive_if0(lane, sb + B_O);
      if (elect_one()) {
        bulk_s2s(mapa(ob, 1), ob, 1024, mapa(sb + B_O, 1));
        bulk_s2s(mapa(ob, 0), ob, 1024, mapa(sb + B_O, 0));
      }
      mbar_expect_if0(lane | w, sb + B_SM, SM_BYTES);
      mbar_wait(sb + B_P + 8 * par, ((t - 1) >> 1) & 1);
      if (OXF_LATE) mbar_wait(sb + B_OXFREE, par ^ 1);
      PROF_T(9);
      const uint32_t pp = sb + Q_PX + par * 4096 + l * 2048 + lane * 16;
      const uint32_t ox = sb + Q_OX + l * 8192 + tile * 4096 + (lane >> 3) * 512 + (lane & 7) * 16;
      uint32_t q[16];
      q[0] = lds1(pp - lane * 12);
      ldsm4(q[4], q[5], q[6], q[7], pp + 512);
#pragma unroll
      for (int g = 0; g < 4; g++) {
        const int b = g < 2 ? 4 + 2 * g : 4 * g;
#pragma unroll
        for (int i = 0; i < 4; i++) { o[i][0] = o[i][1] = o[i][2] = o[i][3] = 0.f; mma1688(o[i], vf[i][8], vf[i][9], q[g]); }
#pragma unroll
        for (int i = 0; i < 4; i++) mma16816(o[i], vf[i][0], vf[i][1], vf[i][2], vf[i][3], q[b], q[b + 1]);
        if (g >= 2) {
#pragma unroll
          for (int i = 0; i < 4; i++) mma16816(o[i], vf[i][4], vf[i][5], vf[i][6], vf[i][7], q[b + 2], q[b + 3]);
        }
        if (g == 3) bar_arrive<2, 384>();
        stsm4(ox + g * 128, pack_bf16(o[0][0], o[0][1]), pack_bf16(o[0][2], o[0][3]), pack_bf16(o[1][0], o[1][1]), pack_bf16(o[1][2], o[1][3]));
        if (g < 3) q[g + 1] = lds1(pp - lane * 12 + (g + 1) * 128);
        if (g == 1 || g == 2) ldsm4(q[4 * g + 4], q[4 * g + 5], q[4 * g + 6], q[4 * g + 7], pp + (g + 1) * 512);
        stsm4(ox + g * 128 + 2048, pack_bf16(o[2][0], o[2][1]), pack_bf16(o[2][2], o[2][3]), pack_bf16(o[3][0], o[3][1]), pack_bf16(o[3][2], o[3][3]));
      }
      fence_async_smem();
      __syncwarp();
      mbar_arrive_if0(lane, sb + B_OXREADY);
      PROF_T(23);
    } else {
      float s[10];
      const int lane = rd_lane();
      const uint32_t pd = mapa(sb + Q_PX + par * 4096 + rank * 2048 + w * 128 + lane * 4, 2), pb = mapa(sb + B_P + 8 * par, 2);
      mbar_wait(sb + B_SM, par);
      PROF_T(20);
      load_scores(s, sb + Q_SIN + (w + 1) * 1280 + lane * 16, lane);
      const int last = 8 + 8 * w + (lane >> 2) - 2 * (lane & 3);
#pragma unroll
      for (int i = 2; i < 10; i++) s[i] = (8 * (i >> 1) + (i & 1) <= last) ? s[i] : -INFINITY;
      float sum = softmax_num(s);
      sum += __shfl_xor_sync(0xffffffffu, sum, 1);
      sum += __shfl_xor_sync(0xffffffffu, sum, 2);
      const float r = rcp(sum);
#pragma unroll
      for (int j = 0; j < 5; j++)
        if (j < 3 || w >= 2) asm volatile("st.async.shared::cluster.mbarrier::complete_tx::bytes.b32 [%0], %1, [%2];"
                     :: "r"(j ? pd + (w < 2 ? 3 + w : 3 * w - 1) * 128 + j * 128 : pd), "r"(pack_bf16(s[2 * j] * r, s[2 * j + 1] * r)), "r"(pb) : "memory");
      PROF_T(22);
      mbar_arrive_if0(lane, sb + B_XS);
      mbar_expect_if0(lane | w, sb + B_SM, SX_BYTES);
      mbar_wait(sb + B_O, par);
      mbar_expect_if0(lane | w, sb + B_O, 4096);
    }
  }
  cluster_sync();
}

__device__ __forceinline__ void head_producer(uint32_t sb) {
  const int rank = rd_rank(), head = __shfl_sync(0xffffffffu, rd_cid(), 0), ne = rank == 2 ? 3 : 4;
  cluster_sync();
  uint32_t* fl = g_flags + FL_XS;
#pragma unroll 1
  for (int h = -1; h <= 2 * NT + 2; h++) {
    const int t = h >> 1, e = h & 1;
    if (t + e <= NT) {
      if (e ? t < NSEG : t >= LAG) warp_flag_wait(fl + (h + 1) * 16, 4);
      fence_async_global();
      const uint4* src = g_xs + (t * 8 + (e ? 8 : ne)) * 580;
      const uint32_t bytes = (e ? ne : 8 - ne) * Q_GS, dst = sb + Q_X + (e ? 2 : 2 + ne) * Q_GS, bar = sb + B_XFULL + 8 - 8 * e;
      if (h > 0) mbar_wait(sb + B_XEMPTY + 8 * e, t & 1);
      if (elect_one()) { mbar_expect(bar, bytes); bulk_g2s(dst, src, bytes, bar); }
      if (!e) { PROF_T(24); PROF_MID(); }
      if (h < 0) PROF_G(31);
    }
    if (rank == 2 && !e && t > 1) {
      mbar_wait(sb + B_OXREADY, t & 1);
      if (elect_one()) {
        mbar_expect(sb + B_P + 8 * (t & 1), 4096);
        uint4* od = g_ox + (size_t)((t - 1) & (OXRING - 1)) * 32768 + head * 512;
        if (t - 1 <= NSEG) bulk_s2g(od, sb + Q_OX, 8192);
        if (t - 1 > LAG) bulk_s2g(od + 16384, sb + Q_OX + 8192, 8192);
        bulk_commit_wait();
        mbar_arrive(sb + B_OXFREE);
        flag_add(fl + FL_OX - FL_XS + (t - 1) * 32 + head);
      }
      __syncwarp();
      PROF_T(25);
    }
  }
  cluster_sync();
}

__device__ __forceinline__ uint32_t bf2_op(uint32_t a, uint32_t b, uint32_t c) {
  uint32_t r; asm("fma.rn.bf16x2 %0, %1, %2, %3;" : "=r"(r) : "r"(a), "r"(b), "r"(c)); return r;
}
__device__ __forceinline__ uint32_t bf2_mul(uint32_t a, uint32_t b) {
  uint32_t r; asm("mul.rn.bf16x2 %0, %1, %2;" : "=r"(r) : "r"(a), "r"(b)); return r;
}
__device__ __forceinline__ uint32_t bf2_add(uint32_t a, uint32_t b) {
  uint32_t r; asm("add.rn.bf16x2 %0, %1, %2;" : "=r"(r) : "r"(a), "r"(b)); return r;
}
__device__ __forceinline__ void head_reducer(uint32_t sb, const Params& P) {
  const int lane = threadIdx.x & 31, rank = rd_rank(), i3 = rd_warp() - 13;
  const int head = rd_cid(), c = rank == 2 ? i3 : 4 - rank + 2 * i3;
  uint32_t dof = c * 8192 + (lane & 4) * 1024 + (lane & 8) * 128 + head * 32 + (lane & 16) + (lane & 3) * 4;
  uint32_t sof = (blockIdx.x * 3 + i3) * 8192;
  sof += __shfl_sync(0xffffffffu, lds1(sb + Q_SEL + 36 + 4 * i3), 0);
#pragma unroll 1
  for (int j = 0; j < 8; j++) st_gpu4((uint4*)((char*)P.part + sof) + j * 32 + lane, SENT, SENT, SENT, SENT);
  PROF_G(0);
  warp_flag_wait(g_flags + FL_INIT, 288);
  PROF_G(1);
  uint32_t when = rd_clock();
  if (i3 == 0) { sts1(sb + Q_REF + 4, next_tick()); sts1(sb + Q_REF, when - 8192); }
  mbar_arrive_if0(lane | i3, sb + B_REF);
  asm volatile("st.release.gpu.global.u32 [%0], %1;" :: "l"(g_flags + FL_SEL + blockIdx.x * 4 + i3), "r"(((sof >> 12) & 1) + 1) : "memory");
  cluster_sync();
  const uint32_t gof = c * 8192 + __shfl_sync(0xffffffffu, lds1(sb + Q_SEL + 4 * c), 0);
#pragma unroll 1
  for (int t = 1; t <= NT; t++) {
    {
      const char* gs = (const char*)P.memx + gof + (t & 1) * 2048;
      fence_async_global();
      spin_until(when);
      if (elect_one()) {
        bulk_g2s_mc(sb + Q_X + c * 1024, gs, 1024, sb + B_GCP + 8 * c, 7);
        bulk_g2s_mc(sb + Q_X + c * 1024 + Q_GS, gs + 1024, 1024, sb + B_GCP + 8 * c, 7);
      }
    }
    {
      uint4* old = (uint4*)((char*)P.part + sof) + lane;
#pragma unroll
      for (int j = 0; j < 4; j++) st_gpu4(old + j * 32, SENT, SENT, SENT, SENT);
    }
    sof ^= 2048;
    const uint4* src = (const uint4*)((const char*)P.part + sof);
    uint4 v[4];
    if (i3 == 0) {
      const uint32_t g0 = next_tick(), c0 = rd_clock();
      uint2* tms = (uint2*)(P.memx + 9 * 512);
      uint32_t* pub = (uint32_t*)(tms + (rd_lane() & 1) * 512 + head) + rank;
      tms += lds1(sb + Q_SEL + 48) / 8 + lane;
      if (rank != 2) {
        bar_sync<6, 288>();
        spin_until(c0);
        st_gpu1(pub, g0 + ((rd_clock() - c0) * 9 >> 4));
      }
      mbar_wait(sb + B_SM, (t - 1) & 1);
      int d0, d1;
      uint32_t n = 0, gref = lds1(sb + Q_REF + 4);
      do {
        asm volatile("ld.relaxed.gpu.global.v2.u32 {%0,%1}, [%2];" : "=r"(d0), "=r"(d1) : "l"(tms) : "memory");
        d0 -= gref; d1 -= gref;
        if (++n > SPIN_LIMIT) __trap();
      } while (__any_sync(0xffffffffu, min(d0, d1) <= 0));
      gref += __reduce_max_sync(0xffffffffu, max(d0, d1));
      sts1(sb + Q_REF, c0 + (min((int)(gref - g0), 4096) * 29 >> 4));
      sts1(sb + Q_REF + 4, gref);
      mbar_arrive_if0(lane, sb + B_REF);
      PROF_T(19);
    }
    if (t == NT) break;
    when = ref_time(sb, t) + red_delay(c);
    if (rank != 2) mbar_wait(sb + B_XS, (t - 1) & 1);
    uint32_t* dst = (uint32_t*)((char*)P.memx + dof);
    const bool inj = t == LAG && (lane & 8);
    if (t == LAG) st_gpu1_if(inj, dst, lds1(sb + Q_M0 + (i3 * 32 + 32 + rd_lane()) * 4));
    src += lane;
    asm volatile("" : "+l"(dst), "+l"(src));
    spin_until(when);
    const uint32_t nr = poll4(v, src);
    PROF_T(26 + i3);
    PROF_V(i3 == 0, 11, when);
    const uint32_t z = bf2_add(bf2_add(v[0].z, v[1].z), bf2_add(v[2].z, v[3].z)), u = bf2_add(bf2_add(v[0].w, v[1].w), bf2_add(v[2].w, v[3].w));
    const uint32_t x = bf2_add(bf2_add(v[0].x, v[1].x), bf2_add(v[2].x, v[3].x)), y = bf2_add(bf2_add(v[0].y, v[1].y), bf2_add(v[2].y, v[3].y));
    const uint32_t x2 = __shfl_xor_sync(0xffffffffu, z, 16), y2 = __shfl_xor_sync(0xffffffffu, u, 16);
    float f0 = bf_lo(x) + bf_lo(x2), f1 = bf_hi(x) + bf_hi(x2);
    f0 += __shfl_xor_sync(0xffffffffu, bf_lo(y) + bf_lo(y2), 8);
    f1 += __shfl_xor_sync(0xffffffffu, bf_hi(y) + bf_hi(y2), 8);
    f0 += __shfl_xor_sync(0xffffffffu, f0, 4);
    f1 += __shfl_xor_sync(0xffffffffu, f1, 4);
    st_gpu1_if(!inj, dst, pack_bf16(f0, f1));
    when += D_GX;
    PROF_T(29 + i3);
    PROF_A(10 + i3, nr);
    dof ^= 2048;
    st_gpu1((uint32_t*)((char*)P.memx + dof), SENT);
  }
  cluster_sync();
}

__global__ void __cluster_dims__(3, 1, 1) __launch_bounds__(512, 1) head_kernel(const Params P) {
  extern __shared__ uint8_t smem_raw[];
  const uint32_t sb = (uint32_t)__cvta_generic_to_shared(smem_raw);
  if ((sb & 0xFFFFFFu) != SB0) __trap();
  asm volatile("griddepcontrol.launch_dependents;");
  if (threadIdx.x < 96) {
    const int i = blockIdx.x * 24 + threadIdx.x % 24, m = threadIdx.x / 24;
    const __nv_bfloat16* p = m == 3 ? P.ssm_k + (size_t)(i >> 2) * SEQ + (i & 3) * 64 : (m == 0 ? P.ck : m == 1 ? P.cv : P.x0) + (size_t)i * 64;
    asm volatile("prefetch.global.L2 [%0];" :: "l"(p));
  } else if (threadIdx.x == 96 && blockIdx.x < 45) {
    asm volatile("prefetch.global.L2 [%0];" :: "l"(blockIdx.x < 36 ? P.shift + blockIdx.x * 64 : P.ssm_d + (blockIdx.x - 36) * 64));
  }
  PROF_BEGIN();
  {
    const int wp = rd_warp();
    if (wp > 12) { sts1(sb + Q_SET, (__ldcg(&g_epoch) & 1) * FL_TOTAL); __syncwarp(); }
    if (wp <= 12) {
      const uint32_t sel = __shfl_sync(0xffffffffu, near_page(wp < 9 ? P.memx + wp * 512 + (blockIdx.x & 63) * 2 :
          wp < 12 ? P.part + (blockIdx.x * 3 + wp - 9) * 512 : P.memx + 9 * 512 + 64 + blockIdx.x * 2), 0);
      sts1(sb + Q_SEL + 4 * wp, sel * 4096);
    } else {
      const int lane = threadIdx.x & 31, head = rd_cid(), rk = rd_rank(), c = rk == 2 ? wp - 13 : 4 - rk + 2 * (wp - 13);
      const __nv_bfloat16* m0 = P.mem0 + (lane & 3) * 2 * DM + c * 64 + head * 2 + (lane >> 4);
      const uint32_t mw = __bfloat16_as_ushort(m0[0]) | (uint32_t)__bfloat16_as_ushort(m0[DM]) << 16;
      uint32_t* md = (uint32_t*)(P.memx + c * 512 + (lane & 4) * 64 + (lane & 8) * 8 + head * 2 + (lane >> 4)) + (lane & 3);
      st_gpu1(md, SENT);
      st_gpu1(md + 512, mw);
      if (wp == 13 && rk != 2) st_gpu1((uint32_t*)(P.memx + 9 * 512 + (lane & 1) * 256) + head * 2 + rk, next_tick());
      sts1(sb + Q_M0 + (threadIdx.x & 127) * 4, mw);
      __syncwarp();
      if (lane == 0) flag_add(g_flags + FL_INIT);
    }
  }
  const int rank = rd_rank(), wg = rd_warp() >> 2;
  if (threadIdx.x == 0) {
    mbar_init(sb + B_XFULL, 1); mbar_init(sb + B_XFULL + 8, 1); mbar_init(sb + B_MEMOK, 4); sts1(sb + Q_REDO, SENT);
    for (int c = 0; c < 4; c++) mbar_arrive(sb + B_MEMOK);
    for (int c = 0; c < 9; c++) { mbar_init(sb + B_GCP + 8 * c, 1); mbar_arrive(sb + B_GCP + 8 * c); }
    mbar_init(sb + B_XEMPTY, 8); mbar_init(sb + B_XEMPTY + 8, 8);
    mbar_init(sb + B_SM, 1); mbar_init(sb + B_O, rank == 2 ? 4 : 1); mbar_init(sb + B_XS, 4); mbar_init(sb + B_P, 1); mbar_init(sb + B_P + 8, 1);
    mbar_init(sb + B_REF, 1);
    mbar_init(sb + B_OXREADY, 4); mbar_init(sb + B_OXFREE, 1);
    mbar_expect(sb + B_SM, rank == 2 ? SM_BYTES : SX_BYTES); mbar_expect(sb + B_P, 4096); mbar_expect(sb + B_P + 8, 4096);
    if (rank != 2) mbar_expect(sb + B_O, 4096);
    asm volatile("fence.mbarrier_init.release.cluster;" ::: "memory");
  }
  __syncthreads();
  PROF_G(6);
  if (wg < 2) {
    asm volatile("setmaxnreg.inc.sync.aligned.u32 200;");
    head_main(sb, P);
    PROF_END();
  } else if (wg == 2) {
    asm volatile("setmaxnreg.dec.sync.aligned.u32 80;");
    head_aux(sb, P);
    PROF_END();
  } else {
    asm volatile("setmaxnreg.dec.sync.aligned.u32 32;");
    if (rd_warp() == 12) head_producer(sb); else head_reducer(sb, P);
    PROF_END();
  }
}

__device__ __forceinline__ void tail_gemm(uint32_t sb, const Params& P) {
  const int lane = threadIdx.x & 31, warp = rd_warp(), w = warp & 3, wg = warp >> 2, tid = threadIdx.x & 127;
  const __nv_bfloat16* wsrc = P.wo + (size_t)(blockIdx.x / 3) * 512 * DM + (blockIdx.x % 3) * 192 + wg * 64;
  uint32_t a[4 * W_KR];
  load_rows<29>(sb + wg * 65536, wsrc, DM, W_KR * 16, tid, 128);
  load_rows<3>(sb + W_WS + wg * 6144, wsrc + (size_t)W_KR * 16 * DM, DM, 512 - W_KR * 16, tid, 128);
  bar_sync_r(9 + wg, 128);
  load_afrags<W_KR>(a, sb + wg * 65536, w, lane);
  fence_async_smem();
  bar_sync<1, 416>();
  PROF_G(26);
  if (wg == 2) bar_arrive<2, 256>();
  const uint64_t dw = P.d_ws + wg * 384;
  float4* dst0 = g_acc + ((blockIdx.x % 3) * 12 + warp) * 32 + lane;
#pragma unroll 1
  for (int t = 1; t <= NT; t++) {
#pragma unroll 1
    for (int l = t > NSEG; l <= (t > LAG); l++) {
      const int seg = t - 1 - l * LAG, grp = (seg & 1) * 2 + l;
      const uint64_t db = P.d_ring + grp * 2048;
      float acc[16];
      bar_sync_r(2 + wg, 256);
#pragma unroll
      for (int c = 0; c < 4; c++) {
        if (wg == 0) mbar_wait(sb + B_FULL + 32 * grp + 8 * c, (seg >> 1) & 1);
        if (c == 0) PROF_T(6 * l + wg);
        wg_fence();
#pragma unroll
        for (int i = 0; i < 8; i++) {
          if (c == 0 && i == 0) wg_rs<0>(acc, a, db, 0);
          else if (8 * c + i < W_KR) wg_rs<1>(acc, a + 32 * c + 4 * i, db, 512 * c + 64 * i);
          else wg_ss<1, 1>(acc, dw, 128 * (8 * c + i - W_KR), db, 512 * c + 64 * i);
        }
      }
      wg_commit();
      bar_arrive_r(wg == 2 ? 2 : 3 + wg, 256);
      wg_wait<0>();
      reg_fence(acc);
      mbar_arrive_if0(tid, sb + B_EMPTY + 8 * grp);
      float4* dst = dst0 + (size_t)(l * 256 + seg * 4) * 1152;
#pragma unroll
      for (int j = 0; j < 4; j++)
        asm volatile("red.relaxed.gpu.global.add.v4.f32 [%0], {%1,%2,%3,%4};" :: "l"(dst + j * 1152),
                     "f"(acc[4 * j]), "f"(acc[4 * j + 1]), "f"(acc[4 * j + 2]), "f"(acc[4 * j + 3]) : "memory");
      bar_sync_r(5 + wg, 160);
    }
  }
}
__device__ __forceinline__ void tail_service(uint32_t sb) {
  const int lane = threadIdx.x & 31, warp = rd_warp();
  if (warp == 12) bar_sync<1, 416>();
#pragma unroll 1
  for (int t = 1; t <= NT; t++) {
    if (warp == 12) {
      if (lane < 8) {
        const int l = lane >> 2, h = (blockIdx.x / 3) * 4 + (lane & 3), seg = t - 1 - l * LAG, grp = (seg & 1) * 2 + l;
        if (seg >= 0 && seg < NSEG) {
          flag_wait(g_flags + FL_OX + t * 32 + h, 1);
          fence_async_global();
          mbar_wait_lim(sb + B_EMPTY + 8 * grp, ((seg >> 1) & 1) ^ 1);
          const uint32_t bar = sb + B_FULL + 32 * grp + 8 * (lane & 3);
          mbar_expect(bar, 8192);
          bulk_g2s(sb + W_RING + (grp * 4 + (lane & 3)) * 8192, g_ox + (size_t)(t % OXRING) * 32768 + l * 16384 + h * 512, 8192, bar);
        }
      }
      __syncwarp();
      PROF_T(12);
      PROF_MID();
    } else {
#pragma unroll 1
      for (int l = t > NSEG; l <= (t > LAG); l++) {
        bar_sync_r(warp - 8, 160);
        if (lane == 0) flag_add(g_flags + FL_ACC + (l * 64 + t - 1 - l * LAG) * 32);
        __syncwarp();
        PROF_T(6 * l + warp - 10);
      }
    }
  }
}

__device__ __forceinline__ void tail_finisher(uint32_t sb, const Params& P) {
  const int lane = threadIdx.x & 31, warp = rd_warp(), kind = warp < 12 ? warp / 6 : warp & 1, f = warp - 6 * kind, tg = blockIdx.x & 3;
  if (warp >= 14) {
    const uint32_t set = lds1(sb + Q_SET), ft = sb + W_FO + kind * 576;
    if (tg == 0) for (int i = kind * 32 + lane; i < FL_TOTAL; i += 64) g_flagsets[FL_TOTAL - set + i] = 0;
#pragma unroll 1
    for (int t = 0; t < NSEG; t++) {
      warp_flag_wait(g_flags + FL_ACC + (64 + t) * 32, 72);
      PROF_T(17);
      if (t == 0 && tg == 0 && threadIdx.x == 448) g_epoch = set ? 0 : 1;
      const float4* ac = g_acc + ((size_t)(256 + t * 4 + tg) * 36 + kind * 18) * 32 + lane;
      float4 v[18];
#pragma unroll
      for (int i = 0; i < 18; i++) v[i] = __ldcg(ac + i * 32);
#pragma unroll
      for (int i = 0; i < 9; i++)
        stsm4t(ft + (lane & 7) * 1168 + (lane >> 3) * 16 + 64 * i, pack_bf16(v[2 * i].x, v[2 * i].y), pack_bf16(v[2 * i].z, v[2 * i].w),
               pack_bf16(v[2 * i + 1].x, v[2 * i + 1].y), pack_bf16(v[2 * i + 1].z, v[2 * i + 1].w));
      fence_async_smem();
      __syncwarp();
      if (lane < 8) {
        bulk_s2g(P.out + (size_t)((t * 4 + tg) * 8 + lane) * DM + kind * 288, ft + lane * 1168, 576);
        bulk_commit_wait();
      }
      __syncwarp();
      PROF_T(18);
    }
    return;
  }
  if (warp >= 12) {
#pragma unroll 1
    for (int t = -1; t <= NSEG; t++) {
      if (kind == 0 && t + 1 < NSEG) {
        const uint32_t bar = sb + B_FT + 8 * ((t + 1) & 1);
        if (lane == 0) {
          if (t >= LAG + 5) flag_wait(g_flags + FL_XS + (t - 5) * 32 + 16, 4);
          mbar_expect(bar, 9216);
        }
        __syncwarp();
        if (lane < 8) bulk_g2s(sb + W_FT + ((t + 1) & 1) * 9344 + lane * 1168, P.x0 + (size_t)(((t + 1) * 4 + tg) * 8 + lane) * DM, 1152, bar);
      }
      if (t < 0) continue;
      if (t < NSEG) bar_sync_r(9 + 2 * kind, 224);
      if (lane == 0) {
        flag_add(g_flags + FL_XS + (t + kind * LAG) * 32 + kind * 16);
        if (t < NSEG) {
          bulk_s2g(g_acc + (size_t)(kind * 256 + t * 4 + tg) * 1152, sb + W_RS + (kind * 2 + (t & 1)) * 18432, 18432);
          bulk_commit_wait();
        }
      }
      __syncwarp();
      if (kind) { PROF_T(14); PROF_MID(); }
    }
    return;
  }
  const uint32_t BF_1 = 0x3F803F80u, BF_M0 = 0x80008000u;
  const uint32_t* ys = (const uint32_t*)(g_y + ((tg >> 1) * DM + f * 96 + (lane >> 2)) * 2 + (tg & 1)) + (lane & 3);
  uint32_t y[12] = {};
#pragma unroll 1
  for (int t = 0; t < NSEG; t++) {
    uint32_t x[12];
    if (kind == 0) {
      mbar_wait(sb + B_FT + 8 * (t & 1), (t >> 1) & 1);
#pragma unroll
      for (int i = 0; i < 3; i++)
        ldsm4t(x[4 * i], x[4 * i + 1], x[4 * i + 2], x[4 * i + 3], sb + W_FT + (t & 1) * 9344 + (lane & 7) * 1168 + f * 192 + (lane >> 3) * 16 + 64 * i);
    } else {
      warp_flag_wait(g_flags + FL_ACC + t * 32, 72);
      PROF_T(13);
#pragma unroll
      for (int i = 0; i < 6; i++) {
        const float4 v = __ldcg(g_acc + ((size_t)(t * 4 + tg) * 36 + f * 6 + i) * 32 + lane);
        x[2 * i] = pack_bf16(v.x, v.y); x[2 * i + 1] = pack_bf16(v.z, v.w);
      }
      PROF_T(15);
    }
    {
      if (t == 0) PROF_G(27);
#pragma unroll 1
      for (int pass = 0; pass < 2; pass++) {
        const uint32_t cw = __shfl_sync(0xffffffffu, x[0], lane & 3);
        float s0 = 0.f, s1 = 0.f, q0 = 0.f, q1 = 0.f;
#pragma unroll
        for (int i = 0; i < 12; i++) {
          const float d0 = bf_lo(x[i]) - bf_lo(cw), d1 = bf_hi(x[i]) - bf_hi(cw);
          s0 += d0; s1 += d1; q0 += d0 * d0; q1 += d1 * d1;
        }
#pragma unroll
        for (int o = 4; o < 32; o <<= 1) {
          s0 += __shfl_xor_sync(0xffffffffu, s0, o); s1 += __shfl_xor_sync(0xffffffffu, s1, o);
          q0 += __shfl_xor_sync(0xffffffffu, q0, o); q1 += __shfl_xor_sync(0xffffffffu, q1, o);
        }
        const uint32_t st = sb + W_ST + kind * 1024 + pass * 512 + (lane & 3) * 16;
        if (lane < 4) sts4f(st + f * 64, bf_lo(cw) + s0 * (1.f / 96.f), q0 - s0 * s0 * (1.f / 96.f), bf_hi(cw) + s1 * (1.f / 96.f), q1 - s1 * s1 * (1.f / 96.f));
        bar_sync_r(8 + 2 * kind, 192);
        const float4 r = lds4f(st);
        s0 = s1 = q0 = q1 = 0.f;
#pragma unroll
        for (int i = 0; i < 3; i++) {
          const float4 e = lds4f(st + (((lane >> 2) & 1) * 3 + i) * 64);
          const float d0 = e.x - r.x, d1 = e.z - r.z;
          s0 += d0; s1 += d1; q0 += e.y + 96.f * d0 * d0; q1 += e.w + 96.f * d1 * d1;
        }
#pragma unroll
        for (int o = 4; o < 8; o <<= 1) {
          s0 += __shfl_xor_sync(0xffffffffu, s0, o); s1 += __shfl_xor_sync(0xffffffffu, s1, o);
          q0 += __shfl_xor_sync(0xffffffffu, q0, o); q1 += __shfl_xor_sync(0xffffffffu, q1, o);
        }
        const float v0 = (q0 - 16.f * s0 * s0) * (1.f / 576.f), v1 = (q1 - 16.f * s1 * s1) * (1.f / 576.f);
        const uint32_t nmean = pack_bf16(-(r.x + s0 * (1.f / 6.f)), -(r.z + s1 * (1.f / 6.f))), vb = pack_bf16(fmaxf(v0, 0.f), fmaxf(v1, 0.f));
        const uint32_t ve = pack_bf16(bf_lo(vb) + 1e-5f, bf_hi(vb) + 1e-5f), sd = pack_bf16(sqr(bf_lo(ve)), sqr(bf_hi(ve)));
        const float r0 = rcp(bf_lo(sd)), r1 = rcp(bf_hi(sd));
        if (pass == 0 && (t == 0 || t == 4 * CT_A || t == 4 * CT_B || t == 4 * CT_C)) {
          if (t == 0) PROF_G(25);
          warp_flag_wait(g_flags + FL_Y + t * 8, t < 4 * CT_B ? 32 : DM);
          if (t == 0) PROF_G(26);
#pragma unroll
          for (int i = 0; i < 12; i++) y[i] = __ldcg(ys + t * (DM * 16) + i * 64);
        }
        uint32_t* xd = (uint32_t*)(g_xs + ((size_t)(t + kind * LAG) * 8 + kind * 4 + tg) * 580 + f * 96) + lane;
#pragma unroll
        for (int i = 0; i < 12; i++) {
          const uint32_t d = bf2_op(x[i], BF_1, nmean);
          const uint32_t q = pack_bf16(bf_lo(d) * r0, bf_hi(d) * r1);
          if (pass == 0) x[i] = bf2_op(x[i], BF_1, bf2_op(q, y[i], BF_M0));
          else xd[i * 32] = q;
        }
      }
#pragma unroll
      for (int i = 0; i < 6; i++)
        sts4f(sb + W_RS + (kind * 2 + (t & 1)) * 18432 + (f * 6 + i) * 512 + lane * 16, bf_lo(x[2 * i]), bf_hi(x[2 * i]), bf_lo(x[2 * i + 1]), bf_hi(x[2 * i + 1]));
      fence_async_smem();
      if (kind) PROF_T(16);
      if (t < 3) PROF_G(28 + t);
      bar_sync_r(9 + 2 * kind, 224);
#pragma unroll
      for (int i = 0; i < 12; i++) y[i] = __ldcg(ys + ((t + 1) & 63) * (DM * 16) + i * 64);
    }
  }
}

template <int NP, typename V>
__device__ __forceinline__ void kv_block(uint4 (&o)[2 * NP], const Params& P, int r0, int c0) {
  V kk[11], vv[8];
  uint4 sw[NP];
#pragma unroll
  for (int i = 0; i < NP; i++) sw[i] = __ldg((const uint4*)(P.shift + (c0 + 2 * i) * 4));
#pragma unroll
  for (int i = 0; i < 11; i++) kk[i] = r0 + i >= 3 ? __ldg((const V*)(P.ck + (size_t)(r0 + i - 3) * DM + c0)) : V{};
#pragma unroll
  for (int i = 0; i < 8; i++) vv[i] = __ldg((const V*)(P.cv + (size_t)(r0 + i) * DM + c0));
#pragma unroll
  for (int cp = 0; cp < NP; cp++) {
    const uint32_t wt[4] = {__byte_perm(sw[cp].y, sw[cp].w, 0x7632), __byte_perm(sw[cp].y, sw[cp].w, 0x5410),
                            __byte_perm(sw[cp].x, sw[cp].z, 0x7632), __byte_perm(sw[cp].x, sw[cp].z, 0x5410)};
    uint32_t e[8];
#pragma unroll
    for (int i = 0; i < 8; i++) {
      uint32_t a = bf2_mul(((const uint32_t*)&kk[i])[cp], wt[0]);
#pragma unroll
      for (int j = 1; j < 4; j++) a = bf2_add(a, bf2_mul(((const uint32_t*)&kk[i + j])[cp], wt[j]));
      e[i] = bf2_mul(a, ((const uint32_t*)&vv[i])[cp]);
    }
    o[2 * cp] = make_uint4(__byte_perm(e[0], e[1], 0x5410), __byte_perm(e[2], e[3], 0x5410), __byte_perm(e[4], e[5], 0x5410), __byte_perm(e[6], e[7], 0x5410));
    o[2 * cp + 1] = make_uint4(__byte_perm(e[0], e[1], 0x7632), __byte_perm(e[2], e[3], 0x7632), __byte_perm(e[4], e[5], 0x7632), __byte_perm(e[6], e[7], 0x7632));
  }
}
__device__ __forceinline__ void kv_task(const Params& P, int id) {
  const int lane = threadIdx.x & 31, tq = id / 9, c0 = (id % 9) * 64 + (lane >> 2) * 8;
  uint4 o[8];
  kv_block<4, uint4>(o, P, tq * 32 + (lane & 3) * 8, c0);
#pragma unroll
  for (int c = 0; c < 8; c++) g_kv[((size_t)tq * DM + c0 + c) * 4 + (lane & 3)] = o[c];
}
__device__ __forceinline__ int next_job(uint32_t sb) {
  int j = 0;
  if ((threadIdx.x & 31) == 0) j = atomicAdd(g_flags + FL_KV + 96, 1);
  return __shfl_sync(0xffffffffu, j, 0);
}
__device__ __forceinline__ uint2 lds2_ro(uint32_t a) { uint2 v; asm("ld.shared.v2.u32 {%0,%1}, [%2];" : "=r"(v.x), "=r"(v.y) : "r"(a)); return v; }

template <int T0, int T1>
__device__ __forceinline__ void conv_job(uint32_t sb, const Params& P, int ch) {
  const int lane = threadIdx.x & 31, w = threadIdx.x >> 5;
  const uint32_t ub = sb + w * C_CH, zb = ub + C_U;
  constexpr int NL = (T1 + 1) / 2;
  constexpr bool CTA = T1 <= CT_B;
  PROF_G(13 + 4 * (T0 == 0 ? 0 : T0 == CT_A ? 1 : 2));
  uint2 q[T1];
#pragma unroll
  for (int u = 0; u < T1; u++) q[u] = __ldg((const uint2*)(P.ssm_k + (size_t)ch * SEQ) + u * 32 + lane);
  const uint32_t dd = (uint32_t)__bfloat16_as_ushort(P.ssm_d[ch]) * 0x10001u;
  if (CTA) {
#pragma unroll
    for (int tq = w; tq < 4 * T1; tq += 16) {
      uint4 o[2];
      const int tgp = tq * 4 + (lane & 3), c0 = (lane >> 2) * 2;
      kv_block<1, uint32_t>(o, P, tgp * 8, ch - w + c0);
#pragma unroll
      for (int c = 0; c < 2; c++) {
        sts4(sb + (c0 + c) * C_CH + 256 + tgp * 16, o[c]);
        if (T0) g_kv[((size_t)tq * DM + ch - w + c0 + c) * 4 + (lane & 3)] = o[c];
      }
    }
    __syncwarp();
  } else {
    uint4 o[NL];
#pragma unroll
    for (int u = 0; u < NL; u++) o[u] = __ldcg(g_kv + ((size_t)(u * 8 + (lane >> 2)) * DM + ch) * 4 + (lane & 3));
#pragma unroll
    for (int u = 0; u < NL; u++) sts4(ub + 256 + (u * 32 + lane) * 16, o[u]);
  }
  if (lane < 16) { sts4(ub + lane * 16, make_uint4(0, 0, 0, 0)); sts1(zb + lane * 4, 0); }
#pragma unroll
  for (int u = 0; u < T1; u++) {
    const uint32_t pv = __shfl_sync(0xffffffffu, lane == 31 ? (u ? q[u ? u - 1 : 0].y : 0u) : q[u].y, (lane + 31) & 31);
    sts4(zb + 64 + (u * 32 + lane) * 16, make_uint4(__byte_perm(q[u].x, pv, 0x7610), __byte_perm(q[u].x, q[u].x, 0x1032),
                                                   __byte_perm(q[u].y, q[u].x, 0x7610), __byte_perm(q[u].y, q[u].y, 0x1032)));
  }
  if (CTA) __syncthreads(); else __syncwarp();
  PROF_G(14 + 4 * (T0 == 0 ? 0 : T0 == CT_A ? 1 : 2));
  float acc[T1 - T0][4];
#pragma unroll
  for (int i = 0; i < T1 - T0; i++) acc[i][0] = acc[i][1] = acc[i][2] = acc[i][3] = 0.f;
#pragma unroll(T0 == 0 ? 4 : 1)
  for (int r = 0; r < 8; r++) {
    uint2 b[T1];
    uint32_t ba = ub + 256 - r * 32 + lane * 8, zp = zb + 64 + (16 * r + 2 * (lane >> 2) - 4 * (lane & 3)) * 4;
    asm volatile("" : "+r"(zp), "+r"(ba) :: "memory");
#pragma unroll
    for (int i = 0; i < T1; i++) b[i] = lds2_ro(ba + i * 256);
#pragma unroll
    for (int mu = 0; mu < T1; mu++) {
      const uint2 a01 = lds2_ro(zp + 512 * mu), a23 = lds2_ro(zp + 512 * mu - 8);
#pragma unroll
      for (int i = (mu > T0 ? mu : T0); i < T1; i++) mma16816(acc[i - T0], a01.x, a01.y, a23.x, a23.y, b[i - mu].x, b[i - mu].y);
    }
  }
  PROF_G(15 + 4 * (T0 == 0 ? 0 : T0 == CT_A ? 1 : 2));
#pragma unroll
  for (int i = 0; i < T1 - T0; i++)
#pragma unroll
    for (int e = 0; e < 2; e++) {
      const int col = (T0 + i) * 8 + 2 * (lane & 3) + e;
      ((uint32_t*)g_y)[((size_t)col * DM + ch) * 8 + (lane >> 2)] =
          bf2_add(pack_bf16(acc[i][e], acc[i][2 + e]), bf2_mul(lds1(ub + 256 + col * 32 + (lane >> 2) * 4), dd));
    }
  if (CTA) __syncthreads(); else __syncwarp();
  PROF_G(16 + 4 * (T0 == 0 ? 0 : T0 == CT_A ? 1 : 2));
  if (CTA ? threadIdx.x == 480 && ch < 512 : lane == 0) flag_add(g_flags + FL_Y + T0 * 32);
  __syncwarp();
}

__global__ void __launch_bounds__(512, 1) tail_kernel(const Params P) {
  extern __shared__ uint8_t smem_raw[];
  const uint32_t sb = (uint32_t)__cvta_generic_to_shared(smem_raw);
  if (sb != SB0) __trap();
  PROF_BEGIN();
  if (threadIdx.x == 0) {
    for (int c = 0; c < 16; c++) mbar_init(sb + B_FULL + 8 * c, 1);
    for (int c = 0; c < 4; c++) mbar_init(sb + B_EMPTY + 8 * c, 3);
    for (int c = 0; c < 4; c++) mbar_init(sb + B_FT + 8 * c, 1);
    sts1(sb + Q_SET, (__ldcg(&g_epoch) & 1) * FL_TOTAL);
    fence_async_smem();
  }
  const int b = blockIdx.x, w = threadIdx.x >> 5;
  if ((b >> 2) == 6) {
    __syncthreads();
  } else {
#pragma unroll 1
    for (int g = b; g == b || (g >> 2) == 6; g -= 8) conv_job<0, CT_A>(sb, P, g * 16 + w);
    PROF_G(3);
#pragma unroll 1
    for (int g = b; g == b || (g >> 2) == 6; g -= 8) conv_job<CT_A, CT_B>(sb, P, g * 16 + w);
    PROF_G(4);
    constexpr int KV0 = 36 * CT_B, KV1 = KV0 + 192;
    int job = b < 32 ? KV0 + (b - 28) * 16 + w : -1;
#pragma unroll 1
    for (int k = 0; b >= 28; k++) {
      if (job >= 0) {
        kv_task(P, job);
        __syncwarp();
        if ((threadIdx.x & 31) == 0) flag_add(g_flags + FL_KV + (job < KV1 ? 0 : 32));
        if (job + 64 < KV1) { job += 64; continue; }
      }
      if (job < KV1) {
        warp_flag_wait(g_flags + FL_Y + CT_A * 32, 32);
        warp_flag_wait(g_flags + FL_KV, 192);
        spin_until(rd_clock() + (w >> 2) * 2000);
      }
      while ((job = next_job(sb)) < DM) conv_job<CT_B, CT_C>(sb, P, job);
      if (job < DM + 128) PROF_G(6);
      job -= DM - KV1;
      if (job >= 576) break;
    }
    if (b >= 28) {
      warp_flag_wait(g_flags + FL_KV + 32, 576 - KV1);
#pragma unroll 1
      for (job -= 576; job < DM; job = next_job(sb) - DM - (576 - KV1)) conv_job<CT_C, 16>(sb, P, job);
      PROF_G(5);
      PROF_END();
      return;
    }
    __syncwarp();
  }
  if (blockIdx.x >= 24) {
    PROF_G(24);
    tail_finisher(sb, P);
    PROF_END();
    asm volatile("griddepcontrol.wait;" ::: "memory");
  } else if (rd_warp() < 12) {
    asm volatile("setmaxnreg.inc.sync.aligned.u32 160;");
    tail_gemm(sb, P);
    PROF_END();
  } else {
    asm volatile("setmaxnreg.dec.sync.aligned.u32 32;");
    tail_service(sb);
    PROF_END();
  }
}

}

extern "C" void kernel_launch(void* const* d_in, const int* in_sizes, int n_in, void* d_out, int out_size) {
  typedef const __nv_bfloat16* bp;
  Params P;
  P.x0 = (bp)d_in[0]; P.ck = (bp)d_in[1]; P.cv = (bp)d_in[2]; P.shift = (bp)d_in[3]; P.ssm_k = (bp)d_in[4]; P.ssm_d = (bp)d_in[5];
  P.mem0 = (bp)d_in[7]; P.wq = (bp)d_in[8]; P.wk = (bp)d_in[9]; P.wv = (bp)d_in[10]; P.wo = (bp)d_in[11];
  P.out = (__nv_bfloat16*)d_out;
  void* xc = nullptr;
  cudaGetSymbolAddress(&xc, g_xchg);
  P.part = (uint4*)(((uintptr_t)xc + 8191) & ~(uintptr_t)8191);
  P.memx = P.part + 288 * 512;
  P.d_x = mkdesc(Q_X, 128, Q_GS, 0); P.d_wl = mkdesc(Q_WL, 16, 1024, 1);
  P.d_qk = mkdesc(Q_STG, 768, 128, 0); P.d_wo = mkdesc(Q_WO, 16, 1024, 1); P.d_ob = mkdesc(Q_OB, 128, 2048, 0);
  P.d_ring = mkdesc(W_RING, 512, 128, 0); P.d_ws = mkdesc(W_WS, 16, 1024, 1);
  cudaFuncSetAttribute(head_kernel, cudaFuncAttributeMaxDynamicSharedMemorySize, SMEM_TOTAL);
  cudaFuncSetAttribute(tail_kernel, cudaFuncAttributeMaxDynamicSharedMemorySize, SMEM_TOTAL);
  head_kernel<<<96, 512, SMEM_TOTAL>>>(P);
  cudaLaunchConfig_t cfg = {};
  cfg.gridDim = dim3(36); cfg.blockDim = dim3(512); cfg.dynamicSmemBytes = SMEM_TOTAL; cfg.stream = 0;
  cudaLaunchAttribute attr[1];
  attr[0].id = cudaLaunchAttributeProgrammaticStreamSerialization;
  attr[0].val.programmaticStreamSerializationAllowed = 1;
  cfg.attrs = attr; cfg.numAttrs = 1;
  cudaLaunchKernelEx(&cfg, tail_kernel, P);
}
```

```cpp
#include <cuda_runtime.h>
#include <cuda_bf16.h>
#include <stdint.h>

namespace {

constexpr int SEQ = 2048, DM = 576, NSEG = 64;
#define LAG_V 5
#define RV_V 2050
#define R1_V 350
#define R0_V 600
#define RC_V 140
#define GX_V 1100
#define AD_V 0
#define XA_V 0
#define XB_V 210
#define XD_V 520
#define XP_V 270
#define RS_V 3
#define CALIB 0
#define RF_V 2300
#define RL_V 2000
#define KPV_V 14
#define KP1_V 18
#define KP0_V 22
constexpr int LAG = LAG_V;
constexpr int NT = NSEG + LAG;
constexpr int OXRING = 8;
static_assert(LAG >= 3 && LAG < OXRING, "pipeline lag");
constexpr uint32_t D_RED = RV_V;
__host__ __device__ constexpr uint32_t rank_delay(int r) { return r == 2 ? 0 : r ? R1_V : R0_V; }
constexpr uint32_t D_DUE = RF_V, D_LATE = RL_V;
constexpr uint32_t D_TILE = RC_V * 9 / 16, D_GX = GX_V * 9 / 16, D_ADAPT = AD_V * 9 / 16;
constexpr int KP_V = KPV_V, KP_1 = KP1_V, KP_0 = KP0_V;
constexpr int KP_MAX = KP_0 > KP_1 ? KP_0 : KP_1;
constexpr uint32_t SB0 = 1024;
constexpr float SM_SCALE = 0.08838834764831845f * 1.4426950408889634f;
constexpr uint32_t SENT = 0xFFFFFFFFu;
constexpr uint32_t SPIN_LIMIT = 1u << 21;

constexpr int FL_XS = 0;
constexpr int FL_ACC = (NT + 2) * 32;
constexpr int FL_OX = FL_ACC + 128 * 32;
constexpr int FL_SEL = FL_OX + (NT + 1) * 32;
constexpr int FL_Y = FL_SEL + 96 * 4;
constexpr int FL_KV = FL_Y + 512;
constexpr int FL_TOTAL = FL_KV + 128;

__device__ __align__(1024) uint4 g_y[256 * DM];
__device__ __align__(1024) uint4 g_kv[256 * DM];
__device__ __align__(1024) float4 g_acc[2 * 256 * 36 * 32];
__device__ __align__(1024) uint4 g_xs[NT * 4608];
__device__ __align__(1024) uint4 g_ox[OXRING * 512 * 8 * 8];
__device__ __align__(1024) uint4 g_xchg[(288 + 10 + 1) * 512];
__device__ __align__(1024) uint32_t g_flagsets[2 * FL_TOTAL];
__device__ uint32_t g_epoch;
#define PROF_T(slot) do {} while (0)
#define PROF_END() do {} while (0)
#define PROF_W(cond, slot) do {} while (0)
#define PROF_V(cond, slot, val) do { (void)(val); } while (0)
#define PROF_G(slot) do {} while (0)
#define PROF_OR(slot, val) do {} while (0)
#define PROF_A(idx, val) do { (void)(val); } while (0)
#define PROF_BEGIN() do {} while (0)
#define PROF_MID() do {} while (0)

#define HINT ", 100000"
__device__ __forceinline__ uint32_t pack_bf16(float lo, float hi) {
  uint32_t r; asm("cvt.rn.bf16x2.f32 %0, %1, %2;" : "=r"(r) : "f"(hi), "f"(lo)); return r;
}
__device__ __forceinline__ float bf_lo(uint32_t w) { return __uint_as_float(__byte_perm(w, 0, 0x1044)); }
__device__ __forceinline__ float bf_hi(uint32_t w) { return __uint_as_float(w & 0xFFFF0000u); }
__device__ __forceinline__ uint32_t mapa(uint32_t a, uint32_t r) {
  uint32_t o; asm("mapa.shared::cluster.u32 %0, %1, %2;" : "=r"(o) : "r"(a), "r"(r)); return o;
}
__device__ __forceinline__ void mbar_init(uint32_t bar, uint32_t cnt) {
  asm volatile("mbarrier.init.shared::cta.b64 [%0], %1;" :: "r"(bar), "r"(cnt) : "memory");
}
__device__ __forceinline__ void mbar_expect(uint32_t bar, uint32_t bytes) {
  asm volatile("mbarrier.arrive.expect_tx.shared::cta.b64 _, [%0], %1;" :: "r"(bar), "r"(bytes) : "memory");
}
__device__ __forceinline__ void mbar_arrive(uint32_t bar) {
  asm volatile("mbarrier.arrive.shared::cta.b64 _, [%0];" :: "r"(bar) : "memory");
}
__device__ __forceinline__ void mbar_arrive_if0(uint32_t sel, uint32_t bar) {
  asm volatile("{\n.reg .pred p;\nsetp.eq.u32 p, %1, 0;\n@p mbarrier.arrive.shared::cta.b64 _, [%0];\n}" :: "r"(bar), "r"(sel) : "memory");
}
__device__ __forceinline__ void mbar_expect_if0(uint32_t sel, uint32_t bar, uint32_t bytes) {
  asm volatile("{\n.reg .pred p;\nsetp.eq.u32 p, %1, 0;\n@p mbarrier.arrive.expect_tx.shared::cta.b64 _, [%0], %2;\n}" :: "r"(bar), "r"(sel), "r"(bytes) : "memory");
}
__device__ __forceinline__ void mbar_rarrive_if0(uint32_t sel, uint32_t bar) {
  asm volatile("{\n.reg .pred p;\nsetp.eq.u32 p, %1, 0;\n@p mbarrier.arrive.relaxed.cluster.shared::cluster.b64 _, [%0];\n}" :: "r"(bar), "r"(sel) : "memory");
}
__device__ __forceinline__ void mbar_wait_lim(uint32_t bar, uint32_t par) {
  asm volatile(
    "{\n.reg .pred p;\n.reg .u32 c;\nmov.u32 c, 0;\n"
    "W_%=:\n"
    "mbarrier.try_wait.parity.shared::cta.b64 p, [%0], %1;\n"
    "@p bra D_%=;\n"
    "add.u32 c, c, 1;\nsetp.lt.u32 p, c, %2;\n@p bra W_%=;\ntrap;\n"
    "D_%=:\n}\n" :: "r"(bar), "r"(par), "n"(SPIN_LIMIT) : "memory");
}
__device__ __forceinline__ void mbar_wait(uint32_t bar, uint32_t par) {
  asm volatile(
    "{\n.reg .pred p;\n"
    "W_%=:\n"
    "mbarrier.try_wait.parity.shared::cta.b64 p, [%0], %1" HINT ";\n"
    "@!p bra W_%=;\n}\n" :: "r"(bar), "r"(par) : "memory");
}
__device__ __forceinline__ void mbar_spin(uint32_t bar, uint32_t par) {
  asm volatile("{\n.reg .pred p;\nW_%=:\nmbarrier.try_wait.parity.shared::cta.b64 p, [%0], %1;\n@!p bra W_%=;\n}\n" :: "r"(bar), "r"(par) : "memory");
}
__device__ __forceinline__ void mbar_wait_if(uint32_t& done, uint32_t test, uint32_t bar, uint32_t par, bool force) {
  asm volatile(
    "{\n.reg .pred p, q;\nsetp.ne.u32 p, %0, 0;\n@p bra.uni D_%=;\nsetp.ne.u32 q, %4, 0;\n"
    "mbarrier.test_wait.parity.shared::cta.b64 p, [%1], %3;\n"
    "or.pred p, p, q;\n@!p bra D_%=;\n"
    "W_%=:\n"
    "mbarrier.try_wait.parity.shared::cta.b64 p, [%2], %3, 100000;\n"
    "@!p bra W_%=;\nmov.u32 %0, 1;\nD_%=:\n}\n" : "+r"(done) : "r"(test), "r"(bar), "r"(par), "r"((uint32_t)force) : "memory");
}
template <int ID, int N> __device__ __forceinline__ void bar_sync() { asm volatile("bar.sync %0, %1;" :: "n"(ID), "n"(N) : "memory"); }
template <int ID, int N> __device__ __forceinline__ void bar_arrive() { asm volatile("bar.arrive %0, %1;" :: "n"(ID), "n"(N) : "memory"); }
__device__ __forceinline__ void bar_sync_r(int id, int n) { asm volatile("bar.sync %0, %1;" :: "r"(id), "r"(n) : "memory"); }
__device__ __forceinline__ void bar_arrive_r(int id, int n) { asm volatile("bar.arrive %0, %1;" :: "r"(id), "r"(n) : "memory"); }
__device__ __forceinline__ uint32_t pin(uint32_t x) { return __shfl_sync(0xffffffffu, x, threadIdx.x); }
__device__ __forceinline__ void cluster_sync() {
  asm volatile("barrier.cluster.arrive.aligned;\nbarrier.cluster.wait.aligned;" ::: "memory");
}
__device__ __forceinline__ void fence_async_smem() { asm volatile("fence.proxy.async.shared::cta;" ::: "memory"); }
__device__ __forceinline__ void fence_async_global() { asm volatile("fence.proxy.async.global;" ::: "memory"); }
__device__ __forceinline__ uint4 ld_poll(const uint4* p) {
  uint4 v;
  asm volatile("ld.relaxed.gpu.global.v4.u32 {%0,%1,%2,%3}, [%4];" : "=r"(v.x), "=r"(v.y), "=r"(v.z), "=r"(v.w) : "l"(p) : "memory");
  return v;
}
__device__ __forceinline__ uint32_t rd_clock() { uint64_t c; asm volatile("mov.u64 %0, %%clock64;" : "=l"(c) :: "memory"); return (uint32_t)c; }
__device__ __forceinline__ void spin_until(uint32_t when) {
  asm volatile("{\n.reg .pred p;\n.reg .b64 c;\n.reg .s32 lo;\nS_%=:\nmov.u64 c, %%clock64;\ncvt.u32.u64 lo, c;\nsub.s32 lo, lo, %0;\n"
               "setp.lt.s32 p, lo, 0;\n@p bra.uni S_%=;\n}" :: "r"(when) : "memory");
}
__device__ __forceinline__ uint32_t near_page(uint4* pair) {
  uint32_t best0 = ~0u, best1 = ~0u;
  const int lane = threadIdx.x & 31;
  if (lane < 4) asm volatile("st.relaxed.gpu.global.v4.u32 [%0], {%1,%1,%1,%1};" :: "l"(pair + (lane >> 1) * 256 + (lane & 1)), "r"(SENT) : "memory");
  __syncwarp();
#pragma unroll 1
  for (int r = 0; r < 8; r++) {
    if (r >= 4 && !(r & 1) && __all_sync(0xffffffffu, max(best0, best1) - min(best0, best1) > 110u && min(best0, best1) < 420u)) break;
    uint32_t t0, t1, v;
    asm volatile("mov.u32 %0, %%clock;" : "=r"(t0) :: "memory");
    asm volatile("{\n.reg .pred p;\nsetp.eq.u32 p, %2, 0;\nmov.u32 %0, 0;\n@p atom.relaxed.gpu.global.exch.b32 %0, [%1], %3;\n}"
                 : "=&r"(v) : "l"(pair + (r & 1) * 256), "r"(lane), "r"(SENT) : "memory");
    asm volatile("{\n.reg .pred p;\nsetp.ne.u32 p, %1, 0x9E3779B9;\nmov.u32 %0, %2;\n@p mov.u32 %0, %%clock;\n}" : "=&r"(t1) : "r"(v), "r"(t0 - 1) : "memory");
    if (r & 1) best1 = min(best1, t1 - t0); else best0 = min(best0, t1 - t0);
  }
  return best1 < best0;
}
__device__ __forceinline__ void st_gpu4(uint4* p, uint32_t a, uint32_t b, uint32_t c, uint32_t d) {
  asm volatile("st.relaxed.gpu.global.v4.u32 [%0], {%1,%2,%3,%4};" :: "l"(p), "r"(a), "r"(b), "r"(c), "r"(d) : "memory");
}
__device__ __forceinline__ void st_gpu1(uint32_t* p, uint32_t a) {
  asm volatile("st.relaxed.gpu.global.u32 [%0], %1;" :: "l"(p), "r"(a) : "memory");
}
__device__ __forceinline__ void st_gpu1_if(bool c, uint32_t* p, uint32_t a) {
  asm volatile("{\n.reg .pred p;\nsetp.ne.u32 p, %2, 0;\n@p st.relaxed.gpu.global.u32 [%0], %1;\n}" :: "l"(p), "r"(a), "r"((uint32_t)c) : "memory");
}
__device__ __forceinline__ void warp_flag_wait(const uint32_t* p, uint32_t target) {
  uint32_t v, n = 0;
  do {
    asm volatile("ld.relaxed.gpu.global.u32 %0, [%1];" : "=r"(v) : "l"(p) : "memory");
    if (++n > SPIN_LIMIT) __trap();
  } while (__any_sync(0xffffffffu, v < target));
}
__device__ __forceinline__ void flag_add(uint32_t* p) {
  asm volatile("red.release.gpu.global.add.u32 [%0], 1;" :: "l"(p) : "memory");
}
__device__ __forceinline__ void bulk_g2s(uint32_t dst, const void* src, uint32_t bytes, uint32_t bar) {
  asm volatile("cp.async.bulk.shared::cluster.global.mbarrier::complete_tx::bytes [%0], [%1], %2, [%3];"
               :: "r"(dst), "l"(src), "r"(bytes), "r"(bar) : "memory");
}
__device__ __forceinline__ void bulk_g2s_mc(uint32_t dst, const void* src, uint32_t bytes, uint32_t bar, uint16_t mask) {
  asm volatile("cp.async.bulk.shared::cluster.global.mbarrier::complete_tx::bytes.multicast::cluster [%0], [%1], %2, [%3], %4;"
               :: "r"(dst), "l"(src), "r"(bytes), "r"(bar), "h"(mask) : "memory");
}
__device__ __forceinline__ void bulk_s2s(uint32_t dst, uint32_t src, uint32_t bytes, uint32_t bar) {
  asm volatile("cp.async.bulk.shared::cluster.shared::cta.mbarrier::complete_tx::bytes [%0], [%1], %2, [%3];"
               :: "r"(dst), "r"(src), "r"(bytes), "r"(bar) : "memory");
}
__device__ __forceinline__ void bulk_s2g(void* dst, uint32_t src, uint32_t bytes) {
  asm volatile("cp.async.bulk.global.shared::cta.bulk_group [%0], [%1], %2;" :: "l"(dst), "r"(src), "r"(bytes) : "memory");
}
__device__ __forceinline__ void bulk_commit_wait() {
  asm volatile("cp.async.bulk.commit_group;\ncp.async.bulk.wait_group 0;" ::: "memory");
}
__device__ __forceinline__ bool elect_one() {
  uint32_t p; asm volatile("{\n.reg .pred p;\nelect.sync _|p, 0xffffffff;\nselp.u32 %0, 1, 0, p;\n}" : "=r"(p)); return p;
}
__device__ __forceinline__ void ldsm4(uint32_t& r0, uint32_t& r1, uint32_t& r2, uint32_t& r3, uint32_t a) {
  asm volatile("ldmatrix.sync.aligned.m8n8.x4.shared.b16 {%0,%1,%2,%3}, [%4];" : "=r"(r0), "=r"(r1), "=r"(r2), "=r"(r3) : "r"(a) : "memory");
}
__device__ __forceinline__ void ldsm4t(uint32_t& r0, uint32_t& r1, uint32_t& r2, uint32_t& r3, uint32_t a) {
  asm volatile("ldmatrix.sync.aligned.m8n8.x4.trans.shared.b16 {%0,%1,%2,%3}, [%4];" : "=r"(r0), "=r"(r1), "=r"(r2), "=r"(r3) : "r"(a) : "memory");
}
__device__ __forceinline__ void stsm4(uint32_t a, uint32_t r0, uint32_t r1, uint32_t r2, uint32_t r3) {
  asm volatile("stmatrix.sync.aligned.m8n8.x4.shared.b16 [%0], {%1,%2,%3,%4};" :: "r"(a), "r"(r0), "r"(r1), "r"(r2), "r"(r3) : "memory");
}
__device__ __forceinline__ void stsm2(uint32_t a, uint32_t r0, uint32_t r1) {
  asm volatile("stmatrix.sync.aligned.m8n8.x2.shared.b16 [%0], {%1,%2};" :: "r"(a), "r"(r0), "r"(r1) : "memory");
}
__device__ __forceinline__ void stsm4t(uint32_t a, uint32_t r0, uint32_t r1, uint32_t r2, uint32_t r3) {
  asm volatile("stmatrix.sync.aligned.m8n8.x4.trans.shared.b16 [%0], {%1,%2,%3,%4};" :: "r"(a), "r"(r0), "r"(r1), "r"(r2), "r"(r3) : "memory");
}
__device__ __forceinline__ float4 lds4f(uint32_t a) {
  float4 v; asm volatile("ld.shared.v4.f32 {%0,%1,%2,%3}, [%4];" : "=f"(v.x), "=f"(v.y), "=f"(v.z), "=f"(v.w) : "r"(a) : "memory"); return v;
}
__device__ __forceinline__ uint4 lds4(uint32_t a) {
  uint4 v; asm volatile("ld.shared.v4.u32 {%0,%1,%2,%3}, [%4];" : "=r"(v.x), "=r"(v.y), "=r"(v.z), "=r"(v.w) : "r"(a) : "memory"); return v;
}
__device__ __forceinline__ uint32_t lds1(uint32_t a) {
  uint32_t v; asm volatile("ld.shared.u32 %0, [%1];" : "=r"(v) : "r"(a) : "memory"); return v;
}
__device__ __forceinline__ void sts4(uint32_t a, uint4 v) {
  asm volatile("st.shared.v4.u32 [%0], {%1,%2,%3,%4};" :: "r"(a), "r"(v.x), "r"(v.y), "r"(v.z), "r"(v.w) : "memory");
}
__device__ __forceinline__ void sts1(uint32_t a, uint32_t v) { asm volatile("st.shared.u32 [%0], %1;" :: "r"(a), "r"(v) : "memory"); }
__device__ __forceinline__ void mma16816(float (&d)[4], uint32_t a0, uint32_t a1, uint32_t a2, uint32_t a3, uint32_t b0, uint32_t b1) {
  asm volatile("mma.sync.aligned.m16n8k16.row.col.f32.bf16.bf16.f32 {%0,%1,%2,%3}, {%4,%5,%6,%7}, {%8,%9}, {%0,%1,%2,%3};"
               : "+f"(d[0]), "+f"(d[1]), "+f"(d[2]), "+f"(d[3]) : "r"(a0), "r"(a1), "r"(a2), "r"(a3), "r"(b0), "r"(b1));
}
__device__ __forceinline__ void mma1688(float (&d)[4], uint32_t a0, uint32_t a1, uint32_t b0) {
  asm volatile("mma.sync.aligned.m16n8k8.row.col.f32.bf16.bf16.f32 {%0,%1,%2,%3}, {%4,%5}, {%6}, {%0,%1,%2,%3};"
               : "+f"(d[0]), "+f"(d[1]), "+f"(d[2]), "+f"(d[3]) : "r"(a0), "r"(a1), "r"(b0));
}
__device__ __forceinline__ float rcp(float x) { float r; asm("rcp.approx.ftz.f32 %0, %1;" : "=f"(r) : "f"(x)); return r; }
__device__ __forceinline__ float sqr(float x) { float r; asm("sqrt.approx.f32 %0, %1;" : "=f"(r) : "f"(x)); return r; }
__device__ __forceinline__ float ex2(float x) { float r; asm("ex2.approx.ftz.f32 %0, %1;" : "=f"(r) : "f"(x)); return r; }

__host__ __device__ constexpr uint64_t mkdesc(uint32_t off, uint32_t lbo, uint32_t sbo, uint32_t sw) {
  return (uint64_t)((SB0 + off) >> 4) | ((uint64_t)(lbo >> 4) << 16) | ((uint64_t)(sbo >> 4) << 32) | ((uint64_t)sw << 62);
}
__device__ __forceinline__ void wg_fence() { asm volatile("wgmma.fence.sync.aligned;" ::: "memory"); }
__device__ __forceinline__ void wg_commit() { asm volatile("wgmma.commit_group.sync.aligned;" ::: "memory"); }
template <int N> __device__ __forceinline__ void wg_wait() { asm volatile("wgmma.wait_group.sync.aligned %0;" :: "n"(N) : "memory"); }
template <int N> __device__ __forceinline__ void reg_fence(float (&d)[N]) {
#pragma unroll
  for (int i = 0; i < N; i++) asm volatile("" : "+f"(d[i]) :: "memory");
}

#define F4(d, o) "+f"(d[o]), "+f"(d[o + 1]), "+f"(d[o + 2]), "+f"(d[o + 3])
template <int SC, int TB> __device__ __forceinline__ void wg_rs(float (&d)[8], const uint32_t* a, uint64_t db, int ob) {
  asm volatile("{\n.reg .pred p;\n.reg .b64 b;\nsetp.ne.b32 p, %13, 0;\nadd.s64 b, %12, %15;\n"
    "wgmma.mma_async.sync.aligned.m64n16k16.f32.bf16.bf16 {%0,%1,%2,%3,%4,%5,%6,%7}, {%8,%9,%10,%11}, b, p, 1, 1, %14;\n}\n"
    : F4(d, 0), F4(d, 4) : "r"(a[0]), "r"(a[1]), "r"(a[2]), "r"(a[3]), "l"(db), "n"(SC), "n"(TB), "l"((uint64_t)ob));
}
template <int SC, int TB> __device__ __forceinline__ void wg_rs(float (&d)[12], const uint32_t* a, uint64_t db, int ob) {
  asm volatile("{\n.reg .pred p;\n.reg .b64 b;\nsetp.ne.b32 p, %17, 0;\nadd.s64 b, %16, %19;\n"
    "wgmma.mma_async.sync.aligned.m64n24k16.f32.bf16.bf16 {%0,%1,%2,%3,%4,%5,%6,%7,%8,%9,%10,%11}, {%12,%13,%14,%15}, b, p, 1, 1, %18;\n}\n"
    : F4(d, 0), F4(d, 4), F4(d, 8) : "r"(a[0]), "r"(a[1]), "r"(a[2]), "r"(a[3]), "l"(db), "n"(SC), "n"(TB), "l"((uint64_t)ob));
}
template <int SC, int TB> __device__ __forceinline__ void wg_rs(float (&d)[16], const uint32_t* a, uint64_t db, int ob) {
  asm volatile("{\n.reg .pred p;\n.reg .b64 b;\nsetp.ne.b32 p, %21, 0;\nadd.s64 b, %20, %23;\n"
    "wgmma.mma_async.sync.aligned.m64n32k16.f32.bf16.bf16 {%0,%1,%2,%3,%4,%5,%6,%7,%8,%9,%10,%11,%12,%13,%14,%15}, {%16,%17,%18,%19}, b, p, 1, 1, %22;\n}\n"
    : F4(d, 0), F4(d, 4), F4(d, 8), F4(d, 12) : "r"(a[0]), "r"(a[1]), "r"(a[2]), "r"(a[3]), "l"(db), "n"(SC), "n"(TB), "l"((uint64_t)ob));
}
template <int SC, int TB> __device__ __forceinline__ void wg_rs(float (&d)[28], const uint32_t* a, uint64_t db, int ob) {
  asm volatile("{\n.reg .pred p;\n.reg .b64 b;\nsetp.ne.b32 p, %33, 0;\nadd.s64 b, %32, %35;\n"
    "wgmma.mma_async.sync.aligned.m64n56k16.f32.bf16.bf16 {%0,%1,%2,%3,%4,%5,%6,%7,%8,%9,%10,%11,%12,%13,%14,%15,%16,%17,%18,%19,%20,%21,%22,%23,%24,%25,%26,%27}, {%28,%29,%30,%31}, b, p, 1, 1, %34;\n}\n"
    : F4(d, 0), F4(d, 4), F4(d, 8), F4(d, 12), F4(d, 16), F4(d, 20), F4(d, 24) : "r"(a[0]), "r"(a[1]), "r"(a[2]), "r"(a[3]), "l"(db), "n"(SC), "n"(TB), "l"((uint64_t)ob));
}
template <int SC, int TB> __device__ __forceinline__ void wg_ss(float (&d)[8], uint64_t da, int oa, uint64_t db, int ob) {
  asm volatile("{\n.reg .pred p;\n.reg .b64 a, b;\nsetp.ne.b32 p, %10, 0;\nadd.s64 a, %8, %12;\nadd.s64 b, %9, %13;\n"
    "wgmma.mma_async.sync.aligned.m64n16k16.f32.bf16.bf16 {%0,%1,%2,%3,%4,%5,%6,%7}, a, b, p, 1, 1, 1, %11;\n}\n"
    : F4(d, 0), F4(d, 4) : "l"(da), "l"(db), "n"(SC), "n"(TB), "l"((uint64_t)oa), "l"((uint64_t)ob));
}
template <int SC, int TB> __device__ __forceinline__ void wg_ss(float (&d)[12], uint64_t da, int oa, uint64_t db, int ob) {
  asm volatile("{\n.reg .pred p;\n.reg .b64 a, b;\nsetp.ne.b32 p, %14, 0;\nadd.s64 a, %12, %16;\nadd.s64 b, %13, %17;\n"
    "wgmma.mma_async.sync.aligned.m64n24k16.f32.bf16.bf16 {%0,%1,%2,%3,%4,%5,%6,%7,%8,%9,%10,%11}, a, b, p, 1, 1, 1, %15;\n}\n"
    : F4(d, 0), F4(d, 4), F4(d, 8) : "l"(da), "l"(db), "n"(SC), "n"(TB), "l"((uint64_t)oa), "l"((uint64_t)ob));
}
template <int SC, int TB> __device__ __forceinline__ void wg_ss(float (&d)[16], uint64_t da, int oa, uint64_t db, int ob) {
  asm volatile("{\n.reg .pred p;\n.reg .b64 a, b;\nsetp.ne.b32 p, %18, 0;\nadd.s64 a, %16, %20;\nadd.s64 b, %17, %21;\n"
    "wgmma.mma_async.sync.aligned.m64n32k16.f32.bf16.bf16 {%0,%1,%2,%3,%4,%5,%6,%7,%8,%9,%10,%11,%12,%13,%14,%15}, a, b, p, 1, 1, 1, %19;\n}\n"
    : F4(d, 0), F4(d, 4), F4(d, 8), F4(d, 12) : "l"(da), "l"(db), "n"(SC), "n"(TB), "l"((uint64_t)oa), "l"((uint64_t)ob));
}
template <int SC, int TB> __device__ __forceinline__ void wg_ss(float (&d)[20], uint64_t da, int oa, uint64_t db, int ob) {
  asm volatile("{\n.reg .pred p;\n.reg .b64 a, b;\nsetp.ne.b32 p, %22, 0;\nadd.s64 a, %20, %24;\nadd.s64 b, %21, %25;\n"
    "wgmma.mma_async.sync.aligned.m64n40k16.f32.bf16.bf16 {%0,%1,%2,%3,%4,%5,%6,%7,%8,%9,%10,%11,%12,%13,%14,%15,%16,%17,%18,%19}, a, b, p, 1, 1, 1, %23;\n}\n"
    : F4(d, 0), F4(d, 4), F4(d, 8), F4(d, 12), F4(d, 16) : "l"(da), "l"(db), "n"(SC), "n"(TB), "l"((uint64_t)oa), "l"((uint64_t)ob));
}
template <int SC, int TB> __device__ __forceinline__ void wg_ss(float (&d)[28], uint64_t da, int oa, uint64_t db, int ob) {
  asm volatile("{\n.reg .pred p;\n.reg .b64 a, b;\nsetp.ne.b32 p, %30, 0;\nadd.s64 a, %28, %32;\nadd.s64 b, %29, %33;\n"
    "wgmma.mma_async.sync.aligned.m64n56k16.f32.bf16.bf16 {%0,%1,%2,%3,%4,%5,%6,%7,%8,%9,%10,%11,%12,%13,%14,%15,%16,%17,%18,%19,%20,%21,%22,%23,%24,%25,%26,%27}, a, b, p, 1, 1, 1, %31;\n}\n"
    : F4(d, 0), F4(d, 4), F4(d, 8), F4(d, 12), F4(d, 16), F4(d, 20), F4(d, 24) : "l"(da), "l"(db), "n"(SC), "n"(TB), "l"((uint64_t)oa), "l"((uint64_t)ob));
}

template <int SC> __device__ __forceinline__ void wg_sskk(float (&d)[16], uint64_t da, int oa, uint64_t db, int ob) {
  asm volatile("{\n.reg .pred p;\n.reg .b64 a, b;\nsetp.ne.b32 p, %18, 0;\nadd.s64 a, %16, %19;\nadd.s64 b, %17, %20;\n"
    "wgmma.mma_async.sync.aligned.m64n32k16.f32.bf16.bf16 {%0,%1,%2,%3,%4,%5,%6,%7,%8,%9,%10,%11,%12,%13,%14,%15}, a, b, p, 1, 1, 0, 0;\n}\n"
    : F4(d, 0), F4(d, 4), F4(d, 8), F4(d, 12) : "l"(da), "l"(db), "n"(SC), "l"((uint64_t)oa), "l"((uint64_t)ob));
}

template <int NB>
__device__ __forceinline__ void load_rows(uint32_t dst, const __nv_bfloat16* src, int pitch, int nrows, int tid, int nthr) {
  for (int i0 = tid; i0 < nrows * 8; i0 += nthr * NB) {
    uint4 v[NB];
#pragma unroll
    for (int u = 0; u < NB; u++) {
      const int i = i0 + u * nthr, r = i >> 3;
      if (i < nrows * 8) v[u] = __ldg((const uint4*)(src + (size_t)r * pitch + (i & 7) * 8));
    }
#pragma unroll
    for (int u = 0; u < NB; u++) {
      const int i = i0 + u * nthr, r = i >> 3;
      if (i < nrows * 8) sts4(dst + r * 128 + (((i & 7) ^ (r & 7)) << 4), v[u]);
    }
  }
}
template <int NK> __device__ __forceinline__ void load_afrags(uint32_t* a, uint32_t tile, int w, int lane) {
  int i = lane >> 3, r = lane & 7;
  uint32_t base = tile + ((i >> 1) * 8 + r) * 128 + (((2 * w + (i & 1)) ^ r) << 4);
#pragma unroll
  for (int kk = 0; kk < NK; kk++) ldsm4t(a[4 * kk], a[4 * kk + 1], a[4 * kk + 2], a[4 * kk + 3], base + kk * 2048);
}

constexpr uint32_t Q_WL = 0;
constexpr uint32_t Q_WO = 24576;
constexpr uint32_t Q_OX = Q_WO;
constexpr uint32_t Q_X = 73728;
constexpr uint32_t Q_CS = 10240;
constexpr uint32_t Q_STG = 165888;
constexpr uint32_t Q_OB = 190464;
constexpr uint32_t Q_SIN = 194560;
constexpr uint32_t Q_PX = 204800;
constexpr uint32_t Q_SOUT = Q_PX;
constexpr int Q_KR = 30;
constexpr uint32_t BARS = 228352;
constexpr uint32_t B_CP = BARS;
constexpr uint32_t B_OK = BARS + 408;
constexpr uint32_t B_XF = BARS + 72;
constexpr uint32_t B_E = BARS + 224;
constexpr uint32_t B_SM = BARS + 160;
constexpr uint32_t B_O = BARS + 168;
constexpr uint32_t B_P = BARS + 176;
constexpr uint32_t B_OXREADY = BARS + 192;
constexpr uint32_t B_OXFREE = BARS + 200;
constexpr uint32_t B_REF = BARS + 208;
constexpr uint32_t B_RES = BARS + 216;
constexpr uint32_t Q_REF = BARS + 288;
constexpr uint32_t Q_SEL = BARS + 304;
constexpr uint32_t Q_SET = BARS + 360;
constexpr uint32_t SM_BYTES = 4 * 1024, SX_BYTES = 2560, PX_BYTES = 2 * 14 * 128;
constexpr int W_KR = 29;
constexpr uint32_t W_RING = 0;
constexpr uint32_t W_WS = 196608;
constexpr uint32_t W_FT = 0;
constexpr uint32_t W_FO = 18688;
constexpr uint32_t W_Z = 30720;
constexpr uint32_t W_RS = 49152;
constexpr uint32_t W_ST = 28672;
constexpr int CT_A = 2, CT_B = 6, CT_C = 11;
static_assert(36 * CT_C <= 36 * CT_B + 192, "kv stages");
constexpr uint32_t C_U = 256 + 4096;
constexpr uint32_t C_CH = C_U + 64 + 8192 + 96;
constexpr uint32_t B_FULL = BARS;
constexpr uint32_t B_EMPTY = BARS + 128;
constexpr uint32_t B_FT = BARS + 160;
constexpr uint32_t B_RF = BARS + 176;
constexpr uint32_t W_K1 = BARS + 240;
constexpr uint32_t SMEM_TOTAL = BARS + 512;

struct Params {
  const __nv_bfloat16 *x0, *wq, *wk, *wv, *wo, *mem0, *ck, *cv, *shift, *ssm_k, *ssm_d;
  __nv_bfloat16* out;
  uint4 *part, *memx;
  uint64_t d_x, d_wl, d_ring, d_ws;
};

constexpr uint64_t D_QK = mkdesc(Q_STG, 768, 128, 0), D_WO = mkdesc(Q_WO, 16, 1024, 1), D_OB = mkdesc(Q_OB, 128, 2048, 0), D_PX = mkdesc(Q_PX, 128, 768, 0);
constexpr uint64_t D_V = mkdesc(Q_STG, 128, 768, 0);

#define g_flags (g_flagsets + lds1(sb + Q_SET))

__device__ __forceinline__ int rd_cid() { uint32_t v; asm volatile("mov.u32 %0, %%clusterid.x;" : "=r"(v)); return v; }
__device__ __forceinline__ int rd_rank() { uint32_t v; asm volatile("mov.u32 %0, %%cluster_ctarank;" : "=r"(v)); return v; }
__device__ __forceinline__ int rd_lane() { uint32_t v; asm volatile("mov.u32 %0, %%laneid;" : "=r"(v)); return v; }
__device__ __forceinline__ int rd_warp() { uint32_t v; asm volatile("mov.u32 %0, %%tid.x;" : "=r"(v)); return __shfl_sync(0xffffffffu, v >> 5, 0); }

template <int NA>
__device__ __forceinline__ void proj_step(float (&acc)[NA], const uint32_t* a, uint64_t db, uint64_t dwl, int k) {
  const int ob = (k >> 2) * (Q_CS / 16) + (k & 3) * 16;
  if (k == 0) wg_rs<0, 1>(acc, a, db, ob);
  else if (k % 6 != 5) wg_rs<1, 1>(acc, a + 4 * (k - k / 6), db, ob);
  else wg_ss<1, 1>(acc, dwl, 128 * (k / 6), db, ob);
}
__device__ __forceinline__ void stage_groups(uint32_t stl, const uint32_t (&pk)[14]) {
#pragma unroll
  for (int h = 0; h < 2; h++) {
    stsm4(stl + h * 768 + 256, pk[h], pk[2 + h], pk[4 + h], 0);
    stsm4(stl + h * 768 + 6144 + 128, pk[6 + h], pk[8 + h], pk[10 + h], pk[12 + h]);
  }
}
__device__ __forceinline__ void head_main(uint32_t sb, const Params& P) {
  const int lane = threadIdx.x & 31, warp = rd_warp(), w = warp & 3, wg = warp >> 2, rank = rd_rank();
  uint32_t a[4 * Q_KR];
  {
    const int tid = threadIdx.x & 127;
    const __nv_bfloat16* src = (rank == 2 ? P.wv + wg * 64 : (wg ? P.wk : P.wq) + rank * 64) + rd_cid() * 128 + (size_t)(tid >> 3) * 4096 + (tid & 7) * 8;
    const uint32_t so = (tid >> 3) * 128 + (((tid & 7) ^ ((tid >> 3) & 7)) << 4), st = sb + Q_X + wg * (Q_KR * 2048);
    uint4 v[36];
#pragma unroll
    for (int k = 0; k < 36; k++) v[k] = __ldg((const uint4*)(src + (size_t)k * 65536));
#pragma unroll
    for (int k = 0; k < 36; k++) sts4(so + (k % 6 == 5 ? sb + Q_WL + wg * 12288 + (k / 6) * 2048 : st + (k - k / 6) * 2048), v[k]);
    bar_sync_r(9 + wg, 128);
    PROF_G(7);
    load_afrags<Q_KR>(a, st, w, lane);
    fence_async_smem();
    bar_arrive<11, 384>();
  }
  cluster_sync();
  PROF_G(8);
  const uint64_t dwl = P.d_wl + wg * 768, dq = D_QK + wg * 384;
  const uint32_t stg = sb + Q_STG + wg * 12288 + 2 * w * 768;
  const uint32_t stm = pin(stg + (lane >> 4) * 6144 + ((lane >> 3) & 1) * 768 + (lane & 7) * 16), stl = pin(stg + lane * 16);
  const uint32_t rel = mapa(sb + B_E, 2), sel = pin(threadIdx.x & 127), arm = pin(threadIdx.x - 128 > 8), xfa = pin(sb + B_XF + 8 * lane);
  const uint32_t sx = sb + (wg == rank ? Q_SIN + rank * 4096 : Q_SOUT + 2048), s0 = w ? sx + (2 * w - 1) * 512 : sb + Q_SOUT + wg * 1024, s1 = sx + 2 * w * 512;
  const uint32_t sd0 = pin(s0 + lane * 16), sd1 = pin(s1 + lane * 16), sr = sb + Q_SIN + rank * 4096;
  const int kp = rank == 2 ? KP_V : rank ? KP_1 : KP_0;
  const uint32_t pz = sb + (rank == 2 ? B_SM : B_RES);
  uint32_t pk[14] = {};
#pragma unroll 1
  for (int t = 0;; t++) {
    const uint32_t par = t & 1;
    if (t > 0) {
      float m[12];
#pragma unroll
      for (int c = 0; c < 9; c++) {
        mbar_spin(sb + B_OK + 8 * c, par ^ 1);
        if (c == 0 || c == 3 || c == 8) PROF_W(warp == 0, c == 0 ? 0 : c == 3 ? 1 : 3);
        if (c == 3 || c == 6) { wg_wait<1>(); mbar_rarrive_if0(sel, rel + (c == 6) * 8); }
        if (c == 3) mbar_expect_if0(arm, xfa, 8192);
        if (c == 8) mbar_rarrive_if0(sel | (rank >> 1), rel + 24);
        wg_fence();
#pragma unroll
        for (int k = 4 * c; k < 4 * c + 4; k++) proj_step(m, a, P.d_x, dwl, k);
        if (c % 3 != 0 && c != 7) wg_commit();
      }
      if (rank == 2) {
        if (t > 1) bar_sync<3, 384>();
        stage_groups(stl, pk);
      }
      wg_wait<0>();
      reg_fence(m);
      PROF_W(warp == 0, 2);
      stsm4(stm, pack_bf16(m[0], m[1]), pack_bf16(m[2], m[3]), pack_bf16(m[4], m[5]), pack_bf16(m[6], m[7]));
      stsm2(stm + 128, pack_bf16(m[8], m[9]), pack_bf16(m[10], m[11]));
      mbar_rarrive_if0(sel, rel + 16);
      mbar_expect_if0(arm, xfa - (B_XF - B_CP), 2048);
      if (rank == 2) {
        bar_arrive<1, 384>();
      } else {
        float s[20];
        bar_sync<1, 256>();
        fence_async_smem();
        wg_fence();
        wg_ss<0, 1>(s, dq, 0, dq, 768);
#pragma unroll
        for (int i = 1; i < 4; i++) wg_ss<1, 1>(s, dq, 96 * i, dq, 768 + 96 * i);
        wg_commit();
        wg_wait<0>();
        reg_fence(s);
        if (w < 3) {
          sts4(sd0, make_uint4(pack_bf16(s[0], s[1]), pack_bf16(s[4], s[5]), pack_bf16(s[8], s[9]), pack_bf16(s[12], s[13])));
          if (w != 1) sts1(sd0 + 512, pack_bf16(s[16], s[17]));
          if (w == 0) {
            fence_async_smem();
            __syncwarp();
            if (elect_one()) bulk_s2s(mapa(sr + wg * 1024, 2), s0, 1024, mapa(sb + B_SM, 2));
            __syncwarp();
            PROF_W(wg == 1, 4); PROF_W(wg == 0, 8);
          }
          if (w < 2) sts4(sd1, make_uint4(pack_bf16(s[2], s[3]), pack_bf16(s[6], s[7]), pack_bf16(s[10], s[11]), pack_bf16(s[14], s[15])));
          bar_arrive<8, 224>();
        }
      }
      if (t == NT) break;
    }
    float e[28];
    uint32_t paused = 0;
#pragma unroll
    for (int k = 0; k < 36; k++) {
      if (k % 4 == 0) mbar_wait(sb + B_XF + 2 * k, par);
      if (k == 0) PROF_W(warp == 0, 5);
      if (k % 2 == 0 && k <= KP_MAX) {
        PROF_W(warp == 0 && k == kp, 6);
        mbar_wait_if(paused, pz, sb + B_RES, par ^ 1, k == kp);
      }
      if (k % 4 == 0 || (k % 2 == 0 && k <= KP_MAX)) wg_fence();
      proj_step(e, a, P.d_x + 192, dwl, k);
    }
    wg_commit();
    wg_wait<0>();
    reg_fence(e);
    PROF_W(warp == 0, 10);
#pragma unroll
    for (int i = 0; i < 14; i++) pk[i] = pack_bf16(e[2 * i], e[2 * i + 1]);
    if (rank != 2) stage_groups(stl, pk);
    PROF_W(warp == 0, 12);
  }
  cluster_sync();
}

__device__ __forceinline__ uint32_t next_tick() {
  uint64_t g0, g1;
  asm volatile("mov.u64 %0, %%globaltimer;" : "=l"(g0) :: "memory");
#pragma unroll 1
  for (int n = 0; n < 8; n++) {
    asm volatile("mov.u64 %0, %%globaltimer;" : "=l"(g1) :: "memory");
    if (__any_sync(0xffffffffu, (uint32_t)g1 != (uint32_t)g0)) break;
  }
  return (uint32_t)g1;
}
__device__ __forceinline__ void wait_ns(uint32_t when) {
  uint32_t c;
  asm volatile("{\n.reg .pred p;\n.reg .b64 g;\n.reg .s32 lo;\nS_%=:\nmov.u64 g, %%globaltimer;\ncvt.u32.u64 lo, g;\nsub.s32 lo, %1, lo;\n"
               "setp.gt.s32 p, lo, 31;\n@p bra.uni S_%=;\nmov.u64 g, %%clock64;\ncvt.u32.u64 %0, g;\nshl.b32 lo, lo, 1;\nadd.s32 %0, %0, lo;\n}" : "=&r"(c) : "r"(when) : "memory");
  spin_until(c - 30);
}
template <bool TAG>
__device__ __forceinline__ uint32_t poll4(uint4 (&v)[4], const uint4* src, uint32_t tag) {
#pragma unroll
  for (int j = 0; j < 4; j++) v[j] = ld_poll(src + j * 32);
  uint32_t n = 0;
  while (__any_sync(0xffffffffu, TAG ? (((v[0].x ^ tag) | (v[1].x ^ tag) | (v[2].x ^ tag) | (v[3].x ^ tag)) & 1) != 0
                                     : max(__vimax3_u32(v[0].x, v[1].x, v[2].x), v[3].x) == SENT)) {
#pragma unroll
    for (int j = 0; j < 4; j++) if (TAG ? ((v[j].x ^ tag) & 1) != 0 : v[j].x == SENT) v[j] = ld_poll(src + j * 32);
    if (++n > SPIN_LIMIT) __trap();
  }
  return n;
}

template <int STEP>
__device__ __forceinline__ void check_tiles(uint32_t sb, const Params& P, int w, int t) {
  const int lane = rd_lane();
  const uint32_t last = sb + B_CP + 8 * (STEP == 2 ? 7 + w : 8);
  uint32_t chk = sb + Q_X + w * Q_CS + lane * 32 + (lane >> 2) * 4;
#pragma unroll 1
  for (uint32_t bar = sb + B_CP + 8 * w; bar <= last;) {
    uint32_t ok;
    asm volatile("{\n.reg .pred p, q;\n.reg .b32 a, b;\nsetp.eq.u32 q, %4, 0;\n"
                 "W_%=:\nmbarrier.try_wait.parity.shared::cta.b64 p, [%1], %2;\n@!p bra W_%=;\n"
                 "ld.shared.u32 a, [%3];\nld.shared.u32 b, [%3 + 1024];\nmax.u32 a, a, b;\nsetp.ne.u32 p, a, 0xFFFFFFFF;\n"
                 "vote.sync.all.pred p, p, 0xFFFFFFFF;\nand.pred q, q, p;\n@q mbarrier.arrive.shared::cta.b64 _, [%1 + %5];\nselp.u32 %0, 1, 0, p;\n}"
                 : "=r"(ok) : "r"(bar), "r"(~t & 1), "r"(chk), "r"(lane), "n"(B_OK - B_CP) : "memory");
    const int c = (bar - sb - B_CP) / 8;
    if (!ok) {
      uint4 v[4];
      poll4<false>(v, P.memx + c * 512 + (t & 1) * 128 + lds1(sb + Q_SEL + 4 * c) / 16 + lane, 0);
#pragma unroll
      for (int j = 0; j < 4; j++) sts4(sb + Q_X + c * Q_CS + j * 512 + lane * 16, v[j]);
      fence_async_smem();
      __syncwarp();
      mbar_arrive_if0(lane, bar + B_OK - B_CP);
      if (t > LAG + 4) sts1(sb + Q_REF + 4, lds1(sb + Q_REF + 4) + 1);
      PROF_OR(7, 1 << c);
      PROF_A(c, 1);
    }
    const int d = STEP == 2 && c == 7 ? 1 : STEP;
    bar += 8 * d; chk += d * Q_CS;
  }
}
__device__ __forceinline__ void load_scores(float (&s)[10], uint32_t sa) {
  const uint4 a = lds4(sa), b = lds4(sa + 4096);
  const uint32_t a4 = lds1(sa + 512), b4 = lds1(sa + 4608);
  s[0] = bf_lo(a.x) + bf_lo(b.x); s[1] = bf_hi(a.x) + bf_hi(b.x); s[2] = bf_lo(a.y) + bf_lo(b.y); s[3] = bf_hi(a.y) + bf_hi(b.y);
  s[4] = bf_lo(a.z) + bf_lo(b.z); s[5] = bf_hi(a.z) + bf_hi(b.z); s[6] = bf_lo(a.w) + bf_lo(b.w); s[7] = bf_hi(a.w) + bf_hi(b.w);
  s[8] = bf_lo(a4) + bf_lo(b4); s[9] = bf_hi(a4) + bf_hi(b4);
}
__device__ __forceinline__ void softmax_num(float (&s)[10]) {
  float mx = fmaxf(fmaxf(fmaxf(s[0], s[1]), fmaxf(s[2], s[3])), fmaxf(fmaxf(s[4], s[5]), fmaxf(s[6], s[7])));
  mx = fmaxf(mx, fmaxf(s[8], s[9]));
  const float m1 = __shfl_xor_sync(0xffffffffu, mx, 1), m2 = __shfl_xor_sync(0xffffffffu, mx, 2), m3 = __shfl_xor_sync(0xffffffffu, mx, 3);
  mx = fmaxf(fmaxf(mx, m1), fmaxf(m2, m3));
  mx *= -SM_SCALE;
#pragma unroll
  for (int i = 0; i < 10; i++) s[i] = ex2(fmaf(s[i], SM_SCALE, mx));
}

__device__ __forceinline__ void wo_tiles(uint32_t sb, const uint32_t (&f)[76], char* d0, uint32_t pg, uint32_t rs, int t) {
  float d[2][8];
  wg_fence();
#pragma unroll
  for (int i = 0; i < 4; i++) {
    if (i < 3) {
#pragma unroll
      for (int k = 0; k < 8; k++) {
        if (i == 2 && ((k & 1) || k == 6)) wg_ss<1, 0>(d[0], D_WO, 2048 + 128 * k, D_OB, 16 * k);
        else if (k == 0) wg_rs<0, 0>(d[i & 1], f + 32 * i, D_OB, 0);
        else wg_rs<1, 0>(d[i & 1], f + (i < 2 ? 32 * i + 4 * k : 64 + 2 * k), D_OB, 16 * k);
        if (i == 2 && k == RS_V) wg_commit();
      }
      wg_commit();
    }
    if (i > 0) {
      if (i == 1) wg_wait<1>(); else if (i == 2) wg_wait<2>(); else wg_wait<0>();
      float (&q)[8] = d[(i - 1) & 1];
      reg_fence(q);
      st_gpu4((uint4*)d0, (pack_bf16(q[0], q[1]) & ~1u) | ((t - 1) >> 1 & 1), pack_bf16(q[4], q[5]), pack_bf16(q[2], q[3]), pack_bf16(q[6], q[7]));
      __syncwarp();
      if (i == 2) { wg_wait<1>(); mbar_arrive_if0(rs, sb + B_RES); }
      d0 += i == 1 ? pg & 0xFFFF : pg >> 16;
      PROF_W(threadIdx.x < 288, 13 + i);
      if (i == 1) wg_fence();
    }
  }
}
__device__ __forceinline__ void head_aux(uint32_t sb, const Params& P) {
  const int tid = threadIdx.x & 127, w = rd_warp() & 3, rank = rd_rank(), head = __shfl_sync(0xffffffffu, rd_cid(), 0);
#pragma unroll 1
  for (int i = 0; i < 3; i++) {
    uint4 a[4], b[4];
#pragma unroll
    for (int u = 0; u < 4; u++) {
      const int r = u * 32 + (tid >> 2);
      const uint4* src = (const uint4*)(P.wo + (size_t)(head * 128 + (r & 64) + (r & 7) * 8 + ((r >> 3) & 7)) * DM + (6 - 3 * rank + i) * 64) + (tid & 3) * 2;
      a[u] = __ldg(src); b[u] = __ldg(src + 1);
    }
#pragma unroll
    for (int u = 0; u < 4; u++) {
      const int r = u * 32 + (tid >> 2);
      const uint32_t dst = sb + Q_WO + i * 16384 + r * 128 + ((((tid & 3) * 2) ^ (r & 7) ^ ((head >> 2) & 1)) << 4);
      sts4(dst, make_uint4(__byte_perm(a[u].x, a[u].y, 0x5410), __byte_perm(a[u].z, a[u].w, 0x5410), __byte_perm(b[u].x, b[u].y, 0x5410), __byte_perm(b[u].z, b[u].w, 0x5410)));
      sts4(dst ^ 16, make_uint4(__byte_perm(a[u].x, a[u].y, 0x7632), __byte_perm(a[u].z, a[u].w, 0x7632), __byte_perm(b[u].x, b[u].y, 0x7632), __byte_perm(b[u].z, b[u].w, 0x7632)));
    }
  }
#pragma unroll
  for (int i = 0; i < 6; i++) sts4(sb + Q_PX + (i * 128 + tid) * 16, make_uint4(0, 0, 0, 0));
  char* pd;
  uint32_t pg;
  {
    const int lane = tid & 31, dcta = (w * 8 + (lane >> 2)) * 3 + rank;
    uint4 f;
    uint32_t n = 0;
    do {
      f = ld_poll((const uint4*)(g_flags + FL_SEL) + dcta);
      if (++n > SPIN_LIMIT) __trap();
    } while (__any_sync(0xffffffffu, !f.x || !f.y || !f.z));
    pd = (char*)P.part + (dcta * 1536 + head * 4 + (lane & 3) + (f.x - 1) * 256) * 16;
    pg = (8192 + (f.y - f.x) * 4096) | (8192 + (f.z - f.y) * 4096) << 16;
  }
  bar_sync<11, 384>();
#pragma unroll 1
  for (int k = tid; k < DM; k += 128) {
    uint32_t q[4];
#pragma unroll
    for (int j = 0; j < 4; j++) q[j] = min(__bfloat16_as_ushort(P.mem0[2 * j * DM + k]) | (uint32_t)__bfloat16_as_ushort(P.mem0[(2 * j + 1) * DM + k]) << 16, SENT - 1);
    sts4(sb + Q_X + (k >> 6) * Q_CS + (k & 63) * 16, make_uint4(q[0], q[1], q[2], q[3]));
    sts4(sb + Q_X + (k >> 6) * Q_CS + (k & 63) * 16 + 1024, make_uint4(q[0], q[1], q[2], q[3]));
  }
#pragma unroll
  for (int i = 0; i < 2; i++) sts4(sb + Q_STG + (i * 16 + (tid >> 3)) * 768 + 640 + (tid & 7) * 16, make_uint4(0, 0, 0, 0));
  fence_async_smem();
  PROF_G(2);
  const uint32_t wa = pin(sb + Q_WO + ((tid >> 4 & 1) * 8 + (tid & 7)) * 128 + (((2 * w + ((tid >> 3) & 1)) ^ (tid & 7)) << 4));
  uint32_t f[76];
  if (rank != 2) {
#pragma unroll
    for (int k = 0; k < 19; k++) ldsm4t(f[4 * k], f[4 * k + 1], f[4 * k + 2], f[4 * k + 3], wa + (k < 16 ? k : 2 * k - 16) * 2048);
    const uint32_t rs = pin(tid);
    cluster_sync();
#pragma unroll 1
    for (int t = 1;; t++) {
      pd = (char*)((uintptr_t)pd ^ 2048);
      check_tiles<4>(sb, P, w, t);
      if (w == 0) {
        bar_sync<8, 224>();
        fence_async_smem();
        if (elect_one()) {
          bulk_s2s(mapa(sb + Q_SIN + rank * 4096, rank ^ 1), sb + Q_SOUT + 2048, SX_BYTES, mapa(sb + B_SM, rank ^ 1));
          mbar_arrive(sb + B_SM);
        }
        __syncwarp();
      }
      if (t == NT) break;
      mbar_spin(sb + B_O, (t - 1) & 1);
      PROF_W(w == 0, 13);
      wo_tiles(sb, f, pd, pg, rs, t);
      mbar_expect_if0(rs, sb + B_O, 4096);
    }
  } else {
#pragma unroll
    for (int k = 0; k < 8; k++) ldsm4t(f[4 * k], f[4 * k + 1], f[4 * k + 2], f[4 * k + 3], wa + k * 2048);
    cluster_sync();
    const int l = w & 1, tile = w >> 1;
    const uint32_t ob = pin(sb + Q_OB + (l ^ ((head >> 1) & 1)) * 2048 + tile * 1024 + (tid >> 2 & 7) * 128 + (tid & 3) * 16);
    const uint32_t ob0 = sb + Q_OB + ((head >> 1) & 1) * 2048;
    const uint32_t sa = pin(sb + Q_SIN + l * 1024 + (tid & 31) * 16);
#pragma unroll 1
    for (int t = 1; t <= NT; t++) {
      const uint32_t par = (t - 1) & 1;
      {
        uint32_t vf[4][10], p[5];
        float s[10], o[4][4];
        const int lane = rd_lane();
        const uint32_t vb = sb + Q_STG + tile * 12288 + l * 6144 + (lane & 7) * 16;
        const uint32_t ax = vb + ((lane >> 3) & 1) * 768 + (lane >> 4) * 128;
        pd = (char*)((uintptr_t)pd ^ 2048);
        bar_sync<1, 384>();
#pragma unroll
        for (int i = 0; i < 4; i++) ldsm4(vf[i][4], vf[i][5], vf[i][6], vf[i][7], ax + i * 1536 + 256);
        ldsm4(vf[0][8], vf[0][9], vf[1][8], vf[1][9], vb + (lane >> 3) * 768 + 512);
        ldsm4(vf[2][8], vf[2][9], vf[3][8], vf[3][9], vb + (lane >> 3) * 768 + 512 + 3072);
#pragma unroll
        for (int i = 0; i < 4; i++) ldsm4(vf[i][0], vf[i][1], vf[i][2], vf[i][3], ax + i * 1536);
        mbar_spin(sb + B_SM, par);
        PROF_W(w == 0, 20);
        if (t < NT) {
          load_scores(s, sa);
          __syncwarp();
          softmax_num(s);
#pragma unroll
          for (int j = 0; j < 5; j++) p[j] = pack_bf16(s[2 * j], s[2 * j + 1]);
          __syncwarp();
          PROF_W(w == 0, 9);
          float z[4] = {0.f, 0.f, 0.f, 0.f};
          const uint32_t ONE = 0x3F803F80u;
          mma16816(z, ONE, ONE, ONE, ONE, p[0], p[1]);
#pragma unroll
          for (int i = 0; i < 4; i++) { o[i][0] = o[i][1] = o[i][2] = o[i][3] = 0.f; mma16816(o[i], vf[i][0], vf[i][1], vf[i][2], vf[i][3], p[0], p[1]); }
#pragma unroll
          for (int k = 8; k < 12; k++) ldsm4t(f[4 * k], f[4 * k + 1], f[4 * k + 2], f[4 * k + 3], wa + k * 2048);
          mma16816(z, ONE, ONE, ONE, ONE, p[2], p[3]);
#pragma unroll
          for (int i = 0; i < 4; i++) mma16816(o[i], vf[i][4], vf[i][5], vf[i][6], vf[i][7], p[2], p[3]);
#pragma unroll
          for (int k = 12; k < 16; k++) ldsm4t(f[4 * k], f[4 * k + 1], f[4 * k + 2], f[4 * k + 3], wa + k * 2048);
          mma1688(z, ONE, ONE, p[4]);
#pragma unroll
          for (int i = 0; i < 4; i++) mma1688(o[i], vf[i][8], vf[i][9], p[4]);
#pragma unroll
          for (int k = 16; k < 19; k++) ldsm4t(f[4 * k], f[4 * k + 1], f[4 * k + 2], f[4 * k + 3], wa + (2 * k - 16) * 2048);
          const float r0 = rcp(z[0]), r1 = rcp(z[1]);
          const uint4 u0 = make_uint4(pack_bf16(o[0][0] * r0, o[0][2] * r0), pack_bf16(o[1][0] * r0, o[1][2] * r0),
                                      pack_bf16(o[2][0] * r0, o[2][2] * r0), pack_bf16(o[3][0] * r0, o[3][2] * r0));
          const uint4 u1 = make_uint4(pack_bf16(o[0][1] * r1, o[0][3] * r1), pack_bf16(o[1][1] * r1, o[1][3] * r1),
                                      pack_bf16(o[2][1] * r1, o[2][3] * r1), pack_bf16(o[3][1] * r1, o[3][3] * r1));
          PROF_W(w == 0, 8);
          sts4(ob, u0);
          sts4(ob + 64, u1);
          bar_sync<5, 160>();
          fence_async_smem();
          PROF_W(w == 0, 13);
          wo_tiles(sb, f, pd, pg, ob ^ ob0, t);
        }
      }
      const int lane = rd_lane();
      mbar_expect_if0(lane | w, sb + B_SM, SM_BYTES);
      if (t < NT) bar_sync<12, 160>();
      {
        float o[3][16];
        const uint32_t ox = sb + Q_OX + 2 * w * 512 + lane * 16;
        const uint64_t dp = D_PX + (t & 1) * 384;
        fence_async_smem();
        mbar_wait(sb + B_P + 8 * (t & 1), ((t - 1) >> 1) & 1);
        PROF_W(w == 0, 7);
#pragma unroll
        for (int j = 0; j < 7; j++) {
          if (j >= 3) {
            const int i = j - 3;
            if (i == 0) mbar_wait(sb + B_OXFREE, par ^ 1);
            if (i < 2) wg_wait<2>(); else if (i == 2) wg_wait<0>();
            if (i == 2 && t < NT) bar_arrive<3, 384>();
            reg_fence(o[i % 3]);
#pragma unroll
            for (int h = 0; h < 2; h++)
              stsm4(ox + i * 4096 + h * 512, pack_bf16(o[i % 3][2 * h], o[i % 3][2 * h + 1]), pack_bf16(o[i % 3][4 + 2 * h], o[i % 3][5 + 2 * h]),
                    pack_bf16(o[i % 3][8 + 2 * h], o[i % 3][9 + 2 * h]), pack_bf16(o[i % 3][12 + 2 * h], o[i % 3][13 + 2 * h]));
          }
          if (j < 4) {
            if (j % 3 == 0) wg_fence();
            wg_sskk<0>(o[j % 3], D_V, (j >> 1) * 384 + (j & 1) * 768, dp, (j >> 1) * 192);
            wg_sskk<1>(o[j % 3], D_V, (j >> 1) * 384 + (j & 1) * 768 + 16, dp, (j >> 1) * 192 + 16);
            wg_sskk<1>(o[j % 3], D_V, (j >> 1) * 384 + (j & 1) * 768 + 32, dp, (j >> 1) * 192 + 32);
            wg_commit();
          }
        }
        mbar_expect_if0(lane | w, sb + B_P + 8 * (t & 1), PX_BYTES);
      }
      fence_async_smem();
      __syncwarp();
      mbar_arrive_if0(lane, sb + B_OXREADY);
      PROF_W(w == 0, 23);
    }
  }
  cluster_sync();
}

__device__ __forceinline__ void softmax_x(uint32_t sb, int w, int rank, int t) {
  float s[10];
  const int lane = rd_lane();
  mbar_wait(sb + B_SM, (t - 1) & 1);
  PROF_W(w == 3, 20);
  load_scores(s, sb + Q_SIN + w * 512 + lane * 16);
  const int last = 8 + 8 * w + (lane >> 2) - 2 * (lane & 3);
#pragma unroll
  for (int i = 2; i < 10; i++) s[i] = (8 * (i >> 1) + (i & 1) <= last) ? s[i] : -INFINITY;
  softmax_num(s);
  float sum = ((s[0] + s[1]) + (s[2] + s[3])) + ((s[4] + s[5]) + (s[6] + s[7])) + (s[8] + s[9]);
  sum += __shfl_xor_sync(0xffffffffu, sum, 1);
  sum += __shfl_xor_sync(0xffffffffu, sum, 2);
  const float r = rcp(sum);
  const uint32_t po = sb + Q_SOUT + 6144 + w * 768;
#pragma unroll
  for (int j = 0; j < 5; j++) sts1(po + lane * 4 + j * 128, pack_bf16(s[2 * j] * r, s[2 * j + 1] * r));
  fence_async_smem();
  __syncwarp();
  if (elect_one()) bulk_s2s(mapa(sb + Q_PX + ((t & 1) * 2 + rank) * 3072 + w * 768, 2), po, 128 * (w + 2), mapa(sb + B_P + 8 * (t & 1), 2));
  __syncwarp();
  PROF_W(w == 3, 22);
}

__device__ __forceinline__ uint32_t bf2_op(uint32_t a, uint32_t b, uint32_t c) {
  uint32_t r; asm("fma.rn.bf16x2 %0, %1, %2, %3;" : "=r"(r) : "r"(a), "r"(b), "r"(c)); return r;
}
__device__ __forceinline__ uint32_t bf2_mul(uint32_t a, uint32_t b) {
  uint32_t r; asm("mul.rn.bf16x2 %0, %1, %2;" : "=r"(r) : "r"(a), "r"(b)); return r;
}
__device__ __forceinline__ uint32_t bf2_add(uint32_t a, uint32_t b) {
  uint32_t r; asm("add.rn.bf16x2 %0, %1, %2;" : "=r"(r) : "r"(a), "r"(b)); return r;
}
__device__ __forceinline__ void head_service(uint32_t sb, const Params& P) {
  const int lane = threadIdx.x & 31, rank = rd_rank(), w = rd_warp() & 3, i3 = w - 1;
  const int head = rd_cid(), c = 6 - 3 * rank + i3;
  uint32_t dof = c * 8192 + (lane & 4) * 1024 + (lane & 8) * 128 + head * 32 + (lane & 16) + (lane & 3) * 4;
  uint32_t sof = (blockIdx.x * 3 + i3) * 8192, gof = 0, dly = i3 * D_TILE, g0 = 0, c0 = 0, ref = 0;
  if (w) {
    sof += __shfl_sync(0xffffffffu, lds1(sb + Q_SEL + 36 + 4 * i3), 0);
    gof = c * 8192 + __shfl_sync(0xffffffffu, lds1(sb + Q_SEL + 4 * c), 0);
#pragma unroll 1
    for (int j = 0; j < 8; j++) st_gpu4((uint4*)((char*)P.part + sof) + j * 32 + lane, SENT, SENT, SENT, SENT);
    st_gpu1((uint32_t*)((char*)P.memx + dof), SENT);
    st_gpu1((uint32_t*)((char*)P.memx + dof + 2048), SENT);
    __syncwarp();
    asm volatile("st.release.gpu.global.u32 [%0], %1;" :: "l"(g_flags + FL_SEL + blockIdx.x * 4 + i3), "r"(((sof >> 12) & 1) + 1) : "memory");
  }
  cluster_sync();
#pragma unroll 1
  for (int t = 0; t <= NT; t++) {
    if (w == 0 && rank == 2 && t < NT) {
      const uint32_t* fl = g_flags + FL_XS + t * 32;
      warp_flag_wait(fl + (lane & 1 ? (t >= LAG ? 16 : 0) : (t <= NSEG ? 0 : 16)), 4);
      fence_async_global();
      const char* src = (const char*)g_xs + (size_t)t * 73728;
      const uint32_t dst = sb + Q_X + 2048, ep = (t - 1) & 1;
      uint32_t at = 0;
#pragma unroll 1
      for (int k = 0; k < 9; k++) {
        if (t > 0 && (k == 0 || k == 2 || k == 5)) mbar_wait(sb + B_E + (k + 1) / 3 * 8, ep);
        if (k == 0) { at = rd_clock() + XA_V; PROF_T(24); PROF_MID(); }
        spin_until(at);
        if (elect_one()) bulk_g2s_mc(dst + k * Q_CS, src + k * 8192, 8192, sb + B_XF + 8 * k, 7);
        __syncwarp();
        at += k < 2 ? XB_V : k == 2 ? XD_V : XP_V;
      }
      if (t == 0) PROF_G(31);
    }
    if (t == 0) continue;
    if (rank == 2 && (w == 1 || w == 2)) check_tiles<2>(sb, P, w - 1, t);
    if (w == (rank == 2) && t < NT) {
      const uint32_t* tms = (const uint32_t*)(P.memx + 9 * 512 + lds1(sb + Q_SEL + 48) / 16 + (head >> 4) * 32 + lane) + rank;
      const uint32_t due = ref + D_GX + (D_DUE - rank_delay(rank)) * 9 / 16;
      if (rank == 2) {
        const uint32_t g1 = next_tick(), c1 = rd_clock();
        const uint32_t rate = t > 1 ? __float2uint_rn(65536.f * (g1 - g0) * rcp(c1 - c0)) : 36400;
        g0 = g1; c0 = c1;
        uint4* pub = P.memx + 9 * 512 + (lane & 1) * 256 + (lane & 2) * 16 + head;
        const uint32_t lead = D_RED * rate >> 16, late = D_LATE * rate >> 16, r1 = rank_delay(1) * rate >> 10, r0 = rank_delay(0) * rate >> 10;
        mbar_wait(sb + B_E, (t - 1) & 1);
        mbar_spin(sb + B_E + 24, (t - 1) & 1);
        uint32_t now = g0 + ((rd_clock() - c0) * rate >> 16);
        now = (now + (t == 1 || (int)(now + 90 - due) > 0 ? late : lead)) << 6;
        st_gpu4(pub, ((now + r0) & ~255u) | t, ((now + r1) & ~255u) | t, (now & ~255u) | t, 0);
        PROF_T(22);
      } else {
        mbar_wait(sb + B_OK + 64, (t - 1) & 1);
      }
      if (t > 1) wait_ns(due); else ref = next_tick();
      uint32_t d, n = 0;
      do {
        asm volatile("ld.relaxed.gpu.global.u32 %0, [%1];" : "=r"(d) : "l"(tms) : "memory");
        if (++n > SPIN_LIMIT) __trap();
      } while (__any_sync(0xffffffffu, (d ^ t) & 255));
      ref += __reduce_max_sync(0xffffffffu, (int)(d - (ref << 6))) >> 6;
      sts1(sb + Q_REF, ref);
      __syncwarp();
      mbar_arrive_if0(lane, sb + B_REF);
      PROF_A(13, n);
      PROF_T(19);
    }
    if (w == 2 && rank == 2 && t < NT) {
      bar_sync<5, 160>();
      fence_async_smem();
      if (elect_one()) {
        bulk_s2s(mapa(sb + Q_OB, 1), sb + Q_OB, 4096, mapa(sb + B_O, 1));
        bulk_s2s(mapa(sb + Q_OB, 0), sb + Q_OB, 4096, mapa(sb + B_O, 0));
      }
      __syncwarp();
    }
    if (rank != 2) {
      softmax_x(sb, w, rank, t);
      if (w == 0 && t < NT) bar_arrive<7, 64>();
      mbar_expect_if0(lane | (w - 1), sb + B_SM, SX_BYTES);
    }
    if (w && t < NT) {
      mbar_wait(sb + B_REF, (t - 1) & 1);
      uint32_t when = lds1(sb + Q_REF) + dly;
      sof ^= 2048; dof ^= 2048;
      uint4* src = (uint4*)((char*)P.part + sof) + lane;
      uint32_t* dst = (uint32_t*)((char*)P.memx + (dof ^ 2048));
      const bool inj = t == LAG && (lane & 8);
      if (t == LAG) {
        const __nv_bfloat16* m0 = P.mem0 + (lane & 3) * 2 * DM + c * 64 + head * 2 + (lane >> 4);
        st_gpu1_if(inj, dst, min(__bfloat16_as_ushort(m0[0]) | (uint32_t)__bfloat16_as_ushort(m0[DM]) << 16, SENT - 1));
      }
      asm volatile("" : "+l"(dst), "+l"(src));
      uint4 v[4];
      wait_ns(when);
      PROF_W(i3 == 0, 18);
      const uint32_t nr = poll4<true>(v, src, (t - 1) >> 1);
      PROF_T(26 + i3);
      const uint32_t z = bf2_add(bf2_add(v[0].z, v[1].z), bf2_add(v[2].z, v[3].z)), u = bf2_add(bf2_add(v[0].w, v[1].w), bf2_add(v[2].w, v[3].w));
      const uint32_t x = bf2_add(bf2_add(v[0].x, v[1].x), bf2_add(v[2].x, v[3].x)), y = bf2_add(bf2_add(v[0].y, v[1].y), bf2_add(v[2].y, v[3].y));
      const uint32_t x2 = bf2_add(x, __shfl_xor_sync(0xffffffffu, z, 16)), y2 = bf2_add(y, __shfl_xor_sync(0xffffffffu, u, 16));
      const uint32_t x3 = bf2_add(x2, __shfl_xor_sync(0xffffffffu, y2, 8));
      st_gpu1_if(!inj, dst, bf2_add(x3, __shfl_xor_sync(0xffffffffu, x3, 4)));
      if (w == 3 && rank == 2) bar_arrive<12, 160>();
      PROF_T(29 + i3);
      PROF_A(10 + i3, nr);
      when += D_GX + min(lds1(sb + Q_REF + 4), 8u) * D_ADAPT;
      if (nr && t > LAG + 3 && dly < i3 * D_TILE + 8 * D_ADAPT) dly += D_ADAPT;
      fence_async_global();
      if (w == 3 && rank != 2) bar_sync<7, 64>();
      wait_ns(when);
      if (elect_one()) bulk_g2s_mc(sb + Q_X + c * Q_CS, (const char*)P.memx + gof + (~t & 1) * 2048, 2048, sb + B_CP + 8 * c, 7);
      __syncwarp();
      if (i3 == 0) PROF_T(21);
      st_gpu1((uint32_t*)((char*)P.memx + dof), SENT);
    }
    if (w == 3 && rank == 2) {
      if (t < NT) mbar_wait(sb + B_XF, t & 1); else warp_flag_wait(g_flags + FL_XS + NT * 32 + 16, 4);
      mbar_wait(sb + B_OXREADY, (t - 1) & 1);
      if (elect_one()) {
        uint4* od = g_ox + (size_t)(t & (OXRING - 1)) * 32768 + head * 512;
        if (t <= NSEG) bulk_s2g(od, sb + Q_OX, 8192);
        if (t > LAG) bulk_s2g(od + 16384, sb + Q_OX + 8192, 8192);
        bulk_commit_wait();
        mbar_arrive(sb + B_OXFREE);
        flag_add(g_flags + FL_OX + t * 32 + head);
      }
      __syncwarp();
      PROF_T(25);
    }
  }
  cluster_sync();
}

__global__ void __cluster_dims__(3, 1, 1) __launch_bounds__(512, 1) head_kernel(const Params P) {
  extern __shared__ uint8_t smem_raw[];
  const uint32_t sb = (uint32_t)__cvta_generic_to_shared(smem_raw);
  if ((sb & 0xFFFFFFu) != SB0) __trap();
  asm volatile("griddepcontrol.launch_dependents;");
  if (threadIdx.x < 96) {
    const int i = blockIdx.x * 24 + threadIdx.x % 24, m = threadIdx.x / 24;
    const __nv_bfloat16* p = m == 3 ? P.ssm_k + (size_t)(i >> 2) * SEQ + (i & 3) * 64 : (m == 0 ? P.ck : m == 1 ? P.cv : P.x0) + (size_t)i * 64;
    asm volatile("prefetch.global.L2 [%0];" :: "l"(p));
  } else if (threadIdx.x == 96 && blockIdx.x < 45) {
    asm volatile("prefetch.global.L2 [%0];" :: "l"(blockIdx.x < 36 ? P.shift + blockIdx.x * 64 : P.ssm_d + (blockIdx.x - 36) * 64));
  }
  PROF_BEGIN();
  {
    const int wp = rd_warp();
    if (wp == 13) sts1(sb + Q_SET, (__ldcg(&g_epoch) & 1) * FL_TOTAL);
    if (wp <= 12) {
      const uint32_t sel = __shfl_sync(0xffffffffu, near_page(wp < 9 ? P.memx + wp * 512 + (blockIdx.x & 63) * 2 :
          wp < 12 ? P.part + (blockIdx.x * 3 + wp - 9) * 512 : P.memx + 9 * 512 + 128 + (blockIdx.x & 63) * 2), 0);
      sts1(sb + Q_SEL + 4 * wp, sel * 4096);
    }
  }
  const int rank = rd_rank(), wg = rd_warp() >> 2;
  if (threadIdx.x == 448) {
    for (int c = 0; c < 9; c++) { mbar_init(sb + B_CP + 8 * c, 1); mbar_arrive(sb + B_CP + 8 * c); mbar_init(sb + B_OK + 8 * c, 1); mbar_init(sb + B_XF + 8 * c, 1); mbar_expect(sb + B_XF + 8 * c, 8192); }
    mbar_init(sb + B_E, 6); mbar_init(sb + B_E + 8, 6); mbar_init(sb + B_E + 16, 6); mbar_init(sb + B_E + 24, 4);
    mbar_init(sb + B_SM, rank == 2 ? 1 : 2); mbar_init(sb + B_O, 1); mbar_init(sb + B_P, 1); mbar_init(sb + B_P + 8, 1);
    mbar_init(sb + B_REF, 1); mbar_init(sb + B_RES, 1); mbar_init(sb + B_OXREADY, 4); mbar_init(sb + B_OXFREE, 1);
    mbar_expect(sb + B_SM, rank == 2 ? SM_BYTES : SX_BYTES); mbar_expect(sb + B_P, PX_BYTES); mbar_expect(sb + B_P + 8, PX_BYTES);
    mbar_expect(sb + B_O, 4096);
    sts1(sb + Q_REF + 4, 0);
    asm volatile("fence.mbarrier_init.release.cluster;" ::: "memory");
  }
  __syncthreads();
  PROF_G(6);
  if (wg < 2) {
    asm volatile("setmaxnreg.inc.sync.aligned.u32 176;");
    head_main(sb, P);
    PROF_END();
  } else if (wg == 2) {
    asm volatile("setmaxnreg.dec.sync.aligned.u32 120;");
    head_aux(sb, P);
    PROF_END();
  } else {
    asm volatile("setmaxnreg.dec.sync.aligned.u32 40;");
    head_service(sb, P);
    PROF_END();
  }
}

__device__ __forceinline__ void tail_gemm(uint32_t sb, const Params& P) {
  const int lane = threadIdx.x & 31, warp = rd_warp(), w = warp & 3, wg = warp >> 2, tid = threadIdx.x & 127;
  const __nv_bfloat16* wsrc = P.wo + (size_t)(blockIdx.x / 3) * 512 * DM + (blockIdx.x % 3) * 192 + wg * 64;
  uint32_t a[4 * W_KR];
  load_rows<29>(sb + wg * 65536, wsrc, DM, W_KR * 16, tid, 128);
  load_rows<3>(sb + W_WS + wg * 6144, wsrc + (size_t)W_KR * 16 * DM, DM, 512 - W_KR * 16, tid, 128);
  bar_sync_r(9 + wg, 128);
  load_afrags<W_KR>(a, sb + wg * 65536, w, lane);
  fence_async_smem();
  bar_sync<1, 416>();
  PROF_G(26);
  if (wg == 2) bar_arrive<2, 256>();
  const uint64_t dw = P.d_ws + wg * 384;
  float4* dst0 = g_acc + ((blockIdx.x % 3) * 12 + warp) * 32 + lane;
#pragma unroll 1
  for (int t = 1; t <= NT; t++) {
#pragma unroll 1
    for (int l = t > NSEG; l <= (t > LAG); l++) {
      const int seg = t - 1 - l * LAG, grp = (seg & 1) * 2 + l;
      const uint64_t db = P.d_ring + grp * 2048;
      float acc[16];
      bar_sync_r(2 + wg, 256);
#pragma unroll
      for (int c = 0; c < 4; c++) {
        if (wg == 0) mbar_wait(sb + B_FULL + 32 * grp + 8 * c, (seg >> 1) & 1);
        if (c == 0) PROF_T(6 * l + wg);
        wg_fence();
#pragma unroll
        for (int i = 0; i < 8; i++) {
          if (c == 0 && i == 0) wg_rs<0, 1>(acc, a, db, 0);
          else if (8 * c + i < W_KR) wg_rs<1, 1>(acc, a + 32 * c + 4 * i, db, 512 * c + 64 * i);
          else wg_ss<1, 1>(acc, dw, 128 * (8 * c + i - W_KR), db, 512 * c + 64 * i);
        }
      }
      wg_commit();
      bar_arrive_r(wg == 2 ? 2 : 3 + wg, 256);
      wg_wait<0>();
      reg_fence(acc);
      mbar_arrive_if0(tid, sb + B_EMPTY + 8 * grp);
      float4* dst = dst0 + (size_t)(l * 256 + seg * 4) * 1152;
#pragma unroll
      for (int j = 0; j < 4; j++)
        asm volatile("red.relaxed.gpu.global.add.v4.f32 [%0], {%1,%2,%3,%4};" :: "l"(dst + j * 1152),
                     "f"(acc[4 * j]), "f"(acc[4 * j + 1]), "f"(acc[4 * j + 2]), "f"(acc[4 * j + 3]) : "memory");
      bar_sync_r(5 + wg, 160);
    }
  }
}
__device__ __forceinline__ void tail_service(uint32_t sb) {
  const int lane = threadIdx.x & 31, warp = rd_warp();
  if (warp == 12) bar_sync<1, 416>();
#pragma unroll 1
  for (int t = 1; t <= NT; t++) {
    if (warp == 12) {
      const int h0 = (blockIdx.x / 3) * 4;
      warp_flag_wait(g_flags + FL_OX + t * 32 + h0 + (lane & 3), 1);
      fence_async_global();
#pragma unroll 1
      for (int l = t > NSEG; l <= (t > LAG); l++) {
        const int seg = t - 1 - l * LAG, grp = (seg & 1) * 2 + l;
        const uint4* src = g_ox + (size_t)(t % OXRING) * 32768 + l * 16384 + h0 * 512;
        const uint32_t bar = sb + B_FULL + 32 * grp;
        mbar_wait_lim(sb + B_EMPTY + 8 * grp, ((seg >> 1) & 1) ^ 1);
        mbar_expect_if0(lane > 3, bar + 8 * lane, 8192);
        if (elect_one()) {
#pragma unroll
          for (int j = 0; j < 4; j++) bulk_g2s(sb + W_RING + (grp * 4 + j) * 8192, src + j * 512, 8192, bar + 8 * j);
        }
        __syncwarp();
      }
      PROF_T(12);
      PROF_MID();
    } else {
#pragma unroll 1
      for (int l = t > NSEG; l <= (t > LAG); l++) {
        bar_sync_r(warp - 8, 160);
        if (lane == 0) flag_add(g_flags + FL_ACC + (l * 64 + t - 1 - l * LAG) * 32);
        __syncwarp();
        PROF_T(6 * l + warp - 10);
      }
    }
  }
}

__device__ __forceinline__ void wait_k1(uint32_t sb, int n) {
  uint32_t c = 0;
  while ((int)lds1(sb + W_K1) < n) {
    __nanosleep(64);
    if (++c > SPIN_LIMIT) __trap();
  }
}
__device__ __forceinline__ void tail_finisher(uint32_t sb, const Params& P) {
  const int lane = threadIdx.x & 31, warp = rd_warp(), kind = warp < 12 ? warp / 6 : warp & 1, f = warp - 6 * kind, tg = blockIdx.x & 3;
  if (warp >= 14) {
    const uint32_t set = lds1(sb + Q_SET), ft = sb + W_FO + kind * 576;
    if (tg == 0) for (int i = kind * 32 + lane; i < FL_TOTAL; i += 64) g_flagsets[FL_TOTAL - set + i] = 0;
#pragma unroll 1
    for (int t = 0; t < NSEG; t++) {
      warp_flag_wait(g_flags + FL_ACC + (64 + t) * 32, 72);
      PROF_T(17);
      if (t == 0 && tg == 0 && threadIdx.x == 448) g_epoch = set ? 0 : 1;
      const float4* ac = g_acc + ((size_t)(256 + t * 4 + tg) * 36 + kind * 18) * 32 + lane;
      float4 v[18];
#pragma unroll
      for (int i = 0; i < 18; i++) v[i] = __ldcg(ac + i * 32);
#pragma unroll
      for (int i = 0; i < 9; i++) {
        const uint4 r = lds4(sb + W_RS + (8 + (t & 7)) * 9216 + (kind * 9 + i) * 512 + lane * 16);
        stsm4t(ft + (lane & 7) * 1168 + (lane >> 3) * 16 + 64 * i, bf2_add(r.x, pack_bf16(v[2 * i].x, v[2 * i].y)), bf2_add(r.y, pack_bf16(v[2 * i].z, v[2 * i].w)),
               bf2_add(r.z, pack_bf16(v[2 * i + 1].x, v[2 * i + 1].y)), bf2_add(r.w, pack_bf16(v[2 * i + 1].z, v[2 * i + 1].w)));
      }
      fence_async_smem();
      __syncwarp();
      mbar_arrive_if0(lane, sb + B_RF + 8 * (t & 7));
      wait_k1(sb, min(t + LAG + 1, NSEG));
      if (lane < 8) {
        bulk_s2g(P.out + (size_t)((t * 4 + tg) * 8 + lane) * DM + kind * 288, ft + lane * 1168, 576);
        bulk_commit_wait();
      }
      __syncwarp();
      PROF_T(18);
    }
    return;
  }
  if (warp >= 12) {
    for (int i = kind * 32 + lane; i < 1152; i += 64) sts4(sb + W_Z + i * 16, make_uint4(0, 0, 0, 0));
    fence_async_smem();
    bar_sync<12, 64>();
#pragma unroll 1
    for (int t = -1; t <= NSEG; t++) {
      if (kind == 0 && t + 1 < NSEG) {
        const uint32_t bar = sb + B_FT + 8 * ((t + 1) & 1);
        mbar_expect_if0(lane, bar, 9216);
        __syncwarp();
        if (lane < 8) bulk_g2s(sb + W_FT + ((t + 1) & 1) * 9344 + lane * 1168, P.x0 + (size_t)(((t + 1) * 4 + tg) * 8 + lane) * DM, 1152, bar);
      }
      if (t < 0) continue;
      if (t < NSEG) bar_sync_r(9 + 2 * kind, 224);
      if (lane == 0) {
        flag_add(g_flags + FL_XS + (t + kind * LAG) * 32 + kind * 16);
        if (kind) { sts1(sb + W_K1, t + 1); PROF_T(14); }
        if (kind ? t < NSEG : t < LAG) bulk_s2g(g_acc + (size_t)(kind * 256 + t * 4 + tg) * 1152, sb + W_Z, 18432);
        if (kind && t + LAG < NSEG) bulk_s2g(g_acc + (size_t)((t + LAG) * 4 + tg) * 1152, sb + W_Z, 18432);
        bulk_commit_wait();
      }
      __syncwarp();
      if (kind) PROF_MID();
    }
    return;
  }
  const uint32_t BF_1 = 0x3F803F80u;
  const uint32_t* ys = (const uint32_t*)(g_y + ((tg >> 1) * DM + f * 96 + (lane >> 2)) * 2 + (tg & 1)) + (lane & 3);
  const uint32_t rs = sb + W_RS + f * 1536 + lane * 16;
  uint32_t y[12] = {};
#pragma unroll 1
  for (int t = 0; t < NSEG; t++) {
    uint32_t x[12];
    if (kind == 0) {
      wait_k1(sb, t - 6);
      mbar_wait(sb + B_FT + 8 * (t & 1), (t >> 1) & 1);
#pragma unroll
      for (int i = 0; i < 3; i++)
        ldsm4t(x[4 * i], x[4 * i + 1], x[4 * i + 2], x[4 * i + 3], sb + W_FT + (t & 1) * 9344 + (lane & 7) * 1168 + f * 192 + (lane >> 3) * 16 + 64 * i);
    } else {
      warp_flag_wait(g_flags + FL_ACC + t * 32, 72);
      PROF_T(13);
#pragma unroll
      for (int i = 0; i < 6; i++) {
        const float4 v = __ldcg(g_acc + ((size_t)(t * 4 + tg) * 36 + f * 6 + i) * 32 + lane);
        x[2 * i] = pack_bf16(v.x, v.y); x[2 * i + 1] = pack_bf16(v.z, v.w);
      }
#pragma unroll
      for (int i = 0; i < 3; i++) {
        const uint4 r = lds4(rs + (t & 7) * 9216 + i * 512);
        x[4 * i] = bf2_add(x[4 * i], r.x); x[4 * i + 1] = bf2_add(x[4 * i + 1], r.y); x[4 * i + 2] = bf2_add(x[4 * i + 2], r.z); x[4 * i + 3] = bf2_add(x[4 * i + 3], r.w);
      }
      mbar_wait(sb + B_RF + 8 * (t & 7), ((t >> 3) & 1) ^ 1);
      PROF_T(15);
    }
    {
      if (t == 0) PROF_G(27);
#pragma unroll 1
      for (int pass = 0; pass < 2; pass++) {
        float g[2][4] = {};
#pragma unroll
        for (int i = 0; i < 12; i++) {
          uint32_t u;
          asm volatile("movmatrix.sync.aligned.m8n8.trans.b16 %0, %1;" : "=r"(u) : "r"(x[i]));
          mma1688(g[i & 1], u, BF_1, u);
        }
        const uint32_t st = sb + W_ST + kind * 1024 + pass * 512 + (lane & 3) * 16;
        if ((lane >> 3) == (lane & 3))
          asm volatile("st.shared.v2.f32 [%0], {%1,%2};" :: "r"(st + f * 64 + (lane & 4) * 2), "f"(lane & 4 ? g[0][3] + g[1][3] : g[0][2] + g[1][2]),
                       "f"(lane & 4 ? g[0][1] + g[1][1] : g[0][0] + g[1][0]) : "memory");
        bar_sync_r(8 + 2 * kind, 192);
        float s0 = 0.f, s1 = 0.f, q0 = 0.f, q1 = 0.f;
        if (kind && pass == 0) PROF_T(19);
        if (kind && pass == 1) PROF_T(21);
#pragma unroll
        for (int i = 0; i < 6; i++) {
          const float4 e = lds4f(st + i * 64);
          s0 += e.x; q0 += e.y; s1 += e.z; q1 += e.w;
        }
        s0 *= 1.f / 576.f; s1 *= 1.f / 576.f;
        const float v0 = fmaf(q0, 1.f / 576.f, -s0 * s0), v1 = fmaf(q1, 1.f / 576.f, -s1 * s1);
        const uint32_t nmean = pack_bf16(-s0, -s1), vb = pack_bf16(fmaxf(v0, 0.f), fmaxf(v1, 0.f));
        const uint32_t ve = pack_bf16(bf_lo(vb) + 1e-5f, bf_hi(vb) + 1e-5f), sd = pack_bf16(sqr(bf_lo(ve)), sqr(bf_hi(ve)));
        const float r0 = rcp(bf_lo(sd)), r1 = rcp(bf_hi(sd));
        const uint32_t rh = pack_bf16(r0, r1), rl = pack_bf16(r0 - bf_lo(rh), r1 - bf_hi(rh));
        if (pass == 0 && (t == 0 || t == 4 * CT_A || t == 4 * CT_B || t == 4 * CT_C)) {
          if (t == 0) PROF_G(25);
          warp_flag_wait(g_flags + FL_Y + t * 8, t < 4 * CT_B ? 32 : DM);
          if (t == 0) PROF_G(26);
#pragma unroll
          for (int i = 0; i < 12; i++) y[i] = __ldcg(ys + t * (DM * 16) + i * 64);
        }
        uint32_t* xd = (uint32_t*)(g_xs + (size_t)(t + kind * LAG) * 4608 + (kind * 4 + tg) * 64 + (f * 3 >> 1) * 512 + (f & 1) * 32) + lane;
#pragma unroll
        for (int i = 0; i < 12; i++) {
          const uint32_t d = bf2_add(x[i], nmean), q = bf2_op(d, rh, bf2_mul(d, rl));
          if (pass == 0) x[i] = bf2_add(x[i], bf2_mul(q, y[i]));
          else xd[i < 4 ? i * 32 : i < 8 ? i * 32 + (f & 1) * 1792 : i * 32 + 1792] = q;
        }
        if (pass == 0) {
#pragma unroll
          for (int i = 0; i < 3; i++) sts4(rs + (kind * 8 + (t & 7)) * 9216 + i * 512, make_uint4(x[4 * i], x[4 * i + 1], x[4 * i + 2], x[4 * i + 3]));
        }
        if (kind && pass == 0) PROF_T(20);
        if (kind && pass == 1) PROF_T(22);
      }
      if (kind) PROF_T(16);
      if (t < 3) PROF_G(28 + t);
      bar_sync_r(9 + 2 * kind, 224);
#pragma unroll
      for (int i = 0; i < 12; i++) y[i] = __ldcg(ys + ((t + 1) & 63) * (DM * 16) + i * 64);
    }
  }
}

template <int NP, typename V>
__device__ __forceinline__ void kv_block(uint4 (&o)[2 * NP], const Params& P, int r0, int c0) {
  V kk[11], vv[8];
  uint4 sw[NP];
#pragma unroll
  for (int i = 0; i < NP; i++) sw[i] = __ldg((const uint4*)(P.shift + (c0 + 2 * i) * 4));
#pragma unroll
  for (int i = 0; i < 11; i++) kk[i] = r0 + i >= 3 ? __ldg((const V*)(P.ck + (size_t)(r0 + i - 3) * DM + c0)) : V{};
#pragma unroll
  for (int i = 0; i < 8; i++) vv[i] = __ldg((const V*)(P.cv + (size_t)(r0 + i) * DM + c0));
#pragma unroll
  for (int cp = 0; cp < NP; cp++) {
    const uint32_t wt[4] = {__byte_perm(sw[cp].y, sw[cp].w, 0x7632), __byte_perm(sw[cp].y, sw[cp].w, 0x5410),
                            __byte_perm(sw[cp].x, sw[cp].z, 0x7632), __byte_perm(sw[cp].x, sw[cp].z, 0x5410)};
    uint32_t e[8];
#pragma unroll
    for (int i = 0; i < 8; i++) {
      uint32_t a = bf2_mul(((const uint32_t*)&kk[i])[cp], wt[0]);
#pragma unroll
      for (int j = 1; j < 4; j++) a = bf2_add(a, bf2_mul(((const uint32_t*)&kk[i + j])[cp], wt[j]));
      e[i] = bf2_mul(a, ((const uint32_t*)&vv[i])[cp]);
    }
    o[2 * cp] = make_uint4(__byte_perm(e[0], e[1], 0x5410), __byte_perm(e[2], e[3], 0x5410), __byte_perm(e[4], e[5], 0x5410), __byte_perm(e[6], e[7], 0x5410));
    o[2 * cp + 1] = make_uint4(__byte_perm(e[0], e[1], 0x7632), __byte_perm(e[2], e[3], 0x7632), __byte_perm(e[4], e[5], 0x7632), __byte_perm(e[6], e[7], 0x7632));
  }
}
__device__ __forceinline__ void kv_task(const Params& P, int id) {
  const int lane = threadIdx.x & 31, tq = id / 9, c0 = (id % 9) * 64 + (lane >> 2) * 8;
  uint4 o[8];
  kv_block<4, uint4>(o, P, tq * 32 + (lane & 3) * 8, c0);
#pragma unroll
  for (int c = 0; c < 8; c++) g_kv[((size_t)tq * DM + c0 + c) * 4 + (lane & 3)] = o[c];
}
__device__ __forceinline__ int next_job(uint32_t sb) {
  int j = 0;
  if ((threadIdx.x & 31) == 0) j = atomicAdd(g_flags + FL_KV + 96, 1);
  return __shfl_sync(0xffffffffu, j, 0);
}
__device__ __forceinline__ uint2 lds2_ro(uint32_t a) { uint2 v; asm("ld.shared.v2.u32 {%0,%1}, [%2];" : "=r"(v.x), "=r"(v.y) : "r"(a)); return v; }

template <int T0, int T1>
__device__ __forceinline__ void conv_job(uint32_t sb, const Params& P, int ch) {
  const int lane = threadIdx.x & 31, w = threadIdx.x >> 5;
  const uint32_t ub = sb + w * C_CH, zb = ub + C_U;
  constexpr int NL = (T1 + 1) / 2;
  constexpr bool CTA = T1 <= CT_B;
  PROF_G(13 + 4 * (T0 == 0 ? 0 : T0 == CT_A ? 1 : 2));
  uint2 q[T1];
#pragma unroll
  for (int u = 0; u < T1; u++) q[u] = __ldg((const uint2*)(P.ssm_k + (size_t)ch * SEQ) + u * 32 + lane);
  const uint32_t dd = (uint32_t)__bfloat16_as_ushort(P.ssm_d[ch]) * 0x10001u;
  if (CTA) {
#pragma unroll
    for (int tq = w; tq < 4 * T1; tq += 16) {
      uint4 o[2];
      const int tgp = tq * 4 + (lane & 3), c0 = (lane >> 2) * 2;
      kv_block<1, uint32_t>(o, P, tgp * 8, ch - w + c0);
#pragma unroll
      for (int c = 0; c < 2; c++) {
        sts4(sb + (c0 + c) * C_CH + 256 + tgp * 16, o[c]);
        if (T0) g_kv[((size_t)tq * DM + ch - w + c0 + c) * 4 + (lane & 3)] = o[c];
      }
    }
    __syncwarp();
  } else {
    uint4 o[NL];
#pragma unroll
    for (int u = 0; u < NL; u++) o[u] = __ldcg(g_kv + ((size_t)(u * 8 + (lane >> 2)) * DM + ch) * 4 + (lane & 3));
#pragma unroll
    for (int u = 0; u < NL; u++) sts4(ub + 256 + (u * 32 + lane) * 16, o[u]);
  }
  if (lane < 16) { sts4(ub + lane * 16, make_uint4(0, 0, 0, 0)); sts1(zb + lane * 4, 0); }
#pragma unroll
  for (int u = 0; u < T1; u++) {
    const uint32_t pv = __shfl_sync(0xffffffffu, lane == 31 ? (u ? q[u ? u - 1 : 0].y : 0u) : q[u].y, (lane + 31) & 31);
    sts4(zb + 64 + (u * 32 + lane) * 16, make_uint4(__byte_perm(q[u].x, pv, 0x7610), __byte_perm(q[u].x, q[u].x, 0x1032),
                                                   __byte_perm(q[u].y, q[u].x, 0x7610), __byte_perm(q[u].y, q[u].y, 0x1032)));
  }
  if (CTA) __syncthreads(); else __syncwarp();
  PROF_G(14 + 4 * (T0 == 0 ? 0 : T0 == CT_A ? 1 : 2));
  float acc[T1 - T0][4];
#pragma unroll
  for (int i = 0; i < T1 - T0; i++) acc[i][0] = acc[i][1] = acc[i][2] = acc[i][3] = 0.f;
#pragma unroll(T0 == 0 ? 4 : 1)
  for (int r = 0; r < 8; r++) {
    uint2 b[T1];
    uint32_t ba = ub + 256 - r * 32 + lane * 8, zp = zb + 64 + (16 * r + 2 * (lane >> 2) - 4 * (lane & 3)) * 4;
    asm volatile("" : "+r"(zp), "+r"(ba) :: "memory");
#pragma unroll
    for (int i = 0; i < T1; i++) b[i] = lds2_ro(ba + i * 256);
#pragma unroll
    for (int mu = 0; mu < T1; mu++) {
      const uint2 a01 = lds2_ro(zp + 512 * mu), a23 = lds2_ro(zp + 512 * mu - 8);
#pragma unroll
      for (int i = (mu > T0 ? mu : T0); i < T1; i++) mma16816(acc[i - T0], a01.x, a01.y, a23.x, a23.y, b[i - mu].x, b[i - mu].y);
    }
  }
  PROF_G(15 + 4 * (T0 == 0 ? 0 : T0 == CT_A ? 1 : 2));
#pragma unroll
  for (int i = 0; i < T1 - T0; i++)
#pragma unroll
    for (int e = 0; e < 2; e++) {
      const int col = (T0 + i) * 8 + 2 * (lane & 3) + e;
      ((uint32_t*)g_y)[((size_t)col * DM + ch) * 8 + (lane >> 2)] =
          bf2_add(pack_bf16(acc[i][e], acc[i][2 + e]), bf2_mul(lds1(ub + 256 + col * 32 + (lane >> 2) * 4), dd));
    }
  if (CTA) __syncthreads(); else __syncwarp();
  PROF_G(16 + 4 * (T0 == 0 ? 0 : T0 == CT_A ? 1 : 2));
  if (CTA ? threadIdx.x == 480 && ch < 512 : lane == 0) flag_add(g_flags + FL_Y + T0 * 32);
  __syncwarp();
}

__global__ void __launch_bounds__(512, 1) tail_kernel(const Params P) {
  extern __shared__ uint8_t smem_raw[];
  const uint32_t sb = (uint32_t)__cvta_generic_to_shared(smem_raw);
  if (sb != SB0) __trap();
  PROF_BEGIN();
  if (threadIdx.x == 0) {
    for (int c = 0; c < 16; c++) mbar_init(sb + B_FULL + 8 * c, 1);
    for (int c = 0; c < 4; c++) mbar_init(sb + B_EMPTY + 8 * c, 3);
    for (int c = 0; c < 2; c++) mbar_init(sb + B_FT + 8 * c, 1);
    for (int c = 0; c < 8; c++) mbar_init(sb + B_RF + 8 * c, 2);
    sts1(sb + W_K1, 0);
    sts1(sb + Q_SET, (__ldcg(&g_epoch) & 1) * FL_TOTAL);
    fence_async_smem();
  }
  const int b = blockIdx.x, w = threadIdx.x >> 5;
  if ((b >> 2) == 6) {
    __syncthreads();
  } else {
#pragma unroll 1
    for (int g = b; g == b || (g >> 2) == 6; g -= 8) conv_job<0, CT_A>(sb, P, g * 16 + w);
    PROF_G(3);
#pragma unroll 1
    for (int g = b; g == b || (g >> 2) == 6; g -= 8) conv_job<CT_A, CT_B>(sb, P, g * 16 + w);
    PROF_G(4);
    constexpr int KV0 = 36 * CT_B, KV1 = KV0 + 192;
    int job = b < 32 ? KV0 + (b - 28) * 16 + w : -1;
#pragma unroll 1
    for (int k = 0; b >= 28; k++) {
      if (job >= 0) {
        kv_task(P, job);
        __syncwarp();
        if ((threadIdx.x & 31) == 0) flag_add(g_flags + FL_KV + (job < KV1 ? 0 : 32));
        if (job + 64 < KV1) { job += 64; continue; }
      }
      if (job < KV1) {
        warp_flag_wait(g_flags + FL_Y + CT_A * 32, 32);
        warp_flag_wait(g_flags + FL_KV, 192);
        spin_until(rd_clock() + (w >> 2) * 2000);
      }
      while ((job = next_job(sb)) < DM) conv_job<CT_B, CT_C>(sb, P, job);
      if (job < DM + 128) PROF_G(6);
      job -= DM - KV1;
      if (job >= 576) break;
    }
    if (b >= 28) {
      warp_flag_wait(g_flags + FL_KV + 32, 576 - KV1);
#pragma unroll 1
      for (job -= 576; job < DM; job = next_job(sb) - DM - (576 - KV1)) conv_job<CT_C, 16>(sb, P, job);
      PROF_G(5);
      PROF_END();
      return;
    }
    __syncwarp();
  }
  if (blockIdx.x >= 24) {
    PROF_G(24);
    tail_finisher(sb, P);
    PROF_END();
    asm volatile("griddepcontrol.wait;" ::: "memory");
  } else if (rd_warp() < 12) {
    asm volatile("setmaxnreg.inc.sync.aligned.u32 160;");
    tail_gemm(sb, P);
    PROF_END();
  } else {
    asm volatile("setmaxnreg.dec.sync.aligned.u32 32;");
    tail_service(sb);
    PROF_END();
  }
}

}

extern "C" void kernel_launch(void* const* d_in, const int* in_sizes, int n_in, void* d_out, int out_size) {
  typedef const __nv_bfloat16* bp;
  Params P;
  P.x0 = (bp)d_in[0]; P.ck = (bp)d_in[1]; P.cv = (bp)d_in[2]; P.shift = (bp)d_in[3]; P.ssm_k = (bp)d_in[4]; P.ssm_d = (bp)d_in[5];
  P.mem0 = (bp)d_in[7]; P.wq = (bp)d_in[8]; P.wk = (bp)d_in[9]; P.wv = (bp)d_in[10]; P.wo = (bp)d_in[11];
  P.out = (__nv_bfloat16*)d_out;
  void* xc = nullptr;
  cudaGetSymbolAddress(&xc, g_xchg);
  P.part = (uint4*)(((uintptr_t)xc + 8191) & ~(uintptr_t)8191);
  P.memx = P.part + 288 * 512;
  P.d_x = mkdesc(Q_X, 128, 1024, 0); P.d_wl = mkdesc(Q_WL, 16, 1024, 1);
  P.d_ring = mkdesc(W_RING, 512, 128, 0); P.d_ws = mkdesc(W_WS, 16, 1024, 1);
  cudaFuncSetAttribute(head_kernel, cudaFuncAttributeMaxDynamicSharedMemorySize, SMEM_TOTAL);
  cudaFuncSetAttribute(tail_kernel, cudaFuncAttributeMaxDynamicSharedMemorySize, SMEM_TOTAL);
  head_kernel<<<96, 512, SMEM_TOTAL>>>(P);
  cudaLaunchConfig_t cfg = {};
  cfg.gridDim = dim3(36); cfg.blockDim = dim3(512); cfg.dynamicSmemBytes = SMEM_TOTAL; cfg.stream = 0;
  cudaLaunchAttribute attr[1];
  attr[0].id = cudaLaunchAttributeProgrammaticStreamSerialization;
  attr[0].val.programmaticStreamSerializationAllowed = 1;
  cfg.attrs = attr; cfg.numAttrs = 1;
  cudaLaunchKernelEx(&cfg, tail_kernel, P);
}
```

```cpp
#include <cuda_runtime.h>
#include <cuda_bf16.h>
#include <stdint.h>

namespace {

constexpr int SEQ = 2048, DM = 576, NSEG = 64;
#define LAG_V 5
#define RV_V 2050
#define R1_V 350
#define R0_V 600
#define RC_V 125
#define GX_V 1100
#define AD_V 0
#define RS_V 5
#define CALIB 0
#define RF_V 2300
#define RL_V 2000
#define PA1_V 500
#define PA0_V 700
#define ST_V 5
#define XA_V 1
#define XP_V 160
#define KPV_V 16
#define KP1_V 24
#define KP0_V 28
constexpr int LAG = LAG_V;
constexpr int NT = NSEG + LAG;
constexpr int OXRING = 8;
static_assert(LAG >= 3 && LAG < OXRING, "pipeline lag");
constexpr uint32_t D_RED = RV_V;
__host__ __device__ constexpr uint32_t rank_delay(int r) { return r == 2 ? 0 : r ? R1_V : R0_V; }
constexpr uint32_t D_DUE = RF_V, D_LATE = RL_V;
constexpr uint32_t D_TILE = RC_V * 9 / 16, D_GX = GX_V * 9 / 16, D_ADAPT = AD_V * 9 / 16;
constexpr int KP_V = KPV_V, KP_1 = KP1_V, KP_0 = KP0_V;
constexpr int KP_MAX = KP_0 > KP_1 ? KP_0 : KP_1;
constexpr uint32_t SB0 = 1024;
constexpr float SM_SCALE = 0.08838834764831845f * 1.4426950408889634f;
constexpr uint32_t SENT = 0xFFFFFFFFu;
constexpr uint32_t SPIN_LIMIT = 1u << 21;

constexpr int FL_XS = 0;
constexpr int FL_ACC = (NT + 2) * 32;
constexpr int FL_OX = FL_ACC + 128 * 32;
constexpr int FL_SEL = FL_OX + (NT + 1) * 32;
constexpr int FL_Y = FL_SEL + 96 * 4;
constexpr int FL_KV = FL_Y + 512;
constexpr int FL_TOTAL = FL_KV + 128;

__device__ __align__(1024) uint4 g_y[256 * DM];
__device__ __align__(1024) uint4 g_kv[256 * DM];
__device__ __align__(1024) float4 g_acc[2 * 256 * 36 * 32];
__device__ __align__(1024) uint4 g_xs[NT * 4608];
__device__ __align__(1024) uint4 g_ox[OXRING * 512 * 8 * 8];
__device__ __align__(1024) uint4 g_xchg[(288 + 10 + 1) * 512];
__device__ __align__(1024) uint32_t g_flagsets[2 * FL_TOTAL];
__device__ uint32_t g_epoch;
#define PROF_T(slot) do {} while (0)
#define PROF_END() do {} while (0)
#define PROF_W(cond, slot) do {} while (0)
#define PROF_V(cond, slot, val) do { (void)(val); } while (0)
#define PROF_G(slot) do {} while (0)
#define PROF_OR(slot, val) do {} while (0)
#define PROF_A(idx, val) do { (void)(val); } while (0)
#define PROF_BEGIN() do {} while (0)
#define PROF_MID() do {} while (0)

#define CHINT ""
#define HINT ", 100000"
__device__ __forceinline__ uint32_t pack_bf16(float lo, float hi) {
  uint32_t r; asm("cvt.rn.bf16x2.f32 %0, %1, %2;" : "=r"(r) : "f"(hi), "f"(lo)); return r;
}
__device__ __forceinline__ float bf_lo(uint32_t w) { return __uint_as_float(__byte_perm(w, 0, 0x1044)); }
__device__ __forceinline__ float bf_hi(uint32_t w) { return __uint_as_float(w & 0xFFFF0000u); }
__device__ __forceinline__ uint32_t mapa(uint32_t a, uint32_t r) {
  uint32_t o; asm("mapa.shared::cluster.u32 %0, %1, %2;" : "=r"(o) : "r"(a), "r"(r)); return o;
}
__device__ __forceinline__ void mbar_init(uint32_t bar, uint32_t cnt) {
  asm volatile("mbarrier.init.shared::cta.b64 [%0], %1;" :: "r"(bar), "r"(cnt) : "memory");
}
__device__ __forceinline__ void mbar_expect(uint32_t bar, uint32_t bytes) {
  asm volatile("mbarrier.arrive.expect_tx.shared::cta.b64 _, [%0], %1;" :: "r"(bar), "r"(bytes) : "memory");
}
__device__ __forceinline__ void mbar_arrive(uint32_t bar) {
  asm volatile("mbarrier.arrive.shared::cta.b64 _, [%0];" :: "r"(bar) : "memory");
}
__device__ __forceinline__ void mbar_arrive_if0(uint32_t sel, uint32_t bar) {
  asm volatile("{\n.reg .pred p;\nsetp.eq.u32 p, %1, 0;\n@p mbarrier.arrive.shared::cta.b64 _, [%0];\n}" :: "r"(bar), "r"(sel) : "memory");
}
__device__ __forceinline__ void mbar_expect_if0(uint32_t sel, uint32_t bar, uint32_t bytes) {
  asm volatile("{\n.reg .pred p;\nsetp.eq.u32 p, %1, 0;\n@p mbarrier.arrive.expect_tx.shared::cta.b64 _, [%0], %2;\n}" :: "r"(bar), "r"(sel), "r"(bytes) : "memory");
}
__device__ __forceinline__ void mbar_rarrive_if0(uint32_t sel, uint32_t bar) {
  asm volatile("{\n.reg .pred p;\nsetp.eq.u32 p, %1, 0;\n@p mbarrier.arrive.relaxed.cluster.shared::cluster.b64 _, [%0];\n}" :: "r"(bar), "r"(sel) : "memory");
}
__device__ __forceinline__ void mbar_wait_lim(uint32_t bar, uint32_t par) {
  asm volatile(
    "{\n.reg .pred p;\n.reg .u32 c;\nmov.u32 c, 0;\n"
    "W_%=:\n"
    "mbarrier.try_wait.parity.shared::cta.b64 p, [%0], %1;\n"
    "@p bra D_%=;\n"
    "add.u32 c, c, 1;\nsetp.lt.u32 p, c, %2;\n@p bra W_%=;\ntrap;\n"
    "D_%=:\n}\n" :: "r"(bar), "r"(par), "n"(SPIN_LIMIT) : "memory");
}
__device__ __forceinline__ void mbar_wait(uint32_t bar, uint32_t par) {
  asm volatile(
    "{\n.reg .pred p;\n"
    "W_%=:\n"
    "mbarrier.try_wait.parity.shared::cta.b64 p, [%0], %1" HINT ";\n"
    "@!p bra W_%=;\n}\n" :: "r"(bar), "r"(par) : "memory");
}
__device__ __forceinline__ void mbar_spin(uint32_t bar, uint32_t par) {
  asm volatile("{\n.reg .pred p;\nW_%=:\nmbarrier.try_wait.parity.shared::cta.b64 p, [%0], %1;\n@!p bra W_%=;\n}\n" :: "r"(bar), "r"(par) : "memory");
}
__device__ __forceinline__ void mbar_wait_if(uint32_t& done, uint32_t test, uint32_t bar, uint32_t par, bool force) {
  asm volatile(
    "{\n.reg .pred p, q;\nsetp.ne.u32 p, %0, 0;\n@p bra.uni D_%=;\nsetp.ne.u32 q, %4, 0;\n"
    "mbarrier.test_wait.parity.shared::cta.b64 p, [%1], %3;\n"
    "or.pred p, p, q;\n@!p bra D_%=;\n"
    "W_%=:\n"
    "mbarrier.try_wait.parity.shared::cta.b64 p, [%2], %3, 100000;\n"
    "@!p bra W_%=;\nmov.u32 %0, 1;\nD_%=:\n}\n" : "+r"(done) : "r"(test), "r"(bar), "r"(par), "r"((uint32_t)force) : "memory");
}
template <int ID, int N> __device__ __forceinline__ void bar_sync() { asm volatile("bar.sync %0, %1;" :: "n"(ID), "n"(N) : "memory"); }
template <int ID, int N> __device__ __forceinline__ void bar_arrive() { asm volatile("bar.arrive %0, %1;" :: "n"(ID), "n"(N) : "memory"); }
__device__ __forceinline__ void bar_sync_r(int id, int n) { asm volatile("bar.sync %0, %1;" :: "r"(id), "r"(n) : "memory"); }
__device__ __forceinline__ void bar_arrive_r(int id, int n) { asm volatile("bar.arrive %0, %1;" :: "r"(id), "r"(n) : "memory"); }
__device__ __forceinline__ uint32_t pin(uint32_t x) { return __shfl_sync(0xffffffffu, x, threadIdx.x); }
__device__ __forceinline__ void cluster_sync() {
  asm volatile("barrier.cluster.arrive.aligned;\nbarrier.cluster.wait.aligned;" ::: "memory");
}
__device__ __forceinline__ void fence_async_smem() { asm volatile("fence.proxy.async.shared::cta;" ::: "memory"); }
__device__ __forceinline__ void fence_async_global() { asm volatile("fence.proxy.async.global;" ::: "memory"); }
__device__ __forceinline__ uint4 ld_poll(const uint4* p) {
  uint4 v;
  asm volatile("ld.relaxed.gpu.global.v4.u32 {%0,%1,%2,%3}, [%4];" : "=r"(v.x), "=r"(v.y), "=r"(v.z), "=r"(v.w) : "l"(p) : "memory");
  return v;
}
__device__ __forceinline__ uint32_t rd_clock() { uint64_t c; asm volatile("mov.u64 %0, %%clock64;" : "=l"(c) :: "memory"); return (uint32_t)c; }
__device__ __forceinline__ void spin_until(uint32_t when) {
  asm volatile("{\n.reg .pred p;\n.reg .b64 c;\n.reg .s32 lo;\nS_%=:\nmov.u64 c, %%clock64;\ncvt.u32.u64 lo, c;\nsub.s32 lo, lo, %0;\n"
               "setp.lt.s32 p, lo, 0;\n@p bra.uni S_%=;\n}" :: "r"(when) : "memory");
}
__device__ __forceinline__ uint32_t near_page(uint4* pair) {
  uint32_t best0 = ~0u, best1 = ~0u;
  const int lane = threadIdx.x & 31;
  if (lane < 4) asm volatile("st.relaxed.gpu.global.v4.u32 [%0], {%1,%1,%1,%1};" :: "l"(pair + (lane >> 1) * 256 + (lane & 1)), "r"(SENT) : "memory");
  __syncwarp();
#pragma unroll 1
  for (int r = 0; r < 8; r++) {
    if (r >= 4 && !(r & 1) && __all_sync(0xffffffffu, max(best0, best1) - min(best0, best1) > 110u && min(best0, best1) < 420u)) break;
    uint32_t t0, t1, v;
    asm volatile("mov.u32 %0, %%clock;" : "=r"(t0) :: "memory");
    asm volatile("{\n.reg .pred p;\nsetp.eq.u32 p, %2, 0;\nmov.u32 %0, 0;\n@p atom.relaxed.gpu.global.exch.b32 %0, [%1], %3;\n}"
                 : "=&r"(v) : "l"(pair + (r & 1) * 256), "r"(lane), "r"(SENT) : "memory");
    asm volatile("{\n.reg .pred p;\nsetp.ne.u32 p, %1, 0x9E3779B9;\nmov.u32 %0, %2;\n@p mov.u32 %0, %%clock;\n}" : "=&r"(t1) : "r"(v), "r"(t0 - 1) : "memory");
    if (r & 1) best1 = min(best1, t1 - t0); else best0 = min(best0, t1 - t0);
  }
  return best1 < best0;
}
__device__ __forceinline__ void st_gpu4(uint4* p, uint32_t a, uint32_t b, uint32_t c, uint32_t d) {
  asm volatile("st.relaxed.gpu.global.v4.u32 [%0], {%1,%2,%3,%4};" :: "l"(p), "r"(a), "r"(b), "r"(c), "r"(d) : "memory");
}
__device__ __forceinline__ void st_gpu1(uint32_t* p, uint32_t a) {
  asm volatile("st.relaxed.gpu.global.u32 [%0], %1;" :: "l"(p), "r"(a) : "memory");
}
__device__ __forceinline__ void st_gpu1_if(bool c, uint32_t* p, uint32_t a) {
  asm volatile("{\n.reg .pred p;\nsetp.ne.u32 p, %2, 0;\n@p st.relaxed.gpu.global.u32 [%0], %1;\n}" :: "l"(p), "r"(a), "r"((uint32_t)c) : "memory");
}
__device__ __forceinline__ void warp_flag_wait(const uint32_t* p, uint32_t target) {
  uint32_t v, n = 0;
  do {
    asm volatile("ld.relaxed.gpu.global.u32 %0, [%1];" : "=r"(v) : "l"(p) : "memory");
    if (++n > SPIN_LIMIT) __trap();
  } while (__any_sync(0xffffffffu, v < target));
}
__device__ __forceinline__ void flag_add(uint32_t* p) {
  asm volatile("red.release.gpu.global.add.u32 [%0], 1;" :: "l"(p) : "memory");
}
__device__ __forceinline__ void bulk_g2s(uint32_t dst, const void* src, uint32_t bytes, uint32_t bar) {
  asm volatile("cp.async.bulk.shared::cluster.global.mbarrier::complete_tx::bytes [%0], [%1], %2, [%3];"
               :: "r"(dst), "l"(src), "r"(bytes), "r"(bar) : "memory");
}
__device__ __forceinline__ void bulk_g2s_mc(uint32_t dst, const void* src, uint32_t bytes, uint32_t bar, uint16_t mask) {
  asm volatile("cp.async.bulk.shared::cluster.global.mbarrier::complete_tx::bytes.multicast::cluster [%0], [%1], %2, [%3], %4;"
               :: "r"(dst), "l"(src), "r"(bytes), "r"(bar), "h"(mask) : "memory");
}
__device__ __forceinline__ void bulk_s2s(uint32_t dst, uint32_t src, uint32_t bytes, uint32_t bar) {
  asm volatile("cp.async.bulk.shared::cluster.shared::cta.mbarrier::complete_tx::bytes [%0], [%1], %2, [%3];"
               :: "r"(dst), "r"(src), "r"(bytes), "r"(bar) : "memory");
}
__device__ __forceinline__ void bulk_s2g(void* dst, uint32_t src, uint32_t bytes) {
  asm volatile("cp.async.bulk.global.shared::cta.bulk_group [%0], [%1], %2;" :: "l"(dst), "r"(src), "r"(bytes) : "memory");
}
__device__ __forceinline__ void bulk_commit_wait() {
  asm volatile("cp.async.bulk.commit_group;\ncp.async.bulk.wait_group 0;" ::: "memory");
}
__device__ __forceinline__ bool elect_one() {
  uint32_t p; asm volatile("{\n.reg .pred p;\nelect.sync _|p, 0xffffffff;\nselp.u32 %0, 1, 0, p;\n}" : "=r"(p)); return p;
}
__device__ __forceinline__ void ldsm4(uint32_t& r0, uint32_t& r1, uint32_t& r2, uint32_t& r3, uint32_t a) {
  asm volatile("ldmatrix.sync.aligned.m8n8.x4.shared.b16 {%0,%1,%2,%3}, [%4];" : "=r"(r0), "=r"(r1), "=r"(r2), "=r"(r3) : "r"(a) : "memory");
}
__device__ __forceinline__ void ldsm4t(uint32_t& r0, uint32_t& r1, uint32_t& r2, uint32_t& r3, uint32_t a) {
  asm volatile("ldmatrix.sync.aligned.m8n8.x4.trans.shared.b16 {%0,%1,%2,%3}, [%4];" : "=r"(r0), "=r"(r1), "=r"(r2), "=r"(r3) : "r"(a) : "memory");
}
__device__ __forceinline__ void stsm4(uint32_t a, uint32_t r0, uint32_t r1, uint32_t r2, uint32_t r3) {
  asm volatile("stmatrix.sync.aligned.m8n8.x4.shared.b16 [%0], {%1,%2,%3,%4};" :: "r"(a), "r"(r0), "r"(r1), "r"(r2), "r"(r3) : "memory");
}
__device__ __forceinline__ void stsm2(uint32_t a, uint32_t r0, uint32_t r1) {
  asm volatile("stmatrix.sync.aligned.m8n8.x2.shared.b16 [%0], {%1,%2};" :: "r"(a), "r"(r0), "r"(r1) : "memory");
}
__device__ __forceinline__ void stsm4t(uint32_t a, uint32_t r0, uint32_t r1, uint32_t r2, uint32_t r3) {
  asm volatile("stmatrix.sync.aligned.m8n8.x4.trans.shared.b16 [%0], {%1,%2,%3,%4};" :: "r"(a), "r"(r0), "r"(r1), "r"(r2), "r"(r3) : "memory");
}
__device__ __forceinline__ float4 lds4f(uint32_t a) {
  float4 v; asm volatile("ld.shared.v4.f32 {%0,%1,%2,%3}, [%4];" : "=f"(v.x), "=f"(v.y), "=f"(v.z), "=f"(v.w) : "r"(a) : "memory"); return v;
}
__device__ __forceinline__ uint4 lds4(uint32_t a) {
  uint4 v; asm volatile("ld.shared.v4.u32 {%0,%1,%2,%3}, [%4];" : "=r"(v.x), "=r"(v.y), "=r"(v.z), "=r"(v.w) : "r"(a) : "memory"); return v;
}
__device__ __forceinline__ uint32_t lds1(uint32_t a) {
  uint32_t v; asm volatile("ld.shared.u32 %0, [%1];" : "=r"(v) : "r"(a) : "memory"); return v;
}
__device__ __forceinline__ void sts4(uint32_t a, uint4 v) {
  asm volatile("st.shared.v4.u32 [%0], {%1,%2,%3,%4};" :: "r"(a), "r"(v.x), "r"(v.y), "r"(v.z), "r"(v.w) : "memory");
}
__device__ __forceinline__ void sts1(uint32_t a, uint32_t v) { asm volatile("st.shared.u32 [%0], %1;" :: "r"(a), "r"(v) : "memory"); }
__device__ __forceinline__ void mma16816(float (&d)[4], uint32_t a0, uint32_t a1, uint32_t a2, uint32_t a3, uint32_t b0, uint32_t b1) {
  asm volatile("mma.sync.aligned.m16n8k16.row.col.f32.bf16.bf16.f32 {%0,%1,%2,%3}, {%4,%5,%6,%7}, {%8,%9}, {%0,%1,%2,%3};"
               : "+f"(d[0]), "+f"(d[1]), "+f"(d[2]), "+f"(d[3]) : "r"(a0), "r"(a1), "r"(a2), "r"(a3), "r"(b0), "r"(b1));
}
__device__ __forceinline__ void mma1688(float (&d)[4], uint32_t a0, uint32_t a1, uint32_t b0) {
  asm volatile("mma.sync.aligned.m16n8k8.row.col.f32.bf16.bf16.f32 {%0,%1,%2,%3}, {%4,%5}, {%6}, {%0,%1,%2,%3};"
               : "+f"(d[0]), "+f"(d[1]), "+f"(d[2]), "+f"(d[3]) : "r"(a0), "r"(a1), "r"(b0));
}
__device__ __forceinline__ float rcp(float x) { float r; asm("rcp.approx.ftz.f32 %0, %1;" : "=f"(r) : "f"(x)); return r; }
__device__ __forceinline__ float sqr(float x) { float r; asm("sqrt.approx.f32 %0, %1;" : "=f"(r) : "f"(x)); return r; }
__device__ __forceinline__ float ex2(float x) { float r; asm("ex2.approx.ftz.f32 %0, %1;" : "=f"(r) : "f"(x)); return r; }

__host__ __device__ constexpr uint64_t mkdesc(uint32_t off, uint32_t lbo, uint32_t sbo, uint32_t sw) {
  return (uint64_t)((SB0 + off) >> 4) | ((uint64_t)(lbo >> 4) << 16) | ((uint64_t)(sbo >> 4) << 32) | ((uint64_t)sw << 62);
}
__device__ __forceinline__ void wg_fence() { asm volatile("wgmma.fence.sync.aligned;" ::: "memory"); }
__device__ __forceinline__ void wg_commit() { asm volatile("wgmma.commit_group.sync.aligned;" ::: "memory"); }
template <int N> __device__ __forceinline__ void wg_wait() { asm volatile("wgmma.wait_group.sync.aligned %0;" :: "n"(N) : "memory"); }
template <int N> __device__ __forceinline__ void reg_fence(float (&d)[N]) {
#pragma unroll
  for (int i = 0; i < N; i++) asm volatile("" : "+f"(d[i]) :: "memory");
}

#define F4(d, o) "+f"(d[o]), "+f"(d[o + 1]), "+f"(d[o + 2]), "+f"(d[o + 3])
template <int SC, int TB> __device__ __forceinline__ void wg_rs(float (&d)[8], const uint32_t* a, uint64_t db, int ob) {
  asm volatile("{\n.reg .pred p;\n.reg .b64 b;\nsetp.ne.b32 p, %13, 0;\nadd.s64 b, %12, %15;\n"
    "wgmma.mma_async.sync.aligned.m64n16k16.f32.bf16.bf16 {%0,%1,%2,%3,%4,%5,%6,%7}, {%8,%9,%10,%11}, b, p, 1, 1, %14;\n}\n"
    : F4(d, 0), F4(d, 4) : "r"(a[0]), "r"(a[1]), "r"(a[2]), "r"(a[3]), "l"(db), "n"(SC), "n"(TB), "l"((uint64_t)ob));
}
template <int SC, int TB> __device__ __forceinline__ void wg_rs(float (&d)[12], const uint32_t* a, uint64_t db, int ob) {
  asm volatile("{\n.reg .pred p;\n.reg .b64 b;\nsetp.ne.b32 p, %17, 0;\nadd.s64 b, %16, %19;\n"
    "wgmma.mma_async.sync.aligned.m64n24k16.f32.bf16.bf16 {%0,%1,%2,%3,%4,%5,%6,%7,%8,%9,%10,%11}, {%12,%13,%14,%15}, b, p, 1, 1, %18;\n}\n"
    : F4(d, 0), F4(d, 4), F4(d, 8) : "r"(a[0]), "r"(a[1]), "r"(a[2]), "r"(a[3]), "l"(db), "n"(SC), "n"(TB), "l"((uint64_t)ob));
}
template <int SC, int TB> __device__ __forceinline__ void wg_rs(float (&d)[16], const uint32_t* a, uint64_t db, int ob) {
  asm volatile("{\n.reg .pred p;\n.reg .b64 b;\nsetp.ne.b32 p, %21, 0;\nadd.s64 b, %20, %23;\n"
    "wgmma.mma_async.sync.aligned.m64n32k16.f32.bf16.bf16 {%0,%1,%2,%3,%4,%5,%6,%7,%8,%9,%10,%11,%12,%13,%14,%15}, {%16,%17,%18,%19}, b, p, 1, 1, %22;\n}\n"
    : F4(d, 0), F4(d, 4), F4(d, 8), F4(d, 12) : "r"(a[0]), "r"(a[1]), "r"(a[2]), "r"(a[3]), "l"(db), "n"(SC), "n"(TB), "l"((uint64_t)ob));
}
template <int SC, int TB> __device__ __forceinline__ void wg_rs(float (&d)[28], const uint32_t* a, uint64_t db, int ob) {
  asm volatile("{\n.reg .pred p;\n.reg .b64 b;\nsetp.ne.b32 p, %33, 0;\nadd.s64 b, %32, %35;\n"
    "wgmma.mma_async.sync.aligned.m64n56k16.f32.bf16.bf16 {%0,%1,%2,%3,%4,%5,%6,%7,%8,%9,%10,%11,%12,%13,%14,%15,%16,%17,%18,%19,%20,%21,%22,%23,%24,%25,%26,%27}, {%28,%29,%30,%31}, b, p, 1, 1, %34;\n}\n"
    : F4(d, 0), F4(d, 4), F4(d, 8), F4(d, 12), F4(d, 16), F4(d, 20), F4(d, 24) : "r"(a[0]), "r"(a[1]), "r"(a[2]), "r"(a[3]), "l"(db), "n"(SC), "n"(TB), "l"((uint64_t)ob));
}
template <int SC, int TB> __device__ __forceinline__ void wg_ss(float (&d)[8], uint64_t da, int oa, uint64_t db, int ob) {
  asm volatile("{\n.reg .pred p;\n.reg .b64 a, b;\nsetp.ne.b32 p, %10, 0;\nadd.s64 a, %8, %12;\nadd.s64 b, %9, %13;\n"
    "wgmma.mma_async.sync.aligned.m64n16k16.f32.bf16.bf16 {%0,%1,%2,%3,%4,%5,%6,%7}, a, b, p, 1, 1, 1, %11;\n}\n"
    : F4(d, 0), F4(d, 4) : "l"(da), "l"(db), "n"(SC), "n"(TB), "l"((uint64_t)oa), "l"((uint64_t)ob));
}
template <int SC, int TB> __device__ __forceinline__ void wg_ss(float (&d)[12], uint64_t da, int oa, uint64_t db, int ob) {
  asm volatile("{\n.reg .pred p;\n.reg .b64 a, b;\nsetp.ne.b32 p, %14, 0;\nadd.s64 a, %12, %16;\nadd.s64 b, %13, %17;\n"
    "wgmma.mma_async.sync.aligned.m64n24k16.f32.bf16.bf16 {%0,%1,%2,%3,%4,%5,%6,%7,%8,%9,%10,%11}, a, b, p, 1, 1, 1, %15;\n}\n"
    : F4(d, 0), F4(d, 4), F4(d, 8) : "l"(da), "l"(db), "n"(SC), "n"(TB), "l"((uint64_t)oa), "l"((uint64_t)ob));
}
template <int SC, int TB> __device__ __forceinline__ void wg_ss(float (&d)[16], uint64_t da, int oa, uint64_t db, int ob) {
  asm volatile("{\n.reg .pred p;\n.reg .b64 a, b;\nsetp.ne.b32 p, %18, 0;\nadd.s64 a, %16, %20;\nadd.s64 b, %17, %21;\n"
    "wgmma.mma_async.sync.aligned.m64n32k16.f32.bf16.bf16 {%0,%1,%2,%3,%4,%5,%6,%7,%8,%9,%10,%11,%12,%13,%14,%15}, a, b, p, 1, 1, 1, %19;\n}\n"
    : F4(d, 0), F4(d, 4), F4(d, 8), F4(d, 12) : "l"(da), "l"(db), "n"(SC), "n"(TB), "l"((uint64_t)oa), "l"((uint64_t)ob));
}
template <int SC, int TB> __device__ __forceinline__ void wg_ss(float (&d)[20], uint64_t da, int oa, uint64_t db, int ob) {
  asm volatile("{\n.reg .pred p;\n.reg .b64 a, b;\nsetp.ne.b32 p, %22, 0;\nadd.s64 a, %20, %24;\nadd.s64 b, %21, %25;\n"
    "wgmma.mma_async.sync.aligned.m64n40k16.f32.bf16.bf16 {%0,%1,%2,%3,%4,%5,%6,%7,%8,%9,%10,%11,%12,%13,%14,%15,%16,%17,%18,%19}, a, b, p, 1, 1, 1, %23;\n}\n"
    : F4(d, 0), F4(d, 4), F4(d, 8), F4(d, 12), F4(d, 16) : "l"(da), "l"(db), "n"(SC), "n"(TB), "l"((uint64_t)oa), "l"((uint64_t)ob));
}
template <int SC, int TB> __device__ __forceinline__ void wg_ss(float (&d)[28], uint64_t da, int oa, uint64_t db, int ob) {
  asm volatile("{\n.reg .pred p;\n.reg .b64 a, b;\nsetp.ne.b32 p, %30, 0;\nadd.s64 a, %28, %32;\nadd.s64 b, %29, %33;\n"
    "wgmma.mma_async.sync.aligned.m64n56k16.f32.bf16.bf16 {%0,%1,%2,%3,%4,%5,%6,%7,%8,%9,%10,%11,%12,%13,%14,%15,%16,%17,%18,%19,%20,%21,%22,%23,%24,%25,%26,%27}, a, b, p, 1, 1, 1, %31;\n}\n"
    : F4(d, 0), F4(d, 4), F4(d, 8), F4(d, 12), F4(d, 16), F4(d, 20), F4(d, 24) : "l"(da), "l"(db), "n"(SC), "n"(TB), "l"((uint64_t)oa), "l"((uint64_t)ob));
}

template <int SC> __device__ __forceinline__ void wg_sskk(float (&d)[16], uint64_t da, int oa, uint64_t db, int ob) {
  asm volatile("{\n.reg .pred p;\n.reg .b64 a, b;\nsetp.ne.b32 p, %18, 0;\nadd.s64 a, %16, %19;\nadd.s64 b, %17, %20;\n"
    "wgmma.mma_async.sync.aligned.m64n32k16.f32.bf16.bf16 {%0,%1,%2,%3,%4,%5,%6,%7,%8,%9,%10,%11,%12,%13,%14,%15}, a, b, p, 1, 1, 0, 0;\n}\n"
    : F4(d, 0), F4(d, 4), F4(d, 8), F4(d, 12) : "l"(da), "l"(db), "n"(SC), "l"((uint64_t)oa), "l"((uint64_t)ob));
}

template <int NB>
__device__ __forceinline__ void load_rows(uint32_t dst, const __nv_bfloat16* src, int pitch, int nrows, int tid, int nthr) {
  for (int i0 = tid; i0 < nrows * 8; i0 += nthr * NB) {
    uint4 v[NB];
#pragma unroll
    for (int u = 0; u < NB; u++) {
      const int i = i0 + u * nthr, r = i >> 3;
      if (i < nrows * 8) v[u] = __ldg((const uint4*)(src + (size_t)r * pitch + (i & 7) * 8));
    }
#pragma unroll
    for (int u = 0; u < NB; u++) {
      const int i = i0 + u * nthr, r = i >> 3;
      if (i < nrows * 8) sts4(dst + r * 128 + (((i & 7) ^ (r & 7)) << 4), v[u]);
    }
  }
}
template <int NK> __device__ __forceinline__ void load_afrags(uint32_t* a, uint32_t tile, int w, int lane) {
  int i = lane >> 3, r = lane & 7;
  uint32_t base = tile + ((i >> 1) * 8 + r) * 128 + (((2 * w + (i & 1)) ^ r) << 4);
#pragma unroll
  for (int kk = 0; kk < NK; kk++) ldsm4t(a[4 * kk], a[4 * kk + 1], a[4 * kk + 2], a[4 * kk + 3], base + kk * 2048);
}

constexpr uint32_t Q_WL = 0;
constexpr uint32_t Q_WO = 24576;
constexpr uint32_t Q_OX = Q_WO;
constexpr uint32_t Q_X = 73728;
constexpr uint32_t Q_CS = 10240;
constexpr uint32_t Q_STG = 165888;
constexpr uint32_t Q_OB = 190464;
constexpr uint32_t Q_SIN = 194560;
constexpr uint32_t Q_PX = 204800;
constexpr uint32_t Q_SOUT = Q_PX;
constexpr int Q_KR = 30;
constexpr uint32_t BARS = 228352;
constexpr uint32_t B_CP = BARS;
constexpr uint32_t B_OK = BARS + 408;
constexpr uint32_t B_G0 = BARS + 272;
constexpr uint32_t B_XF = BARS + 72;
constexpr uint32_t B_E = BARS + 224;
constexpr uint32_t B_SM = BARS + 160;
constexpr uint32_t B_O = BARS + 168;
constexpr uint32_t B_P = BARS + 176;
constexpr uint32_t B_OXREADY = BARS + 192;
constexpr uint32_t B_OXFREE = BARS + 200;
constexpr uint32_t B_REF = BARS + 208;
constexpr uint32_t B_AN = BARS + 264;
constexpr uint32_t B_PZ = BARS + 256;
constexpr uint32_t B_RES = BARS + 216;
constexpr uint32_t Q_REF = BARS + 288;
constexpr uint32_t Q_SEL = BARS + 304;
constexpr uint32_t Q_SET = BARS + 360;
constexpr uint32_t SM_BYTES = 4 * 1024, SX_BYTES = 2560, PX_BYTES = 2 * 14 * 128;
constexpr int W_KR = 29;
constexpr uint32_t W_RING = 0;
constexpr uint32_t W_WS = 196608;
constexpr uint32_t W_FT = 0;
constexpr uint32_t W_FO = 18688;
constexpr uint32_t W_Z = 30720;
constexpr uint32_t W_RS = 49152;
constexpr uint32_t W_ST = 28672;
constexpr int CT_A = 2, CT_B = 6, CT_C = 11;
static_assert(36 * CT_C <= 36 * CT_B + 192, "kv stages");
constexpr uint32_t C_U = 256 + 4096;
constexpr uint32_t C_CH = C_U + 64 + 8192 + 96;
constexpr uint32_t B_FULL = BARS;
constexpr uint32_t B_EMPTY = BARS + 128;
constexpr uint32_t B_FT = BARS + 160;
constexpr uint32_t B_RF = BARS + 176;
constexpr uint32_t W_K1 = BARS + 240;
constexpr uint32_t SMEM_TOTAL = BARS + 512;

struct Params {
  const __nv_bfloat16 *x0, *wq, *wk, *wv, *wo, *mem0, *ck, *cv, *shift, *ssm_k, *ssm_d;
  __nv_bfloat16* out;
  uint4 *part, *memx;
  uint64_t d_x, d_wl, d_ring, d_ws;
};

constexpr uint64_t D_QK = mkdesc(Q_STG, 768, 128, 0), D_WO = mkdesc(Q_WO, 16, 1024, 1), D_OB = mkdesc(Q_OB, 128, 2048, 0), D_PX = mkdesc(Q_PX, 128, 768, 0);
constexpr uint64_t D_V = mkdesc(Q_STG, 128, 768, 0);

#define g_flags (g_flagsets + lds1(sb + Q_SET))

__device__ __forceinline__ int rd_cid() { uint32_t v; asm volatile("mov.u32 %0, %%clusterid.x;" : "=r"(v)); return v; }
__device__ __forceinline__ int rd_rank() { uint32_t v; asm volatile("mov.u32 %0, %%cluster_ctarank;" : "=r"(v)); return v; }
__device__ __forceinline__ int rd_lane() { uint32_t v; asm volatile("mov.u32 %0, %%laneid;" : "=r"(v)); return v; }
__device__ __forceinline__ int rd_warp() { uint32_t v; asm volatile("mov.u32 %0, %%tid.x;" : "=r"(v)); return __shfl_sync(0xffffffffu, v >> 5, 0); }

template <int NA>
__device__ __forceinline__ void proj_step(float (&acc)[NA], const uint32_t* a, uint64_t db, uint64_t dwl, int k) {
  const int ob = (k >> 2) * (Q_CS / 16) + (k & 3) * 16;
  if (k == 0) wg_rs<0, 1>(acc, a, db, ob);
  else if (k % 6 != 5) wg_rs<1, 1>(acc, a + 4 * (k - k / 6), db, ob);
  else wg_ss<1, 1>(acc, dwl, 128 * (k / 6), db, ob);
}
__device__ __forceinline__ void stage_groups(uint32_t stl, const uint32_t (&pk)[14]) {
#pragma unroll
  for (int h = 0; h < 2; h++) {
    stsm4(stl + h * 768 + 256, pk[h], pk[2 + h], pk[4 + h], 0);
    stsm4(stl + h * 768 + 6144 + 128, pk[6 + h], pk[8 + h], pk[10 + h], pk[12 + h]);
  }
}
__device__ __forceinline__ void head_main(uint32_t sb, const Params& P) {
  const int lane = threadIdx.x & 31, warp = rd_warp(), w = warp & 3, wg = warp >> 2, rank = rd_rank();
  uint32_t a[4 * Q_KR];
  {
    const int tid = threadIdx.x & 127;
    const __nv_bfloat16* src = (rank == 2 ? P.wv + wg * 64 : (wg ? P.wk : P.wq) + rank * 64) + rd_cid() * 128 + (size_t)(tid >> 3) * 4096 + (tid & 7) * 8;
    const uint32_t so = (tid >> 3) * 128 + (((tid & 7) ^ ((tid >> 3) & 7)) << 4), st = sb + Q_X + wg * (Q_KR * 2048);
    uint4 v[36];
#pragma unroll
    for (int k = 0; k < 36; k++) v[k] = __ldg((const uint4*)(src + (size_t)k * 65536));
#pragma unroll
    for (int k = 0; k < 36; k++) sts4(so + (k % 6 == 5 ? sb + Q_WL + wg * 12288 + (k / 6) * 2048 : st + (k - k / 6) * 2048), v[k]);
    bar_sync_r(9 + wg, 128);
    PROF_G(7);
    load_afrags<Q_KR>(a, st, w, lane);
    fence_async_smem();
    bar_arrive<11, 384>();
  }
  cluster_sync();
  PROF_G(8);
  const uint64_t dwl = P.d_wl + wg * 768, dq = D_QK + wg * 384;
  const uint32_t stg = sb + Q_STG + wg * 12288 + 2 * w * 768;
  const uint32_t stm = pin(stg + (lane >> 4) * 6144 + ((lane >> 3) & 1) * 768 + (lane & 7) * 16), stl = pin(stg + lane * 16);
  const uint32_t rel = mapa(sb + B_E, 0), rev = mapa(sb + B_E, 2), sel = pin(threadIdx.x & 127), arm = pin(threadIdx.x - 128 > 8), xfa = pin(sb + B_XF + 8 * lane);
  const uint32_t sx = sb + (wg == rank ? Q_SIN + rank * 4096 : Q_SOUT + 2048), s0 = w ? sx + (2 * w - 1) * 512 : sb + Q_SOUT + wg * 1024, s1 = sx + 2 * w * 512;
  const uint32_t sd0 = pin(s0 + lane * 16), sd1 = pin(s1 + lane * 16), sr = sb + Q_SIN + rank * 4096;
  const int kp = rank == 2 ? KP_V : rank ? KP_1 : KP_0;
    const uint32_t pz = sb + (rank == 2 ? B_SM : B_PZ);
  uint32_t pk[14] = {};
#pragma unroll 1
  for (int t = 0;; t++) {
    const uint32_t par = t & 1;
    uint32_t paused = 0;
    if (t == 0) {
      mbar_wait(sb + B_XF, 0);
    } else {
      float m[12];
      mbar_wait(sb + B_G0, par ^ 1);
#pragma unroll
      for (int c = 0; c < 9; c++) {
        mbar_spin(sb + B_OK + 8 * c, par ^ 1);
        if (c == 0 || c == 3 || c == 8) PROF_W(warp == 0, c == 0 ? 0 : c == 3 ? 1 : 3);
        if (c == XA_V) mbar_rarrive_if0(sel | (rank >> 1), rel);
        if (c == 3) mbar_rarrive_if0(sel, rev);
        if (c == 8) mbar_rarrive_if0(sel | (rank >> 1), rev + 24);
        wg_fence();
#pragma unroll
        for (int k = 4 * c; k < 4 * c + 4; k++) proj_step(m, a, P.d_x, dwl, k);
        if (c == 8) wg_commit();
        if (c == ST_V && rank == 2) {
          if (t > 1) bar_sync<3, 384>();
          stage_groups(stl, pk);
        }
      }
      wg_wait<0>();
      reg_fence(m);
      PROF_W(warp == 0, 2);
      stsm4(stm, pack_bf16(m[0], m[1]), pack_bf16(m[2], m[3]), pack_bf16(m[4], m[5]), pack_bf16(m[6], m[7]));
      stsm2(stm + 128, pack_bf16(m[8], m[9]), pack_bf16(m[10], m[11]));
      if (rank == 2) {
        bar_arrive<1, 384>();
        if (t == NT) break;
        mbar_wait(sb + B_XF, par);
        mbar_wait_if(paused, pz, sb + B_RES, par ^ 1, false);
      } else {
        float s[20];
        bar_sync<1, 256>();
        fence_async_smem();
        wg_fence();
        wg_ss<0, 1>(s, dq, 0, dq, 768);
#pragma unroll
        for (int i = 1; i < 4; i++) wg_ss<1, 1>(s, dq, 96 * i, dq, 768 + 96 * i);
        wg_commit();
        if (t < NT) mbar_wait(sb + B_XF, par);
        wg_wait<0>();
        reg_fence(s);
        if (w < 3) {
          sts4(sd0, make_uint4(pack_bf16(s[0], s[1]), pack_bf16(s[4], s[5]), pack_bf16(s[8], s[9]), pack_bf16(s[12], s[13])));
          if (w != 1) sts1(sd0 + 512, pack_bf16(s[16], s[17]));
          if (w == 0) {
            fence_async_smem();
            __syncwarp();
            if (elect_one()) bulk_s2s(mapa(sr + wg * 1024, 2), s0, 1024, mapa(sb + B_SM, 2));
            __syncwarp();
            PROF_W(wg == 1, 4); PROF_W(wg == 0, 8);
          }
          if (w < 2) sts4(sd1, make_uint4(pack_bf16(s[2], s[3]), pack_bf16(s[6], s[7]), pack_bf16(s[10], s[11]), pack_bf16(s[14], s[15])));
          bar_arrive<8, 224>();
        }
        if (t == NT) break;
      }
    }
    float e[28];
#pragma unroll
    for (int k = 0; k < 36; k++) {
      if (k == 2 && t > 0) {
        mbar_rarrive_if0(sel, rel + 16);
        mbar_expect_if0(arm, xfa - (B_XF - B_CP), 2048);
        mbar_expect_if0(sel | wg, sb + B_G0, 9216);
      }
      if (k % 4 == 0 && k) mbar_wait(sb + B_XF + 2 * k, par);
      if (k == 0) PROF_W(warp == 0, 5);
      if (k % 2 == 0 && k && k <= KP_MAX) {
        mbar_wait_if(paused, pz, sb + B_RES, par ^ 1, k == kp);
      }
      if (k % 4 == 0 || (k % 2 == 0 && k <= KP_MAX)) wg_fence();
      proj_step(e, a, P.d_x + 192, dwl, k);
    }
    wg_commit();
    wg_wait<0>();
    reg_fence(e);
    PROF_W(warp == 0, 10);
    mbar_expect_if0(arm, xfa, 7168);
    mbar_rarrive_if0(sel | (rank ^ 2), rel);
#pragma unroll
    for (int i = 0; i < 14; i++) pk[i] = pack_bf16(e[2 * i], e[2 * i + 1]);
    if (rank != 2) stage_groups(stl, pk);
    PROF_W(warp == 0, 12);
  }
  cluster_sync();
}

__device__ __forceinline__ uint32_t next_tick() {
  uint64_t g0, g1;
  asm volatile("mov.u64 %0, %%globaltimer;" : "=l"(g0) :: "memory");
#pragma unroll 1
  for (int n = 0; n < 8; n++) {
    asm volatile("mov.u64 %0, %%globaltimer;" : "=l"(g1) :: "memory");
    if (__any_sync(0xffffffffu, (uint32_t)g1 != (uint32_t)g0)) break;
  }
  return (uint32_t)g1;
}
__device__ __forceinline__ void wait_ns(uint32_t when) {
  uint32_t c;
  asm volatile("{\n.reg .pred p;\n.reg .b64 g;\n.reg .s32 lo;\nS_%=:\nmov.u64 g, %%globaltimer;\ncvt.u32.u64 lo, g;\nsub.s32 lo, %1, lo;\n"
               "setp.gt.s32 p, lo, 31;\n@p bra.uni S_%=;\nmov.u64 g, %%clock64;\ncvt.u32.u64 %0, g;\nshl.b32 lo, lo, 1;\nadd.s32 %0, %0, lo;\n}" : "=&r"(c) : "r"(when) : "memory");
  spin_until(c - 30);
}
template <bool TAG>
__device__ __forceinline__ uint32_t poll4(uint4 (&v)[4], const uint4* src, uint32_t tag) {
#pragma unroll
  for (int j = 0; j < 4; j++) v[j] = ld_poll(src + j * 32);
  uint32_t n = 0;
  while (__any_sync(0xffffffffu, TAG ? (((v[0].x ^ tag) | (v[1].x ^ tag) | (v[2].x ^ tag) | (v[3].x ^ tag)) & 1) != 0
                                     : max(__vimax3_u32(v[0].x, v[1].x, v[2].x), v[3].x) == SENT)) {
#pragma unroll
    for (int j = 0; j < 4; j++) if (TAG ? ((v[j].x ^ tag) & 1) != 0 : v[j].x == SENT) v[j] = ld_poll(src + j * 32);
    if (++n > SPIN_LIMIT) __trap();
  }
  return n;
}

template <int STEP>
__device__ __forceinline__ void check_tiles(uint32_t sb, const Params& P, int w, int t) {
  const int lane = rd_lane();
  uint32_t chk = sb + Q_X + w * Q_CS + lane * 32 + (lane >> 2) * 4;
#pragma unroll 1
  for (uint32_t bar = sb + B_CP + 8 * w; bar <= sb + B_CP + 64; bar += 8 * STEP, chk += STEP * Q_CS) {
    uint32_t ok;
    asm volatile("{\n.reg .pred p, q;\n.reg .b32 a, b;\nsetp.eq.u32 q, %4, 0;\n"
                 "W_%=:\nmbarrier.try_wait.parity.shared::cta.b64 p, [%1], %2" CHINT ";\n@!p bra W_%=;\n"
                 "ld.shared.u32 a, [%3];\nld.shared.u32 b, [%3 + 1024];\nmax.u32 a, a, b;\nsetp.ne.u32 p, a, 0xFFFFFFFF;\n"
                 "vote.sync.all.pred p, p, 0xFFFFFFFF;\nand.pred q, q, p;\n@q mbarrier.arrive.shared::cta.b64 _, [%1 + %5];\nselp.u32 %0, 1, 0, p;\n}"
                 : "=r"(ok) : "r"(bar), "r"(~t & 1), "r"(chk), "r"(lane), "n"(B_OK - B_CP) : "memory");
    const int c = (bar - sb - B_CP) / 8;
    if (!ok) {
      uint4 v[4];
      poll4<false>(v, P.memx + c * 512 + (t & 1) * 128 + lds1(sb + Q_SEL + 4 * c) / 16 + lane, 0);
#pragma unroll
      for (int j = 0; j < 4; j++) sts4(sb + Q_X + c * Q_CS + j * 512 + lane * 16, v[j]);
      fence_async_smem();
      __syncwarp();
      mbar_arrive_if0(lane, bar + B_OK - B_CP);
      if (t > LAG + 4) sts1(sb + Q_REF + 4, lds1(sb + Q_REF + 4) + 1);
      PROF_OR(7, 1 << c);
      PROF_A(c, 1);
    }
  }
}
__device__ __forceinline__ void load_scores(float (&s)[10], uint32_t sa) {
  const uint4 a = lds4(sa), b = lds4(sa + 4096);
  const uint32_t a4 = lds1(sa + 512), b4 = lds1(sa + 4608);
  s[0] = bf_lo(a.x) + bf_lo(b.x); s[1] = bf_hi(a.x) + bf_hi(b.x); s[2] = bf_lo(a.y) + bf_lo(b.y); s[3] = bf_hi(a.y) + bf_hi(b.y);
  s[4] = bf_lo(a.z) + bf_lo(b.z); s[5] = bf_hi(a.z) + bf_hi(b.z); s[6] = bf_lo(a.w) + bf_lo(b.w); s[7] = bf_hi(a.w) + bf_hi(b.w);
  s[8] = bf_lo(a4) + bf_lo(b4); s[9] = bf_hi(a4) + bf_hi(b4);
}
__device__ __forceinline__ void softmax_num(float (&s)[10]) {
  float mx = fmaxf(fmaxf(fmaxf(s[0], s[1]), fmaxf(s[2], s[3])), fmaxf(fmaxf(s[4], s[5]), fmaxf(s[6], s[7])));
  mx = fmaxf(mx, fmaxf(s[8], s[9]));
  const float m1 = __shfl_xor_sync(0xffffffffu, mx, 1), m2 = __shfl_xor_sync(0xffffffffu, mx, 2), m3 = __shfl_xor_sync(0xffffffffu, mx, 3);
  mx = fmaxf(fmaxf(mx, m1), fmaxf(m2, m3));
  mx *= -SM_SCALE;
#pragma unroll
  for (int i = 0; i < 10; i++) s[i] = ex2(fmaf(s[i], SM_SCALE, mx));
}

__device__ __forceinline__ void wo_tiles(uint32_t sb, const uint32_t (&f)[76], char* d0, uint32_t pg, uint32_t rs, int t) {
  float d[2][8];
  auto mma = [&](int i, int k0, int k1) {
#pragma unroll
    for (int k = k0; k < k1; k++) {
      if (i == 2 && ((k & 1) || k == 6)) wg_ss<1, 0>(d[0], D_WO, 2048 + 128 * k, D_OB, 16 * k);
      else if (k == 0) wg_rs<0, 0>(d[i & 1], f + 32 * i, D_OB, 0);
      else wg_rs<1, 0>(d[i & 1], f + (i < 2 ? 32 * i + 4 * k : 64 + 2 * k), D_OB, 16 * k);
    }
    wg_commit();
  };
  auto put = [&](float (&q)[8]) {
    reg_fence(q);
    st_gpu4((uint4*)d0, (pack_bf16(q[0], q[1]) & ~1u) | ((t - 1) >> 1 & 1), pack_bf16(q[4], q[5]), pack_bf16(q[2], q[3]), pack_bf16(q[6], q[7]));
    __syncwarp();
  };
  wg_fence();
  mma(0, 0, 8);
  mma(1, 0, 8);
  wg_wait<1>();
  put(d[0]);
  PROF_W(threadIdx.x < 288, 14);
  wg_fence();
  mma(2, 0, RS_V);
  d0 += pg & 0xFFFF;
  wg_wait<1>();
  put(d[1]);
  PROF_W(threadIdx.x < 288, 15);
  mma(2, RS_V, 8);
  d0 += pg >> 16;
  wg_wait<1>();
  mbar_arrive_if0(rs, sb + B_RES);
  PROF_W(threadIdx.x < 288, 17);
  wg_wait<0>();
  put(d[0]);
  PROF_W(threadIdx.x < 288, 16);
}
__device__ __forceinline__ void head_aux(uint32_t sb, const Params& P) {
  const int tid = threadIdx.x & 127, w = rd_warp() & 3, rank = rd_rank(), head = __shfl_sync(0xffffffffu, rd_cid(), 0);
#pragma unroll 1
  for (int i = 0; i < 3; i++) {
    uint4 a[4], b[4];
#pragma unroll
    for (int u = 0; u < 4; u++) {
      const int r = u * 32 + (tid >> 2);
      const uint4* src = (const uint4*)(P.wo + (size_t)(head * 128 + (r & 64) + (r & 7) * 8 + ((r >> 3) & 7)) * DM + (6 - 3 * rank + i) * 64) + (tid & 3) * 2;
      a[u] = __ldg(src); b[u] = __ldg(src + 1);
    }
#pragma unroll
    for (int u = 0; u < 4; u++) {
      const int r = u * 32 + (tid >> 2);
      const uint32_t dst = sb + Q_WO + i * 16384 + r * 128 + ((((tid & 3) * 2) ^ (r & 7) ^ ((head >> 2) & 1)) << 4);
      sts4(dst, make_uint4(__byte_perm(a[u].x, a[u].y, 0x5410), __byte_perm(a[u].z, a[u].w, 0x5410), __byte_perm(b[u].x, b[u].y, 0x5410), __byte_perm(b[u].z, b[u].w, 0x5410)));
      sts4(dst ^ 16, make_uint4(__byte_perm(a[u].x, a[u].y, 0x7632), __byte_perm(a[u].z, a[u].w, 0x7632), __byte_perm(b[u].x, b[u].y, 0x7632), __byte_perm(b[u].z, b[u].w, 0x7632)));
    }
  }
#pragma unroll
  for (int i = 0; i < 6; i++) sts4(sb + Q_PX + (i * 128 + tid) * 16, make_uint4(0, 0, 0, 0));
  char* pd;
  uint32_t pg;
  {
    const int lane = tid & 31, dcta = (w * 8 + (lane >> 2)) * 3 + rank;
    uint4 f;
    uint32_t n = 0;
    do {
      f = ld_poll((const uint4*)(g_flags + FL_SEL) + dcta);
      if (++n > SPIN_LIMIT) __trap();
    } while (__any_sync(0xffffffffu, !f.x || !f.y || !f.z));
    pd = (char*)P.part + (dcta * 1536 + head * 4 + (lane & 3) + (f.x - 1) * 256) * 16;
    pg = (8192 + (f.y - f.x) * 4096) | (8192 + (f.z - f.y) * 4096) << 16;
  }
  bar_sync<11, 384>();
#pragma unroll 1
  for (int k = tid; k < DM; k += 128) {
    uint32_t q[4];
#pragma unroll
    for (int j = 0; j < 4; j++) q[j] = min(__bfloat16_as_ushort(P.mem0[2 * j * DM + k]) | (uint32_t)__bfloat16_as_ushort(P.mem0[(2 * j + 1) * DM + k]) << 16, SENT - 1);
    sts4(sb + Q_X + (k >> 6) * Q_CS + (k & 63) * 16, make_uint4(q[0], q[1], q[2], q[3]));
    sts4(sb + Q_X + (k >> 6) * Q_CS + (k & 63) * 16 + 1024, make_uint4(q[0], q[1], q[2], q[3]));
  }
#pragma unroll
  for (int i = 0; i < 2; i++) sts4(sb + Q_STG + (i * 16 + (tid >> 3)) * 768 + 640 + (tid & 7) * 16, make_uint4(0, 0, 0, 0));
  fence_async_smem();
  PROF_G(2);
  const uint32_t wa = pin(sb + Q_WO + ((tid >> 4 & 1) * 8 + (tid & 7)) * 128 + (((2 * w + ((tid >> 3) & 1)) ^ (tid & 7)) << 4));
  uint32_t f[76];
  if (rank != 2) {
#pragma unroll
    for (int k = 0; k < 19; k++) ldsm4t(f[4 * k], f[4 * k + 1], f[4 * k + 2], f[4 * k + 3], wa + (k < 16 ? k : 2 * k - 16) * 2048);
    const uint32_t rs = pin(tid);
    cluster_sync();
#pragma unroll 1
    for (int t = 1;; t++) {
      pd = (char*)((uintptr_t)pd ^ 2048);
      check_tiles<4>(sb, P, w, t);
      if (w == 0) {
        bar_sync<8, 224>();
        fence_async_smem();
        if (elect_one()) {
          bulk_s2s(mapa(sb + Q_SIN + rank * 4096, rank ^ 1), sb + Q_SOUT + 2048, SX_BYTES, mapa(sb + B_SM, rank ^ 1));
          mbar_arrive(sb + B_SM);
        }
        __syncwarp();
      }
      if (t == NT) break;
      if (w == 1) {
        mbar_wait(sb + B_AN, (t - 1) & 1);
        spin_until(rd_clock() + (rank ? PA1_V : PA0_V));
        mbar_arrive_if0(rs - 32, sb + B_PZ);
      }
      mbar_spin(sb + B_O, (t - 1) & 1);
      PROF_W(w == 0, 13);
      wo_tiles(sb, f, pd, pg, rs, t);
      mbar_expect_if0(rs, sb + B_O, 4096);
    }
  } else {
#pragma unroll
    for (int k = 0; k < 8; k++) ldsm4t(f[4 * k], f[4 * k + 1], f[4 * k + 2], f[4 * k + 3], wa + k * 2048);
    cluster_sync();
    const int l = w & 1, tile = w >> 1;
    const uint32_t ob = pin(sb + Q_OB + (l ^ ((head >> 1) & 1)) * 2048 + tile * 1024 + (tid >> 2 & 7) * 128 + (tid & 3) * 16);
    const uint32_t ob0 = sb + Q_OB + ((head >> 1) & 1) * 2048;
    const uint32_t sa = pin(sb + Q_SIN + l * 1024 + (tid & 31) * 16);
#pragma unroll 1
    for (int t = 1; t <= NT; t++) {
      const uint32_t par = (t - 1) & 1;
      {
        uint32_t vf[4][10], p[5];
        float s[10], o[4][4];
        const int lane = rd_lane();
        const uint32_t vb = sb + Q_STG + tile * 12288 + l * 6144 + (lane & 7) * 16;
        const uint32_t ax = vb + ((lane >> 3) & 1) * 768 + (lane >> 4) * 128;
        pd = (char*)((uintptr_t)pd ^ 2048);
        bar_sync<1, 384>();
#pragma unroll
        for (int i = 0; i < 4; i++) ldsm4(vf[i][4], vf[i][5], vf[i][6], vf[i][7], ax + i * 1536 + 256);
        ldsm4(vf[0][8], vf[0][9], vf[1][8], vf[1][9], vb + (lane >> 3) * 768 + 512);
        ldsm4(vf[2][8], vf[2][9], vf[3][8], vf[3][9], vb + (lane >> 3) * 768 + 512 + 3072);
#pragma unroll
        for (int i = 0; i < 4; i++) ldsm4(vf[i][0], vf[i][1], vf[i][2], vf[i][3], ax + i * 1536);
        mbar_spin(sb + B_SM, par);
        PROF_W(w == 0, 20);
        if (t < NT) {
          load_scores(s, sa);
          __syncwarp();
          softmax_num(s);
#pragma unroll
          for (int j = 0; j < 5; j++) p[j] = pack_bf16(s[2 * j], s[2 * j + 1]);
          __syncwarp();
          PROF_W(w == 0, 9);
          float z[4] = {0.f, 0.f, 0.f, 0.f};
          const uint32_t ONE = 0x3F803F80u;
          mma16816(z, ONE, ONE, ONE, ONE, p[0], p[1]);
#pragma unroll
          for (int i = 0; i < 4; i++) { o[i][0] = o[i][1] = o[i][2] = o[i][3] = 0.f; mma16816(o[i], vf[i][0], vf[i][1], vf[i][2], vf[i][3], p[0], p[1]); }
#pragma unroll
          for (int k = 8; k < 12; k++) ldsm4t(f[4 * k], f[4 * k + 1], f[4 * k + 2], f[4 * k + 3], wa + k * 2048);
          mma16816(z, ONE, ONE, ONE, ONE, p[2], p[3]);
#pragma unroll
          for (int i = 0; i < 4; i++) mma16816(o[i], vf[i][4], vf[i][5], vf[i][6], vf[i][7], p[2], p[3]);
#pragma unroll
          for (int k = 12; k < 16; k++) ldsm4t(f[4 * k], f[4 * k + 1], f[4 * k + 2], f[4 * k + 3], wa + k * 2048);
          mma1688(z, ONE, ONE, p[4]);
#pragma unroll
          for (int i = 0; i < 4; i++) mma1688(o[i], vf[i][8], vf[i][9], p[4]);
#pragma unroll
          for (int k = 16; k < 19; k++) ldsm4t(f[4 * k], f[4 * k + 1], f[4 * k + 2], f[4 * k + 3], wa + (2 * k - 16) * 2048);
          const float r0 = rcp(z[0]), r1 = rcp(z[1]);
          const uint4 u0 = make_uint4(pack_bf16(o[0][0] * r0, o[0][2] * r0), pack_bf16(o[1][0] * r0, o[1][2] * r0),
                                      pack_bf16(o[2][0] * r0, o[2][2] * r0), pack_bf16(o[3][0] * r0, o[3][2] * r0));
          const uint4 u1 = make_uint4(pack_bf16(o[0][1] * r1, o[0][3] * r1), pack_bf16(o[1][1] * r1, o[1][3] * r1),
                                      pack_bf16(o[2][1] * r1, o[2][3] * r1), pack_bf16(o[3][1] * r1, o[3][3] * r1));
          PROF_W(w == 0, 8);
          sts4(ob, u0);
          sts4(ob + 64, u1);
          bar_sync<5, 160>();
          fence_async_smem();
          PROF_W(w == 0, 13);
          wo_tiles(sb, f, pd, pg, ob ^ ob0, t);
        }
      }
      const int lane = rd_lane();
      mbar_expect_if0(lane | w, sb + B_SM, SM_BYTES);
      if (t < NT) bar_sync<12, 160>();
      {
        float o[3][16];
        const uint32_t ox = sb + Q_OX + 2 * w * 512 + lane * 16;
        const uint64_t dp = D_PX + (t & 1) * 384;
        fence_async_smem();
        mbar_wait(sb + B_P + 8 * (t & 1), ((t - 1) >> 1) & 1);
        PROF_W(w == 0, 7);
#pragma unroll
        for (int j = 0; j < 7; j++) {
          if (j >= 3) {
            const int i = j - 3;
            if (i == 0) mbar_wait(sb + B_OXFREE, par ^ 1);
            if (i < 2) wg_wait<2>(); else if (i == 2) wg_wait<0>();
            if (i == 2 && t < NT) bar_arrive<3, 384>();
            reg_fence(o[i % 3]);
#pragma unroll
            for (int h = 0; h < 2; h++)
              stsm4(ox + i * 4096 + h * 512, pack_bf16(o[i % 3][2 * h], o[i % 3][2 * h + 1]), pack_bf16(o[i % 3][4 + 2 * h], o[i % 3][5 + 2 * h]),
                    pack_bf16(o[i % 3][8 + 2 * h], o[i % 3][9 + 2 * h]), pack_bf16(o[i % 3][12 + 2 * h], o[i % 3][13 + 2 * h]));
          }
          if (j < 4) {
            if (j % 3 == 0) wg_fence();
            wg_sskk<0>(o[j % 3], D_V, (j >> 1) * 384 + (j & 1) * 768, dp, (j >> 1) * 192);
            wg_sskk<1>(o[j % 3], D_V, (j >> 1) * 384 + (j & 1) * 768 + 16, dp, (j >> 1) * 192 + 16);
            wg_sskk<1>(o[j % 3], D_V, (j >> 1) * 384 + (j & 1) * 768 + 32, dp, (j >> 1) * 192 + 32);
            wg_commit();
          }
        }
        mbar_expect_if0(lane | w, sb + B_P + 8 * (t & 1), PX_BYTES);
      }
      fence_async_smem();
      __syncwarp();
      mbar_arrive_if0(lane, sb + B_OXREADY);
      PROF_W(w == 0, 23);
    }
  }
  cluster_sync();
}

__device__ __forceinline__ void softmax_x(uint32_t sb, int w, int rank, int t) {
  float s[10];
  const int lane = rd_lane();
  mbar_wait(sb + B_SM, (t - 1) & 1);
  PROF_W(w == 3, 20);
  load_scores(s, sb + Q_SIN + w * 512 + lane * 16);
  const int last = 8 + 8 * w + (lane >> 2) - 2 * (lane & 3);
#pragma unroll
  for (int i = 2; i < 10; i++) s[i] = (8 * (i >> 1) + (i & 1) <= last) ? s[i] : -INFINITY;
  softmax_num(s);
  float sum = ((s[0] + s[1]) + (s[2] + s[3])) + ((s[4] + s[5]) + (s[6] + s[7])) + (s[8] + s[9]);
  sum += __shfl_xor_sync(0xffffffffu, sum, 1);
  sum += __shfl_xor_sync(0xffffffffu, sum, 2);
  const float r = rcp(sum);
  const uint32_t po = sb + Q_SOUT + 6144 + w * 768;
#pragma unroll
  for (int j = 0; j < 5; j++) sts1(po + lane * 4 + j * 128, pack_bf16(s[2 * j] * r, s[2 * j + 1] * r));
  fence_async_smem();
  __syncwarp();
  if (elect_one()) bulk_s2s(mapa(sb + Q_PX + ((t & 1) * 2 + rank) * 3072 + w * 768, 2), po, 128 * (w + 2), mapa(sb + B_P + 8 * (t & 1), 2));
  __syncwarp();
  PROF_W(w == 3, 22);
}

__device__ __forceinline__ uint32_t bf2_op(uint32_t a, uint32_t b, uint32_t c) {
  uint32_t r; asm("fma.rn.bf16x2 %0, %1, %2, %3;" : "=r"(r) : "r"(a), "r"(b), "r"(c)); return r;
}
__device__ __forceinline__ uint32_t bf2_mul(uint32_t a, uint32_t b) {
  uint32_t r; asm("mul.rn.bf16x2 %0, %1, %2;" : "=r"(r) : "r"(a), "r"(b)); return r;
}
__device__ __forceinline__ uint32_t bf2_add(uint32_t a, uint32_t b) {
  uint32_t r; asm("add.rn.bf16x2 %0, %1, %2;" : "=r"(r) : "r"(a), "r"(b)); return r;
}
__device__ __forceinline__ void head_service(uint32_t sb, const Params& P) {
  const int lane = threadIdx.x & 31, rank = rd_rank(), w = rd_warp() & 3, i3 = w - 1;
  const int head = rd_cid(), c = 6 - 3 * rank + i3;
  uint32_t dof = c * 8192 + (lane & 4) * 1024 + (lane & 8) * 128 + head * 32 + (lane & 16) + (lane & 3) * 4;
  uint32_t sof = (blockIdx.x * 3 + i3) * 8192, gof = 0, dly = i3 * D_TILE, g0 = 0, c0 = 0, ref = 0;
  if (w) {
    sof += __shfl_sync(0xffffffffu, lds1(sb + Q_SEL + 36 + 4 * i3), 0);
    gof = c * 8192 + __shfl_sync(0xffffffffu, lds1(sb + Q_SEL + 4 * c), 0);
#pragma unroll 1
    for (int j = 0; j < 8; j++) st_gpu4((uint4*)((char*)P.part + sof) + j * 32 + lane, SENT, SENT, SENT, SENT);
    st_gpu1((uint32_t*)((char*)P.memx + dof), SENT);
    st_gpu1((uint32_t*)((char*)P.memx + dof + 2048), SENT);
    __syncwarp();
    asm volatile("st.release.gpu.global.u32 [%0], %1;" :: "l"(g_flags + FL_SEL + blockIdx.x * 4 + i3), "r"(((sof >> 12) & 1) + 1) : "memory");
  }
  cluster_sync();
#pragma unroll 1
  for (int t = 0; t <= NT; t++) {
    if (w == 0 && rank == 0 && t < NT) {
      const uint32_t* fl = g_flags + FL_XS + t * 32;
      warp_flag_wait(fl + (lane & 1 ? (t >= LAG ? 16 : 0) : (t <= NSEG ? 0 : 16)), 4);
      fence_async_global();
      const char* src = (const char*)g_xs + (size_t)t * 73728;
      if (t > 0) mbar_wait(sb + B_E, (t - 1) & 1);
      PROF_T(24);
      uint32_t at = rd_clock();
#pragma unroll 1
      for (int k = 0; k < 9; k++) {
        if (elect_one()) bulk_g2s_mc(sb + Q_X + 3072 + k * Q_CS, src + 1024 + k * 8192, 7168, sb + B_XF + 8 * k, 7);
        __syncwarp();
        at += XP_V;
        spin_until(at);
      }
      if (t == 0) PROF_G(31);
    }
    if (t > 0) {
    if (rank == 2 && w) check_tiles<3>(sb, P, w - 1, t);
    if (w == (rank == 2) && t < NT) {
      const uint32_t* tms = (const uint32_t*)(P.memx + 9 * 512 + lds1(sb + Q_SEL + 48) / 16 + (head >> 4) * 32 + lane) + rank;
      const uint32_t due = ref + D_GX + (D_DUE - rank_delay(rank)) * 9 / 16;
      if (rank == 2) {
        const uint32_t g1 = next_tick(), c1 = rd_clock();
        const uint32_t rate = t > 1 ? __float2uint_rn(65536.f * (g1 - g0) * rcp(c1 - c0)) : 36400;
        g0 = g1; c0 = c1;
        uint4* pub = P.memx + 9 * 512 + (lane & 1) * 256 + (lane & 2) * 16 + head;
        const uint32_t lead = D_RED * rate >> 16, late = D_LATE * rate >> 16, r1 = rank_delay(1) * rate >> 10, r0 = rank_delay(0) * rate >> 10;
        mbar_wait(sb + B_E, (t - 1) & 1);
        mbar_spin(sb + B_E + 24, (t - 1) & 1);
        uint32_t now = g0 + ((rd_clock() - c0) * rate >> 16);
        now = (now + (t == 1 || (int)(now + 90 - due) > 0 ? late : lead)) << 6;
        st_gpu4(pub, ((now + r0) & ~255u) | t, ((now + r1) & ~255u) | t, (now & ~255u) | t, 0);
        PROF_T(22);
      } else {
        mbar_wait(sb + B_OK + 64, (t - 1) & 1);
      }
      if (t > 1) wait_ns(due); else ref = next_tick();
      uint32_t d, n = 0;
      do {
        asm volatile("ld.relaxed.gpu.global.u32 %0, [%1];" : "=r"(d) : "l"(tms) : "memory");
        if (++n > SPIN_LIMIT) __trap();
      } while (__any_sync(0xffffffffu, (d ^ t) & 255));
      ref += __reduce_max_sync(0xffffffffu, (int)(d - (ref << 6))) >> 6;
      sts1(sb + Q_REF, ref);
      __syncwarp();
      mbar_arrive_if0(lane, sb + B_REF);
      PROF_A(13, n);
      PROF_T(19);
    }
    if (w == 2 && rank == 2 && t < NT) {
      mbar_wait(sb + B_SM, (t - 1) & 1);
      mbar_rarrive_if0(lane >> 1, mapa(sb + B_AN, lane & 1));
      bar_sync<5, 160>();
      fence_async_smem();
      if (elect_one()) {
        bulk_s2s(mapa(sb + Q_OB, 1), sb + Q_OB, 4096, mapa(sb + B_O, 1));
        bulk_s2s(mapa(sb + Q_OB, 0), sb + Q_OB, 4096, mapa(sb + B_O, 0));
      }
      __syncwarp();
    }
    if (rank != 2) {
      softmax_x(sb, w, rank, t);
      if (w == 0 && t < NT) bar_arrive<7, 64>();
      mbar_expect_if0(lane | (w - 1), sb + B_SM, SX_BYTES);
    }
    }
    if (w == 0 && rank == 0 && t < NT) {
      if (t > 0) mbar_wait(sb + B_E + 16, (t - 1) & 1);
      if (elect_one()) {
#pragma unroll 1
        for (int k = 0; k < 9; k++) bulk_g2s_mc(sb + Q_X + 2048 + k * Q_CS, (const char*)g_xs + (size_t)t * 73728 + k * 8192, 1024, sb + B_G0, 7);
      }
      __syncwarp();
    }
    if (t == 0) continue;
    if (w && t < NT) {
      mbar_wait(sb + B_REF, (t - 1) & 1);
      uint32_t when = lds1(sb + Q_REF) + dly;
      sof ^= 2048; dof ^= 2048;
      uint4* src = (uint4*)((char*)P.part + sof) + lane;
      uint32_t* dst = (uint32_t*)((char*)P.memx + (dof ^ 2048));
      const bool inj = t == LAG && (lane & 8);
      if (t == LAG) {
        const __nv_bfloat16* m0 = P.mem0 + (lane & 3) * 2 * DM + c * 64 + head * 2 + (lane >> 4);
        st_gpu1_if(inj, dst, min(__bfloat16_as_ushort(m0[0]) | (uint32_t)__bfloat16_as_ushort(m0[DM]) << 16, SENT - 1));
      }
      asm volatile("" : "+l"(dst), "+l"(src));
      uint4 v[4];
      wait_ns(when);
      PROF_W(i3 == 0, 18);
      const uint32_t nr = poll4<true>(v, src, (t - 1) >> 1);
      PROF_T(26 + i3);
      const uint32_t z = bf2_add(bf2_add(v[0].z, v[1].z), bf2_add(v[2].z, v[3].z)), u = bf2_add(bf2_add(v[0].w, v[1].w), bf2_add(v[2].w, v[3].w));
      const uint32_t x = bf2_add(bf2_add(v[0].x, v[1].x), bf2_add(v[2].x, v[3].x)), y = bf2_add(bf2_add(v[0].y, v[1].y), bf2_add(v[2].y, v[3].y));
      const uint32_t x2 = bf2_add(x, __shfl_xor_sync(0xffffffffu, z, 16)), y2 = bf2_add(y, __shfl_xor_sync(0xffffffffu, u, 16));
      const uint32_t x3 = bf2_add(x2, __shfl_xor_sync(0xffffffffu, y2, 8));
      st_gpu1_if(!inj, dst, bf2_add(x3, __shfl_xor_sync(0xffffffffu, x3, 4)));
      if (w == 3 && rank == 2) bar_arrive<12, 160>();
      PROF_T(29 + i3);
      PROF_A(10 + i3, nr);
      when += D_GX + min(lds1(sb + Q_REF + 4), 8u) * D_ADAPT;
      if (nr && t > LAG + 3 && dly < i3 * D_TILE + 8 * D_ADAPT) dly += D_ADAPT;
      fence_async_global();
      if (w == 3 && rank != 2) bar_sync<7, 64>();
      wait_ns(when);
      if (elect_one()) bulk_g2s_mc(sb + Q_X + c * Q_CS, (const char*)P.memx + gof + (~t & 1) * 2048, 2048, sb + B_CP + 8 * c, 7);
      __syncwarp();
      if (i3 == 0) PROF_T(21);
      st_gpu1((uint32_t*)((char*)P.memx + dof), SENT);
    }
    if (w == 0 && rank == 2) {
      if (t < NT) mbar_wait(sb + B_XF, t & 1); else warp_flag_wait(g_flags + FL_XS + NT * 32 + 16, 4);
      mbar_wait(sb + B_OXREADY, (t - 1) & 1);
      if (elect_one()) {
        uint4* od = g_ox + (size_t)(t & (OXRING - 1)) * 32768 + head * 512;
        if (t <= NSEG) bulk_s2g(od, sb + Q_OX, 8192);
        if (t > LAG) bulk_s2g(od + 16384, sb + Q_OX + 8192, 8192);
        bulk_commit_wait();
        mbar_arrive(sb + B_OXFREE);
        flag_add(g_flags + FL_OX + t * 32 + head);
      }
      __syncwarp();
      PROF_T(25);
    }
  }
  cluster_sync();
}

__global__ void __cluster_dims__(3, 1, 1) __launch_bounds__(512, 1) head_kernel(const Params P) {
  extern __shared__ uint8_t smem_raw[];
  const uint32_t sb = (uint32_t)__cvta_generic_to_shared(smem_raw);
  if ((sb & 0xFFFFFFu) != SB0) __trap();
  asm volatile("griddepcontrol.launch_dependents;");
  if (threadIdx.x < 96) {
    const int i = blockIdx.x * 24 + threadIdx.x % 24, m = threadIdx.x / 24;
    const __nv_bfloat16* p = m == 3 ? P.ssm_k + (size_t)(i >> 2) * SEQ + (i & 3) * 64 : (m == 0 ? P.ck : m == 1 ? P.cv : P.x0) + (size_t)i * 64;
    asm volatile("prefetch.global.L2 [%0];" :: "l"(p));
  } else if (threadIdx.x == 96 && blockIdx.x < 45) {
    asm volatile("prefetch.global.L2 [%0];" :: "l"(blockIdx.x < 36 ? P.shift + blockIdx.x * 64 : P.ssm_d + (blockIdx.x - 36) * 64));
  }
  PROF_BEGIN();
  {
    const int wp = rd_warp();
    if (wp == 13) sts1(sb + Q_SET, (__ldcg(&g_epoch) & 1) * FL_TOTAL);
    if (wp <= 12) {
      const uint32_t sel = __shfl_sync(0xffffffffu, near_page(wp < 9 ? P.memx + wp * 512 + (blockIdx.x & 63) * 2 :
          wp < 12 ? P.part + (blockIdx.x * 3 + wp - 9) * 512 : P.memx + 9 * 512 + 128 + (blockIdx.x & 63) * 2), 0);
      sts1(sb + Q_SEL + 4 * wp, sel * 4096);
    }
  }
  const int rank = rd_rank(), wg = rd_warp() >> 2;
  if (threadIdx.x == 448) {
    for (int c = 0; c < 9; c++) { mbar_init(sb + B_CP + 8 * c, 1); mbar_arrive(sb + B_CP + 8 * c); mbar_init(sb + B_OK + 8 * c, 1); mbar_init(sb + B_XF + 8 * c, 1); mbar_expect(sb + B_XF + 8 * c, 7168); }
    mbar_init(sb + B_E, 6); mbar_init(sb + B_G0, 1); mbar_expect(sb + B_G0, 9216); mbar_init(sb + B_E + 16, 6); mbar_init(sb + B_E + 24, 4);
    mbar_init(sb + B_SM, rank == 2 ? 1 : 2); mbar_init(sb + B_O, 1); mbar_init(sb + B_P, 1); mbar_init(sb + B_P + 8, 1);
    mbar_init(sb + B_REF, 1); mbar_init(sb + B_RES, 1); mbar_init(sb + B_PZ, 1); mbar_init(sb + B_AN, 1); mbar_init(sb + B_OXREADY, 4); mbar_init(sb + B_OXFREE, 1);
    mbar_expect(sb + B_SM, rank == 2 ? SM_BYTES : SX_BYTES); mbar_expect(sb + B_P, PX_BYTES); mbar_expect(sb + B_P + 8, PX_BYTES);
    mbar_expect(sb + B_O, 4096);
    sts1(sb + Q_REF + 4, 0);
    asm volatile("fence.mbarrier_init.release.cluster;" ::: "memory");
  }
  __syncthreads();
  PROF_G(6);
  if (wg < 2) {
    asm volatile("setmaxnreg.inc.sync.aligned.u32 176;");
    head_main(sb, P);
    PROF_END();
  } else if (wg == 2) {
    asm volatile("setmaxnreg.dec.sync.aligned.u32 120;");
    head_aux(sb, P);
    PROF_END();
  } else {
    asm volatile("setmaxnreg.dec.sync.aligned.u32 40;");
    head_service(sb, P);
    PROF_END();
  }
}

__device__ __forceinline__ void tail_gemm(uint32_t sb, const Params& P) {
  const int lane = threadIdx.x & 31, warp = rd_warp(), w = warp & 3, wg = warp >> 2, tid = threadIdx.x & 127;
  const __nv_bfloat16* wsrc = P.wo + (size_t)(blockIdx.x / 3) * 512 * DM + (blockIdx.x % 3) * 192 + wg * 64;
  uint32_t a[4 * W_KR];
  load_rows<29>(sb + wg * 65536, wsrc, DM, W_KR * 16, tid, 128);
  load_rows<3>(sb + W_WS + wg * 6144, wsrc + (size_t)W_KR * 16 * DM, DM, 512 - W_KR * 16, tid, 128);
  bar_sync_r(9 + wg, 128);
  load_afrags<W_KR>(a, sb + wg * 65536, w, lane);
  fence_async_smem();
  bar_sync<1, 416>();
  PROF_G(26);
  if (wg == 2) bar_arrive<2, 256>();
  const uint64_t dw = P.d_ws + wg * 384;
  float4* dst0 = g_acc + ((blockIdx.x % 3) * 12 + warp) * 32 + lane;
#pragma unroll 1
  for (int t = 1; t <= NT; t++) {
#pragma unroll 1
    for (int l = t > NSEG; l <= (t > LAG); l++) {
      const int seg = t - 1 - l * LAG, grp = (seg & 1) * 2 + l;
      const uint64_t db = P.d_ring + grp * 2048;
      float acc[16];
      bar_sync_r(2 + wg, 256);
#pragma unroll
      for (int c = 0; c < 4; c++) {
        if (wg == 0) mbar_wait(sb + B_FULL + 32 * grp + 8 * c, (seg >> 1) & 1);
        if (c == 0) PROF_T(6 * l + wg);
        wg_fence();
#pragma unroll
        for (int i = 0; i < 8; i++) {
          if (c == 0 && i == 0) wg_rs<0, 1>(acc, a, db, 0);
          else if (8 * c + i < W_KR) wg_rs<1, 1>(acc, a + 32 * c + 4 * i, db, 512 * c + 64 * i);
          else wg_ss<1, 1>(acc, dw, 128 * (8 * c + i - W_KR), db, 512 * c + 64 * i);
        }
      }
      wg_commit();
      bar_arrive_r(wg == 2 ? 2 : 3 + wg, 256);
      wg_wait<0>();
      reg_fence(acc);
      mbar_arrive_if0(tid, sb + B_EMPTY + 8 * grp);
      float4* dst = dst0 + (size_t)(l * 256 + seg * 4) * 1152;
#pragma unroll
      for (int j = 0; j < 4; j++)
        asm volatile("red.relaxed.gpu.global.add.v4.f32 [%0], {%1,%2,%3,%4};" :: "l"(dst + j * 1152),
                     "f"(acc[4 * j]), "f"(acc[4 * j + 1]), "f"(acc[4 * j + 2]), "f"(acc[4 * j + 3]) : "memory");
      bar_sync_r(5 + wg, 160);
    }
  }
}
__device__ __forceinline__ void tail_service(uint32_t sb) {
  const int lane = threadIdx.x & 31, warp = rd_warp();
  if (warp == 12) bar_sync<1, 416>();
#pragma unroll 1
  for (int t = 1; t <= NT; t++) {
    if (warp == 12) {
      const int h0 = (blockIdx.x / 3) * 4;
      warp_flag_wait(g_flags + FL_OX + t * 32 + h0 + (lane & 3), 1);
      fence_async_global();
#pragma unroll 1
      for (int l = t > NSEG; l <= (t > LAG); l++) {
        const int seg = t - 1 - l * LAG, grp = (seg & 1) * 2 + l;
        const uint4* src = g_ox + (size_t)(t % OXRING) * 32768 + l * 16384 + h0 * 512;
        const uint32_t bar = sb + B_FULL + 32 * grp;
        mbar_wait_lim(sb + B_EMPTY + 8 * grp, ((seg >> 1) & 1) ^ 1);
        mbar_expect_if0(lane > 3, bar + 8 * lane, 8192);
        if (elect_one()) {
#pragma unroll
          for (int j = 0; j < 4; j++) bulk_g2s(sb + W_RING + (grp * 4 + j) * 8192, src + j * 512, 8192, bar + 8 * j);
        }
        __syncwarp();
      }
      PROF_T(12);
      PROF_MID();
    } else {
#pragma unroll 1
      for (int l = t > NSEG; l <= (t > LAG); l++) {
        bar_sync_r(warp - 8, 160);
        if (lane == 0) flag_add(g_flags + FL_ACC + (l * 64 + t - 1 - l * LAG) * 32);
        __syncwarp();
        PROF_T(6 * l + warp - 10);
      }
    }
  }
}

__device__ __forceinline__ void wait_k1(uint32_t sb, int n) {
  uint32_t c = 0;
  while ((int)lds1(sb + W_K1) < n) {
    __nanosleep(64);
    if (++c > SPIN_LIMIT) __trap();
  }
}
__device__ __forceinline__ void tail_finisher(uint32_t sb, const Params& P) {
  const int lane = threadIdx.x & 31, warp = rd_warp(), kind = warp < 12 ? warp / 6 : warp & 1, f = warp - 6 * kind, tg = blockIdx.x & 3;
  if (warp >= 14) {
    const uint32_t set = lds1(sb + Q_SET), ft = sb + W_FO + kind * 576;
    if (tg == 0) for (int i = kind * 32 + lane; i < FL_TOTAL; i += 64) g_flagsets[FL_TOTAL - set + i] = 0;
#pragma unroll 1
    for (int t = 0; t < NSEG; t++) {
      warp_flag_wait(g_flags + FL_ACC + (64 + t) * 32, 72);
      PROF_T(17);
      if (t == 0 && tg == 0 && threadIdx.x == 448) g_epoch = set ? 0 : 1;
      const float4* ac = g_acc + ((size_t)(256 + t * 4 + tg) * 36 + kind * 18) * 32 + lane;
      float4 v[18];
#pragma unroll
      for (int i = 0; i < 18; i++) v[i] = __ldcg(ac + i * 32);
#pragma unroll
      for (int i = 0; i < 9; i++) {
        const uint4 r = lds4(sb + W_RS + (8 + (t & 7)) * 9216 + (kind * 9 + i) * 512 + lane * 16);
        stsm4t(ft + (lane & 7) * 1168 + (lane >> 3) * 16 + 64 * i, bf2_add(r.x, pack_bf16(v[2 * i].x, v[2 * i].y)), bf2_add(r.y, pack_bf16(v[2 * i].z, v[2 * i].w)),
               bf2_add(r.z, pack_bf16(v[2 * i + 1].x, v[2 * i + 1].y)), bf2_add(r.w, pack_bf16(v[2 * i + 1].z, v[2 * i + 1].w)));
      }
      fence_async_smem();
      __syncwarp();
      mbar_arrive_if0(lane, sb + B_RF + 8 * (t & 7));
      wait_k1(sb, min(t + LAG + 1, NSEG));
      if (lane < 8) {
        bulk_s2g(P.out + (size_t)((t * 4 + tg) * 8 + lane) * DM + kind * 288, ft + lane * 1168, 576);
        bulk_commit_wait();
      }
      __syncwarp();
      PROF_T(18);
    }
    return;
  }
  if (warp >= 12) {
    for (int i = kind * 32 + lane; i < 1152; i += 64) sts4(sb + W_Z + i * 16, make_uint4(0, 0, 0, 0));
    fence_async_smem();
    bar_sync<12, 64>();
#pragma unroll 1
    for (int t = -1; t <= NSEG; t++) {
      if (kind == 0 && t + 1 < NSEG) {
        const uint32_t bar = sb + B_FT + 8 * ((t + 1) & 1);
        mbar_expect_if0(lane, bar, 9216);
        __syncwarp();
        if (lane < 8) bulk_g2s(sb + W_FT + ((t + 1) & 1) * 9344 + lane * 1168, P.x0 + (size_t)(((t + 1) * 4 + tg) * 8 + lane) * DM, 1152, bar);
      }
      if (t < 0) continue;
      if (t < NSEG) bar_sync_r(9 + 2 * kind, 224);
      if (lane == 0) {
        flag_add(g_flags + FL_XS + (t + kind * LAG) * 32 + kind * 16);
        if (kind) { sts1(sb + W_K1, t + 1); PROF_T(14); }
        if (kind ? t < NSEG : t < LAG) bulk_s2g(g_acc + (size_t)(kind * 256 + t * 4 + tg) * 1152, sb + W_Z, 18432);
        if (kind && t + LAG < NSEG) bulk_s2g(g_acc + (size_t)((t + LAG) * 4 + tg) * 1152, sb + W_Z, 18432);
        bulk_commit_wait();
      }
      __syncwarp();
      if (kind) PROF_MID();
    }
    return;
  }
  const uint32_t BF_1 = 0x3F803F80u;
  const uint32_t* ys = (const uint32_t*)(g_y + ((tg >> 1) * DM + f * 96 + (lane >> 2)) * 2 + (tg & 1)) + (lane & 3);
  const uint32_t rs = sb + W_RS + f * 1536 + lane * 16;
  uint32_t y[12] = {};
#pragma unroll 1
  for (int t = 0; t < NSEG; t++) {
    uint32_t x[12];
    if (kind == 0) {
      wait_k1(sb, t - 6);
      mbar_wait(sb + B_FT + 8 * (t & 1), (t >> 1) & 1);
#pragma unroll
      for (int i = 0; i < 3; i++)
        ldsm4t(x[4 * i], x[4 * i + 1], x[4 * i + 2], x[4 * i + 3], sb + W_FT + (t & 1) * 9344 + (lane & 7) * 1168 + f * 192 + (lane >> 3) * 16 + 64 * i);
    } else {
      warp_flag_wait(g_flags + FL_ACC + t * 32, 72);
      PROF_T(13);
#pragma unroll
      for (int i = 0; i < 6; i++) {
        const float4 v = __ldcg(g_acc + ((size_t)(t * 4 + tg) * 36 + f * 6 + i) * 32 + lane);
        x[2 * i] = pack_bf16(v.x, v.y); x[2 * i + 1] = pack_bf16(v.z, v.w);
      }
#pragma unroll
      for (int i = 0; i < 3; i++) {
        const uint4 r = lds4(rs + (t & 7) * 9216 + i * 512);
        x[4 * i] = bf2_add(x[4 * i], r.x); x[4 * i + 1] = bf2_add(x[4 * i + 1], r.y); x[4 * i + 2] = bf2_add(x[4 * i + 2], r.z); x[4 * i + 3] = bf2_add(x[4 * i + 3], r.w);
      }
      mbar_wait(sb + B_RF + 8 * (t & 7), ((t >> 3) & 1) ^ 1);
      PROF_T(15);
    }
    {
      if (t == 0) PROF_G(27);
#pragma unroll 1
      for (int pass = 0; pass < 2; pass++) {
        float g[2][4] = {};
#pragma unroll
        for (int i = 0; i < 12; i++) {
          uint32_t u;
          asm volatile("movmatrix.sync.aligned.m8n8.trans.b16 %0, %1;" : "=r"(u) : "r"(x[i]));
          mma1688(g[i & 1], u, BF_1, u);
        }
        const uint32_t st = sb + W_ST + kind * 1024 + pass * 512 + (lane & 3) * 16;
        if ((lane >> 3) == (lane & 3))
          asm volatile("st.shared.v2.f32 [%0], {%1,%2};" :: "r"(st + f * 64 + (lane & 4) * 2), "f"(lane & 4 ? g[0][3] + g[1][3] : g[0][2] + g[1][2]),
                       "f"(lane & 4 ? g[0][1] + g[1][1] : g[0][0] + g[1][0]) : "memory");
        bar_sync_r(8 + 2 * kind, 192);
        float s0 = 0.f, s1 = 0.f, q0 = 0.f, q1 = 0.f;
        if (kind && pass == 0) PROF_T(19);
        if (kind && pass == 1) PROF_T(21);
#pragma unroll
        for (int i = 0; i < 6; i++) {
          const float4 e = lds4f(st + i * 64);
          s0 += e.x; q0 += e.y; s1 += e.z; q1 += e.w;
        }
        s0 *= 1.f / 576.f; s1 *= 1.f / 576.f;
        const float v0 = fmaf(q0, 1.f / 576.f, -s0 * s0), v1 = fmaf(q1, 1.f / 576.f, -s1 * s1);
        const uint32_t nmean = pack_bf16(-s0, -s1), vb = pack_bf16(fmaxf(v0, 0.f), fmaxf(v1, 0.f));
        const uint32_t ve = pack_bf16(bf_lo(vb) + 1e-5f, bf_hi(vb) + 1e-5f), sd = pack_bf16(sqr(bf_lo(ve)), sqr(bf_hi(ve)));
        const float r0 = rcp(bf_lo(sd)), r1 = rcp(bf_hi(sd));
        const uint32_t rh = pack_bf16(r0, r1), rl = pack_bf16(r0 - bf_lo(rh), r1 - bf_hi(rh));
        if (pass == 0 && (t == 0 || t == 4 * CT_A || t == 4 * CT_B || t == 4 * CT_C)) {
          if (t == 0) PROF_G(25);
          warp_flag_wait(g_flags + FL_Y + t * 8, t < 4 * CT_B ? 32 : DM);
          if (t == 0) PROF_G(26);
#pragma unroll
          for (int i = 0; i < 12; i++) y[i] = __ldcg(ys + t * (DM * 16) + i * 64);
        }
        uint32_t* xd = (uint32_t*)(g_xs + (size_t)(t + kind * LAG) * 4608 + (kind * 4 + tg) * 64 + (f * 3 >> 1) * 512 + (f & 1) * 32) + lane;
#pragma unroll
        for (int i = 0; i < 12; i++) {
          const uint32_t d = bf2_add(x[i], nmean), q = bf2_op(d, rh, bf2_mul(d, rl));
          if (pass == 0) x[i] = bf2_add(x[i], bf2_mul(q, y[i]));
          else xd[i < 4 ? i * 32 : i < 8 ? i * 32 + (f & 1) * 1792 : i * 32 + 1792] = q;
        }
        if (pass == 0) {
#pragma unroll
          for (int i = 0; i < 3; i++) sts4(rs + (kind * 8 + (t & 7)) * 9216 + i * 512, make_uint4(x[4 * i], x[4 * i + 1], x[4 * i + 2], x[4 * i + 3]));
        }
        if (kind && pass == 0) PROF_T(20);
        if (kind && pass == 1) PROF_T(22);
      }
      if (kind) PROF_T(16);
      if (t < 3) PROF_G(28 + t);
      bar_sync_r(9 + 2 * kind, 224);
#pragma unroll
      for (int i = 0; i < 12; i++) y[i] = __ldcg(ys + ((t + 1) & 63) * (DM * 16) + i * 64);
    }
  }
}

template <int NP, typename V>
__device__ __forceinline__ void kv_block(uint4 (&o)[2 * NP], const Params& P, int r0, int c0) {
  V kk[11], vv[8];
  uint4 sw[NP];
#pragma unroll
  for (int i = 0; i < NP; i++) sw[i] = __ldg((const uint4*)(P.shift + (c0 + 2 * i) * 4));
#pragma unroll
  for (int i = 0; i < 11; i++) kk[i] = r0 + i >= 3 ? __ldg((const V*)(P.ck + (size_t)(r0 + i - 3) * DM + c0)) : V{};
#pragma unroll
  for (int i = 0; i < 8; i++) vv[i] = __ldg((const V*)(P.cv + (size_t)(r0 + i) * DM + c0));
#pragma unroll
  for (int cp = 0; cp < NP; cp++) {
    const uint32_t wt[4] = {__byte_perm(sw[cp].y, sw[cp].w, 0x7632), __byte_perm(sw[cp].y, sw[cp].w, 0x5410),
                            __byte_perm(sw[cp].x, sw[cp].z, 0x7632), __byte_perm(sw[cp].x, sw[cp].z, 0x5410)};
    uint32_t e[8];
#pragma unroll
    for (int i = 0; i < 8; i++) {
      uint32_t a = bf2_mul(((const uint32_t*)&kk[i])[cp], wt[0]);
#pragma unroll
      for (int j = 1; j < 4; j++) a = bf2_add(a, bf2_mul(((const uint32_t*)&kk[i + j])[cp], wt[j]));
      e[i] = bf2_mul(a, ((const uint32_t*)&vv[i])[cp]);
    }
    o[2 * cp] = make_uint4(__byte_perm(e[0], e[1], 0x5410), __byte_perm(e[2], e[3], 0x5410), __byte_perm(e[4], e[5], 0x5410), __byte_perm(e[6], e[7], 0x5410));
    o[2 * cp + 1] = make_uint4(__byte_perm(e[0], e[1], 0x7632), __byte_perm(e[2], e[3], 0x7632), __byte_perm(e[4], e[5], 0x7632), __byte_perm(e[6], e[7], 0x7632));
  }
}
__device__ __forceinline__ void kv_task(const Params& P, int id) {
  const int lane = threadIdx.x & 31, tq = id / 9, c0 = (id % 9) * 64 + (lane >> 2) * 8;
  uint4 o[8];
  kv_block<4, uint4>(o, P, tq * 32 + (lane & 3) * 8, c0);
#pragma unroll
  for (int c = 0; c < 8; c++) g_kv[((size_t)tq * DM + c0 + c) * 4 + (lane & 3)] = o[c];
}
__device__ __forceinline__ int next_job(uint32_t sb) {
  int j = 0;
  if ((threadIdx.x & 31) == 0) j = atomicAdd(g_flags + FL_KV + 96, 1);
  return __shfl_sync(0xffffffffu, j, 0);
}
__device__ __forceinline__ uint2 lds2_ro(uint32_t a) { uint2 v; asm("ld.shared.v2.u32 {%0,%1}, [%2];" : "=r"(v.x), "=r"(v.y) : "r"(a)); return v; }

template <int T0, int T1>
__device__ __forceinline__ void conv_job(uint32_t sb, const Params& P, int ch) {
  const int lane = threadIdx.x & 31, w = threadIdx.x >> 5;
  const uint32_t ub = sb + w * C_CH, zb = ub + C_U;
  constexpr int NL = (T1 + 1) / 2;
  constexpr bool CTA = T1 <= CT_B;
  PROF_G(13 + 4 * (T0 == 0 ? 0 : T0 == CT_A ? 1 : 2));
  uint2 q[T1];
#pragma unroll
  for (int u = 0; u < T1; u++) q[u] = __ldg((const uint2*)(P.ssm_k + (size_t)ch * SEQ) + u * 32 + lane);
  const uint32_t dd = (uint32_t)__bfloat16_as_ushort(P.ssm_d[ch]) * 0x10001u;
  if (CTA) {
#pragma unroll
    for (int tq = w; tq < 4 * T1; tq += 16) {
      uint4 o[2];
      const int tgp = tq * 4 + (lane & 3), c0 = (lane >> 2) * 2;
      kv_block<1, uint32_t>(o, P, tgp * 8, ch - w + c0);
#pragma unroll
      for (int c = 0; c < 2; c++) {
        sts4(sb + (c0 + c) * C_CH + 256 + tgp * 16, o[c]);
        if (T0) g_kv[((size_t)tq * DM + ch - w + c0 + c) * 4 + (lane & 3)] = o[c];
      }
    }
    __syncwarp();
  } else {
    uint4 o[NL];
#pragma unroll
    for (int u = 0; u < NL; u++) o[u] = __ldcg(g_kv + ((size_t)(u * 8 + (lane >> 2)) * DM + ch) * 4 + (lane & 3));
#pragma unroll
    for (int u = 0; u < NL; u++) sts4(ub + 256 + (u * 32 + lane) * 16, o[u]);
  }
  if (lane < 16) { sts4(ub + lane * 16, make_uint4(0, 0, 0, 0)); sts1(zb + lane * 4, 0); }
#pragma unroll
  for (int u = 0; u < T1; u++) {
    const uint32_t pv = __shfl_sync(0xffffffffu, lane == 31 ? (u ? q[u ? u - 1 : 0].y : 0u) : q[u].y, (lane + 31) & 31);
    sts4(zb + 64 + (u * 32 + lane) * 16, make_uint4(__byte_perm(q[u].x, pv, 0x7610), __byte_perm(q[u].x, q[u].x, 0x1032),
                                                   __byte_perm(q[u].y, q[u].x, 0x7610), __byte_perm(q[u].y, q[u].y, 0x1032)));
  }
  if (CTA) __syncthreads(); else __syncwarp();
  PROF_G(14 + 4 * (T0 == 0 ? 0 : T0 == CT_A ? 1 : 2));
  float acc[T1 - T0][4];
#pragma unroll
  for (int i = 0; i < T1 - T0; i++) acc[i][0] = acc[i][1] = acc[i][2] = acc[i][3] = 0.f;
#pragma unroll(T0 == 0 ? 4 : 1)
  for (int r = 0; r < 8; r++) {
    uint2 b[T1];
    uint32_t ba = ub + 256 - r * 32 + lane * 8, zp = zb + 64 + (16 * r + 2 * (lane >> 2) - 4 * (lane & 3)) * 4;
    asm volatile("" : "+r"(zp), "+r"(ba) :: "memory");
#pragma unroll
    for (int i = 0; i < T1; i++) b[i] = lds2_ro(ba + i * 256);
#pragma unroll
    for (int mu = 0; mu < T1; mu++) {
      const uint2 a01 = lds2_ro(zp + 512 * mu), a23 = lds2_ro(zp + 512 * mu - 8);
#pragma unroll
      for (int i = (mu > T0 ? mu : T0); i < T1; i++) mma16816(acc[i - T0], a01.x, a01.y, a23.x, a23.y, b[i - mu].x, b[i - mu].y);
    }
  }
  PROF_G(15 + 4 * (T0 == 0 ? 0 : T0 == CT_A ? 1 : 2));
#pragma unroll
  for (int i = 0; i < T1 - T0; i++)
#pragma unroll
    for (int e = 0; e < 2; e++) {
      const int col = (T0 + i) * 8 + 2 * (lane & 3) + e;
      ((uint32_t*)g_y)[((size_t)col * DM + ch) * 8 + (lane >> 2)] =
          bf2_add(pack_bf16(acc[i][e], acc[i][2 + e]), bf2_mul(lds1(ub + 256 + col * 32 + (lane >> 2) * 4), dd));
    }
  if (CTA) __syncthreads(); else __syncwarp();
  PROF_G(16 + 4 * (T0 == 0 ? 0 : T0 == CT_A ? 1 : 2));
  if (CTA ? threadIdx.x == 480 && ch < 512 : lane == 0) flag_add(g_flags + FL_Y + T0 * 32);
  __syncwarp();
}

__global__ void __launch_bounds__(512, 1) tail_kernel(const Params P) {
  extern __shared__ uint8_t smem_raw[];
  const uint32_t sb = (uint32_t)__cvta_generic_to_shared(smem_raw);
  if (sb != SB0) __trap();
  PROF_BEGIN();
  if (threadIdx.x == 0) {
    for (int c = 0; c < 16; c++) mbar_init(sb + B_FULL + 8 * c, 1);
    for (int c = 0; c < 4; c++) mbar_init(sb + B_EMPTY + 8 * c, 3);
    for (int c = 0; c < 2; c++) mbar_init(sb + B_FT + 8 * c, 1);
    for (int c = 0; c < 8; c++) mbar_init(sb + B_RF + 8 * c, 2);
    sts1(sb + W_K1, 0);
    sts1(sb + Q_SET, (__ldcg(&g_epoch) & 1) * FL_TOTAL);
    fence_async_smem();
  }
  const int b = blockIdx.x, w = threadIdx.x >> 5;
  if ((b >> 2) == 6) {
    __syncthreads();
  } else {
#pragma unroll 1
    for (int g = b; g == b || (g >> 2) == 6; g -= 8) conv_job<0, CT_A>(sb, P, g * 16 + w);
    PROF_G(3);
#pragma unroll 1
    for (int g = b; g == b || (g >> 2) == 6; g -= 8) conv_job<CT_A, CT_B>(sb, P, g * 16 + w);
    PROF_G(4);
    constexpr int KV0 = 36 * CT_B, KV1 = KV0 + 192;
    int job = b < 32 ? KV0 + (b - 28) * 16 + w : -1;
#pragma unroll 1
    for (int k = 0; b >= 28; k++) {
      if (job >= 0) {
        kv_task(P, job);
        __syncwarp();
        if ((threadIdx.x & 31) == 0) flag_add(g_flags + FL_KV + (job < KV1 ? 0 : 32));
        if (job + 64 < KV1) { job += 64; continue; }
      }
      if (job < KV1) {
        warp_flag_wait(g_flags + FL_Y + CT_A * 32, 32);
        warp_flag_wait(g_flags + FL_KV, 192);
        spin_until(rd_clock() + (w >> 2) * 2000);
      }
      while ((job = next_job(sb)) < DM) conv_job<CT_B, CT_C>(sb, P, job);
      if (job < DM + 128) PROF_G(6);
      job -= DM - KV1;
      if (job >= 576) break;
    }
    if (b >= 28) {
      warp_flag_wait(g_flags + FL_KV + 32, 576 - KV1);
#pragma unroll 1
      for (job -= 576; job < DM; job = next_job(sb) - DM - (576 - KV1)) conv_job<CT_C, 16>(sb, P, job);
      PROF_G(5);
      PROF_END();
      return;
    }
    __syncwarp();
  }
  if (blockIdx.x >= 24) {
    PROF_G(24);
    tail_finisher(sb, P);
    PROF_END();
    asm volatile("griddepcontrol.wait;" ::: "memory");
  } else if (rd_warp() < 12) {
    asm volatile("setmaxnreg.inc.sync.aligned.u32 160;");
    tail_gemm(sb, P);
    PROF_END();
  } else {
    asm volatile("setmaxnreg.dec.sync.aligned.u32 32;");
    tail_service(sb);
    PROF_END();
  }
}

}

extern "C" void kernel_launch(void* const* d_in, const int* in_sizes, int n_in, void* d_out, int out_size) {
  typedef const __nv_bfloat16* bp;
  Params P;
  P.x0 = (bp)d_in[0]; P.ck = (bp)d_in[1]; P.cv = (bp)d_in[2]; P.shift = (bp)d_in[3]; P.ssm_k = (bp)d_in[4]; P.ssm_d = (bp)d_in[5];
  P.mem0 = (bp)d_in[7]; P.wq = (bp)d_in[8]; P.wk = (bp)d_in[9]; P.wv = (bp)d_in[10]; P.wo = (bp)d_in[11];
  P.out = (__nv_bfloat16*)d_out;
  void* xc = nullptr;
  cudaGetSymbolAddress(&xc, g_xchg);
  P.part = (uint4*)(((uintptr_t)xc + 8191) & ~(uintptr_t)8191);
  P.memx = P.part + 288 * 512;
  P.d_x = mkdesc(Q_X, 128, 1024, 0); P.d_wl = mkdesc(Q_WL, 16, 1024, 1);
  P.d_ring = mkdesc(W_RING, 512, 128, 0); P.d_ws = mkdesc(W_WS, 16, 1024, 1);
  cudaFuncSetAttribute(head_kernel, cudaFuncAttributeMaxDynamicSharedMemorySize, SMEM_TOTAL);
  cudaFuncSetAttribute(tail_kernel, cudaFuncAttributeMaxDynamicSharedMemorySize, SMEM_TOTAL);
  head_kernel<<<96, 512, SMEM_TOTAL>>>(P);
  cudaLaunchConfig_t cfg = {};
  cfg.gridDim = dim3(36); cfg.blockDim = dim3(512); cfg.dynamicSmemBytes = SMEM_TOTAL; cfg.stream = 0;
  cudaLaunchAttribute attr[1];
  attr[0].id = cudaLaunchAttributeProgrammaticStreamSerialization;
  attr[0].val.programmaticStreamSerializationAllowed = 1;
  cfg.attrs = attr; cfg.numAttrs = 1;
  cudaLaunchKernelEx(&cfg, tail_kernel, P);
}
```

```cpp
#include <cuda_runtime.h>
#include <cuda_bf16.h>
#include <stdint.h>

namespace {

constexpr int SEQ = 2048, DM = 576, NSEG = 64;
#define LAG_V 5
#define RV_V 2000
#define R1_V 380
#define R0_V 590
#define V1_V 80
#define V2_V 200
#define Q1_V 150
#define Q2_V 290
#define SWAP_V 1
#define ST0_V 200
#define GX_V 1130
#define AD_V 0
#define RS_V 5
#define CALIB 0
#define RF_V 2350
#define RL_V 2000
#define PA1_V 500
#define PA0_V 700
#define ST_V 5
#define XA_V 1
#define XP_V 160
#define KPV_V 16
#define KP1_V 24
#define KP0_V 28
constexpr int LAG = LAG_V;
constexpr int NT = NSEG + LAG;
constexpr int OXRING = 8;
static_assert(LAG >= 3 && LAG < OXRING, "pipeline lag");
constexpr uint32_t D_RED = RV_V;
__host__ __device__ constexpr uint32_t rank_delay(int r) { return r == 2 ? 0 : r ? R1_V : R0_V; }
__host__ __device__ constexpr int tile_of(int r, int i) { return r == 2 ? i : SWAP_V ? (r ? 3 + i + (i >> 1) : 5 + i + (i > 0)) : 6 - 3 * r + i; }
__host__ __device__ constexpr uint32_t tile_delay(int r, int i) { return (i == 0 ? 0 : r == 2 ? (i == 1 ? V1_V : V2_V) : i == 1 ? Q1_V : Q2_V) * 9 / 16; }
constexpr uint32_t D_DUE = RF_V, D_LATE = RL_V;
constexpr uint32_t D_GX = GX_V * 9 / 16, D_ADAPT = AD_V * 9 / 16;
constexpr int KP_V = KPV_V, KP_1 = KP1_V, KP_0 = KP0_V;
constexpr int KP_MAX = KP_0 > KP_1 ? KP_0 : KP_1;
constexpr uint32_t SB0 = 1024;
constexpr float SM_SCALE = 0.08838834764831845f * 1.4426950408889634f;
constexpr uint32_t SENT = 0x80008000u;
constexpr uint32_t SPIN_LIMIT = 1u << 21;

constexpr int FL_XS = 0;
constexpr int FL_ACC = (NT + 2) * 32;
constexpr int FL_OX = FL_ACC + 128 * 32;
constexpr int FL_SEL = FL_OX + (NT + 1) * 32;
constexpr int FL_Y = FL_SEL + 96 * 4;
constexpr int FL_KV = FL_Y + 512;
constexpr int FL_TOTAL = FL_KV + 128;

__device__ __align__(1024) uint4 g_y[256 * DM];
__device__ __align__(1024) uint4 g_kv[256 * DM];
__device__ __align__(1024) float4 g_acc[2 * 256 * 36 * 32];
__device__ __align__(1024) uint4 g_xs[NT * 4608];
__device__ __align__(1024) uint4 g_ox[OXRING * 512 * 8 * 8];
__device__ __align__(1024) uint4 g_xchg[(288 + 10 + 1) * 512];
__device__ __align__(1024) uint32_t g_flagsets[2 * FL_TOTAL];
__device__ uint32_t g_epoch;
#define PROF_T(slot) do {} while (0)
#define PROF_END() do {} while (0)
#define PROF_W(cond, slot) do {} while (0)
#define PROF_V(cond, slot, val) do { (void)(val); } while (0)
#define PROF_G(slot) do {} while (0)
#define PROF_OR(slot, val) do {} while (0)
#define PROF_A(idx, val) do { (void)(val); } while (0)
#define PROF_BEGIN() do {} while (0)
#define PROF_MID() do {} while (0)

#define CHINT ""
#define HINT ", 100000"
__device__ __forceinline__ uint32_t pack_bf16(float lo, float hi) {
  uint32_t r; asm("cvt.rn.bf16x2.f32 %0, %1, %2;" : "=r"(r) : "f"(hi), "f"(lo)); return r;
}
__device__ __forceinline__ float bf_lo(uint32_t w) { return __uint_as_float(__byte_perm(w, 0, 0x1044)); }
__device__ __forceinline__ float bf_hi(uint32_t w) { return __uint_as_float(w & 0xFFFF0000u); }
__device__ __forceinline__ uint32_t mapa(uint32_t a, uint32_t r) {
  uint32_t o; asm("mapa.shared::cluster.u32 %0, %1, %2;" : "=r"(o) : "r"(a), "r"(r)); return o;
}
__device__ __forceinline__ void mbar_init(uint32_t bar, uint32_t cnt) {
  asm volatile("mbarrier.init.shared::cta.b64 [%0], %1;" :: "r"(bar), "r"(cnt) : "memory");
}
__device__ __forceinline__ void mbar_expect(uint32_t bar, uint32_t bytes) {
  asm volatile("mbarrier.arrive.expect_tx.shared::cta.b64 _, [%0], %1;" :: "r"(bar), "r"(bytes) : "memory");
}
__device__ __forceinline__ void mbar_arrive(uint32_t bar) {
  asm volatile("mbarrier.arrive.shared::cta.b64 _, [%0];" :: "r"(bar) : "memory");
}
__device__ __forceinline__ void mbar_arrive_if0(uint32_t sel, uint32_t bar) {
  asm volatile("{\n.reg .pred p;\nsetp.eq.u32 p, %1, 0;\n@p mbarrier.arrive.shared::cta.b64 _, [%0];\n}" :: "r"(bar), "r"(sel) : "memory");
}
__device__ __forceinline__ void mbar_expect_if0(uint32_t sel, uint32_t bar, uint32_t bytes) {
  asm volatile("{\n.reg .pred p;\nsetp.eq.u32 p, %1, 0;\n@p mbarrier.arrive.expect_tx.shared::cta.b64 _, [%0], %2;\n}" :: "r"(bar), "r"(sel), "r"(bytes) : "memory");
}
__device__ __forceinline__ void mbar_rarrive_if0(uint32_t sel, uint32_t bar) {
  asm volatile("{\n.reg .pred p;\nsetp.eq.u32 p, %1, 0;\n@p mbarrier.arrive.relaxed.cluster.shared::cluster.b64 _, [%0];\n}" :: "r"(bar), "r"(sel) : "memory");
}
__device__ __forceinline__ void mbar_wait_lim(uint32_t bar, uint32_t par) {
  asm volatile(
    "{\n.reg .pred p;\n.reg .u32 c;\nmov.u32 c, 0;\n"
    "W_%=:\n"
    "mbarrier.try_wait.parity.shared::cta.b64 p, [%0], %1;\n"
    "@p bra D_%=;\n"
    "add.u32 c, c, 1;\nsetp.lt.u32 p, c, %2;\n@p bra W_%=;\ntrap;\n"
    "D_%=:\n}\n" :: "r"(bar), "r"(par), "n"(SPIN_LIMIT) : "memory");
}
__device__ __forceinline__ void mbar_wait(uint32_t bar, uint32_t par) {
  asm volatile(
    "{\n.reg .pred p;\n"
    "W_%=:\n"
    "mbarrier.try_wait.parity.shared::cta.b64 p, [%0], %1" HINT ";\n"
    "@!p bra W_%=;\n}\n" :: "r"(bar), "r"(par) : "memory");
}
__device__ __forceinline__ void mbar_spin(uint32_t bar, uint32_t par) {
  asm volatile("{\n.reg .pred p;\nW_%=:\nmbarrier.try_wait.parity.shared::cta.b64 p, [%0], %1;\n@!p bra W_%=;\n}\n" :: "r"(bar), "r"(par) : "memory");
}
__device__ __forceinline__ uint32_t mbar_test(uint32_t bar, uint32_t par) {
  uint32_t r;
  asm volatile("{\n.reg .pred p;\nmbarrier.test_wait.parity.shared::cta.b64 p, [%1], %2;\nselp.u32 %0, 1, 0, p;\n}" : "=r"(r) : "r"(bar), "r"(par) : "memory");
  return __shfl_sync(0xffffffffu, r, 0);
}
__device__ __forceinline__ void mbar_wait_if(uint32_t& done, uint32_t test, uint32_t bar, uint32_t par, bool force) {
  asm volatile(
    "{\n.reg .pred p, q;\nsetp.ne.u32 p, %0, 0;\n@p bra.uni D_%=;\nsetp.ne.u32 q, %4, 0;\n"
    "mbarrier.test_wait.parity.shared::cta.b64 p, [%1], %3;\n"
    "or.pred p, p, q;\n@!p bra D_%=;\n"
    "W_%=:\n"
    "mbarrier.try_wait.parity.shared::cta.b64 p, [%2], %3, 100000;\n"
    "@!p bra W_%=;\nmov.u32 %0, 1;\nD_%=:\n}\n" : "+r"(done) : "r"(test), "r"(bar), "r"(par), "r"((uint32_t)force) : "memory");
}
template <int ID, int N> __device__ __forceinline__ void bar_sync() { asm volatile("bar.sync %0, %1;" :: "n"(ID), "n"(N) : "memory"); }
template <int ID, int N> __device__ __forceinline__ void bar_arrive() { asm volatile("bar.arrive %0, %1;" :: "n"(ID), "n"(N) : "memory"); }
__device__ __forceinline__ void bar_sync_r(int id, int n) { asm volatile("bar.sync %0, %1;" :: "r"(id), "r"(n) : "memory"); }
__device__ __forceinline__ void bar_arrive_r(int id, int n) { asm volatile("bar.arrive %0, %1;" :: "r"(id), "r"(n) : "memory"); }
__device__ __forceinline__ uint32_t pin(uint32_t x) { return __shfl_sync(0xffffffffu, x, threadIdx.x); }
__device__ __forceinline__ void cluster_sync() {
  asm volatile("barrier.cluster.arrive.aligned;\nbarrier.cluster.wait.aligned;" ::: "memory");
}
__device__ __forceinline__ void fence_async_smem() { asm volatile("fence.proxy.async.shared::cta;" ::: "memory"); }
__device__ __forceinline__ void fence_async_global() { asm volatile("fence.proxy.async.global;" ::: "memory"); }
__device__ __forceinline__ uint4 ld_poll(const uint4* p) {
  uint4 v;
  asm volatile("ld.relaxed.gpu.global.v4.u32 {%0,%1,%2,%3}, [%4];" : "=r"(v.x), "=r"(v.y), "=r"(v.z), "=r"(v.w) : "l"(p) : "memory");
  return v;
}
__device__ __forceinline__ uint32_t rd_clock() { uint64_t c; asm volatile("mov.u64 %0, %%clock64;" : "=l"(c) :: "memory"); return (uint32_t)c; }
__device__ __forceinline__ void spin_until(uint32_t when) {
  asm volatile("{\n.reg .pred p;\n.reg .b64 c;\n.reg .s32 lo;\nS_%=:\nmov.u64 c, %%clock64;\ncvt.u32.u64 lo, c;\nsub.s32 lo, lo, %0;\n"
               "setp.lt.s32 p, lo, 0;\n@p bra.uni S_%=;\n}" :: "r"(when) : "memory");
}
__device__ __forceinline__ uint32_t near_page(uint4* pair, uint32_t mark) {
  uint32_t best0 = ~0u, best1 = ~0u;
  const int lane = threadIdx.x & 31;
  if (lane < 4) asm volatile("st.relaxed.gpu.global.v4.u32 [%0], {%1,%1,%1,%1};" :: "l"(pair + (lane >> 1) * 256 + (lane & 1)), "r"(mark) : "memory");
  __syncwarp();
#pragma unroll 1
  for (int r = 0; r < 8; r++) {
    if (r >= 4 && !(r & 1) && __all_sync(0xffffffffu, max(best0, best1) - min(best0, best1) > 110u && min(best0, best1) < 420u)) break;
    uint32_t t0, t1, v;
    asm volatile("mov.u32 %0, %%clock;" : "=r"(t0) :: "memory");
    asm volatile("{\n.reg .pred p;\nsetp.eq.u32 p, %2, 0;\nmov.u32 %0, 0;\n@p atom.relaxed.gpu.global.exch.b32 %0, [%1], %3;\n}"
                 : "=&r"(v) : "l"(pair + (r & 1) * 256), "r"(lane), "r"(mark) : "memory");
    asm volatile("{\n.reg .pred p;\nsetp.ne.u32 p, %1, 0x9E3779B9;\nmov.u32 %0, %2;\n@p mov.u32 %0, %%clock;\n}" : "=&r"(t1) : "r"(v), "r"(t0 - 1) : "memory");
    if (r & 1) best1 = min(best1, t1 - t0); else best0 = min(best0, t1 - t0);
  }
  return best1 < best0;
}
__device__ __forceinline__ void st_gpu4(uint4* p, uint32_t a, uint32_t b, uint32_t c, uint32_t d) {
  asm volatile("st.relaxed.gpu.global.v4.u32 [%0], {%1,%2,%3,%4};" :: "l"(p), "r"(a), "r"(b), "r"(c), "r"(d) : "memory");
}
__device__ __forceinline__ void st_gpu1(uint32_t* p, uint32_t a) {
  asm volatile("st.relaxed.gpu.global.u32 [%0], %1;" :: "l"(p), "r"(a) : "memory");
}
__device__ __forceinline__ void st_gpu1_if(bool c, uint32_t* p, uint32_t a) {
  asm volatile("{\n.reg .pred p;\nsetp.ne.u32 p, %2, 0;\n@p st.relaxed.gpu.global.u32 [%0], %1;\n}" :: "l"(p), "r"(a), "r"((uint32_t)c) : "memory");
}
__device__ __forceinline__ void warp_flag_wait(const uint32_t* p, uint32_t target) {
  uint32_t v, n = 0;
  do {
    asm volatile("ld.relaxed.gpu.global.u32 %0, [%1];" : "=r"(v) : "l"(p) : "memory");
    if (++n > SPIN_LIMIT) __trap();
  } while (__any_sync(0xffffffffu, v < target));
}
__device__ __forceinline__ void flag_add(uint32_t* p) {
  asm volatile("red.release.gpu.global.add.u32 [%0], 1;" :: "l"(p) : "memory");
}
__device__ __forceinline__ void bulk_g2s(uint32_t dst, const void* src, uint32_t bytes, uint32_t bar) {
  asm volatile("cp.async.bulk.shared::cluster.global.mbarrier::complete_tx::bytes [%0], [%1], %2, [%3];"
               :: "r"(dst), "l"(src), "r"(bytes), "r"(bar) : "memory");
}
__device__ __forceinline__ void bulk_g2s_mc(uint32_t dst, const void* src, uint32_t bytes, uint32_t bar, uint16_t mask) {
  asm volatile("cp.async.bulk.shared::cluster.global.mbarrier::complete_tx::bytes.multicast::cluster [%0], [%1], %2, [%3], %4;"
               :: "r"(dst), "l"(src), "r"(bytes), "r"(bar), "h"(mask) : "memory");
}
__device__ __forceinline__ void bulk_s2s(uint32_t dst, uint32_t src, uint32_t bytes, uint32_t bar) {
  asm volatile("cp.async.bulk.shared::cluster.shared::cta.mbarrier::complete_tx::bytes [%0], [%1], %2, [%3];"
               :: "r"(dst), "r"(src), "r"(bytes), "r"(bar) : "memory");
}
__device__ __forceinline__ void bulk_s2g(void* dst, uint32_t src, uint32_t bytes) {
  asm volatile("cp.async.bulk.global.shared::cta.bulk_group [%0], [%1], %2;" :: "l"(dst), "r"(src), "r"(bytes) : "memory");
}
__device__ __forceinline__ void bulk_commit_wait() {
  asm volatile("cp.async.bulk.commit_group;\ncp.async.bulk.wait_group 0;" ::: "memory");
}
__device__ __forceinline__ bool elect_one() {
  uint32_t p; asm volatile("{\n.reg .pred p;\nelect.sync _|p, 0xffffffff;\nselp.u32 %0, 1, 0, p;\n}" : "=r"(p)); return p;
}
__device__ __forceinline__ void ldsm4(uint32_t& r0, uint32_t& r1, uint32_t& r2, uint32_t& r3, uint32_t a) {
  asm volatile("ldmatrix.sync.aligned.m8n8.x4.shared.b16 {%0,%1,%2,%3}, [%4];" : "=r"(r0), "=r"(r1), "=r"(r2), "=r"(r3) : "r"(a) : "memory");
}
__device__ __forceinline__ void ldsm4t(uint32_t& r0, uint32_t& r1, uint32_t& r2, uint32_t& r3, uint32_t a) {
  asm volatile("ldmatrix.sync.aligned.m8n8.x4.trans.shared.b16 {%0,%1,%2,%3}, [%4];" : "=r"(r0), "=r"(r1), "=r"(r2), "=r"(r3) : "r"(a) : "memory");
}
__device__ __forceinline__ void stsm4(uint32_t a, uint32_t r0, uint32_t r1, uint32_t r2, uint32_t r3) {
  asm volatile("stmatrix.sync.aligned.m8n8.x4.shared.b16 [%0], {%1,%2,%3,%4};" :: "r"(a), "r"(r0), "r"(r1), "r"(r2), "r"(r3) : "memory");
}
__device__ __forceinline__ void stsm2(uint32_t a, uint32_t r0, uint32_t r1) {
  asm volatile("stmatrix.sync.aligned.m8n8.x2.shared.b16 [%0], {%1,%2};" :: "r"(a), "r"(r0), "r"(r1) : "memory");
}
__device__ __forceinline__ void stsm4t(uint32_t a, uint32_t r0, uint32_t r1, uint32_t r2, uint32_t r3) {
  asm volatile("stmatrix.sync.aligned.m8n8.x4.trans.shared.b16 [%0], {%1,%2,%3,%4};" :: "r"(a), "r"(r0), "r"(r1), "r"(r2), "r"(r3) : "memory");
}
__device__ __forceinline__ float4 lds4f(uint32_t a) {
  float4 v; asm volatile("ld.shared.v4.f32 {%0,%1,%2,%3}, [%4];" : "=f"(v.x), "=f"(v.y), "=f"(v.z), "=f"(v.w) : "r"(a) : "memory"); return v;
}
__device__ __forceinline__ uint4 lds4(uint32_t a) {
  uint4 v; asm volatile("ld.shared.v4.u32 {%0,%1,%2,%3}, [%4];" : "=r"(v.x), "=r"(v.y), "=r"(v.z), "=r"(v.w) : "r"(a) : "memory"); return v;
}
__device__ __forceinline__ uint32_t lds1(uint32_t a) {
  uint32_t v; asm volatile("ld.shared.u32 %0, [%1];" : "=r"(v) : "r"(a) : "memory"); return v;
}
__device__ __forceinline__ void sts4(uint32_t a, uint4 v) {
  asm volatile("st.shared.v4.u32 [%0], {%1,%2,%3,%4};" :: "r"(a), "r"(v.x), "r"(v.y), "r"(v.z), "r"(v.w) : "memory");
}
__device__ __forceinline__ void sts1(uint32_t a, uint32_t v) { asm volatile("st.shared.u32 [%0], %1;" :: "r"(a), "r"(v) : "memory"); }
__device__ __forceinline__ void mma16816(float (&d)[4], uint32_t a0, uint32_t a1, uint32_t a2, uint32_t a3, uint32_t b0, uint32_t b1) {
  asm volatile("mma.sync.aligned.m16n8k16.row.col.f32.bf16.bf16.f32 {%0,%1,%2,%3}, {%4,%5,%6,%7}, {%8,%9}, {%0,%1,%2,%3};"
               : "+f"(d[0]), "+f"(d[1]), "+f"(d[2]), "+f"(d[3]) : "r"(a0), "r"(a1), "r"(a2), "r"(a3), "r"(b0), "r"(b1));
}
__device__ __forceinline__ void mma1688(float (&d)[4], uint32_t a0, uint32_t a1, uint32_t b0) {
  asm volatile("mma.sync.aligned.m16n8k8.row.col.f32.bf16.bf16.f32 {%0,%1,%2,%3}, {%4,%5}, {%6}, {%0,%1,%2,%3};"
               : "+f"(d[0]), "+f"(d[1]), "+f"(d[2]), "+f"(d[3]) : "r"(a0), "r"(a1), "r"(b0));
}
__device__ __forceinline__ float rcp(float x) { float r; asm("rcp.approx.ftz.f32 %0, %1;" : "=f"(r) : "f"(x)); return r; }
__device__ __forceinline__ float sqr(float x) { float r; asm("sqrt.approx.f32 %0, %1;" : "=f"(r) : "f"(x)); return r; }
__device__ __forceinline__ float ex2(float x) { float r; asm("ex2.approx.ftz.f32 %0, %1;" : "=f"(r) : "f"(x)); return r; }

__device__ __forceinline__ uint32_t bf2_op(uint32_t a, uint32_t b, uint32_t c) {
  uint32_t r; asm("fma.rn.bf16x2 %0, %1, %2, %3;" : "=r"(r) : "r"(a), "r"(b), "r"(c)); return r;
}
__device__ __forceinline__ uint32_t bf2_mul(uint32_t a, uint32_t b) {
  uint32_t r; asm("mul.rn.bf16x2 %0, %1, %2;" : "=r"(r) : "r"(a), "r"(b)); return r;
}
__device__ __forceinline__ uint32_t bf2_add(uint32_t a, uint32_t b) {
  uint32_t r; asm("add.rn.bf16x2 %0, %1, %2;" : "=r"(r) : "r"(a), "r"(b)); return r;
}

__host__ __device__ constexpr uint64_t mkdesc(uint32_t off, uint32_t lbo, uint32_t sbo, uint32_t sw) {
  return (uint64_t)((SB0 + off) >> 4) | ((uint64_t)(lbo >> 4) << 16) | ((uint64_t)(sbo >> 4) << 32) | ((uint64_t)sw << 62);
}
__device__ __forceinline__ void wg_fence() { asm volatile("wgmma.fence.sync.aligned;" ::: "memory"); }
__device__ __forceinline__ void wg_commit() { asm volatile("wgmma.commit_group.sync.aligned;" ::: "memory"); }
template <int N> __device__ __forceinline__ void wg_wait() { asm volatile("wgmma.wait_group.sync.aligned %0;" :: "n"(N) : "memory"); }
template <int N> __device__ __forceinline__ void reg_fence(float (&d)[N]) {
#pragma unroll
  for (int i = 0; i < N; i++) asm volatile("" : "+f"(d[i]) :: "memory");
}

#define F4(d, o) "+f"(d[o]), "+f"(d[o + 1]), "+f"(d[o + 2]), "+f"(d[o + 3])
template <int SC, int TB> __device__ __forceinline__ void wg_rs(float (&d)[8], const uint32_t* a, uint64_t db, int ob) {
  asm volatile("{\n.reg .pred p;\n.reg .b64 b;\nsetp.ne.b32 p, %13, 0;\nadd.s64 b, %12, %15;\n"
    "wgmma.mma_async.sync.aligned.m64n16k16.f32.bf16.bf16 {%0,%1,%2,%3,%4,%5,%6,%7}, {%8,%9,%10,%11}, b, p, 1, 1, %14;\n}\n"
    : F4(d, 0), F4(d, 4) : "r"(a[0]), "r"(a[1]), "r"(a[2]), "r"(a[3]), "l"(db), "n"(SC), "n"(TB), "l"((uint64_t)ob));
}
template <int SC, int TB> __device__ __forceinline__ void wg_rs(float (&d)[12], const uint32_t* a, uint64_t db, int ob) {
  asm volatile("{\n.reg .pred p;\n.reg .b64 b;\nsetp.ne.b32 p, %17, 0;\nadd.s64 b, %16, %19;\n"
    "wgmma.mma_async.sync.aligned.m64n24k16.f32.bf16.bf16 {%0,%1,%2,%3,%4,%5,%6,%7,%8,%9,%10,%11}, {%12,%13,%14,%15}, b, p, 1, 1, %18;\n}\n"
    : F4(d, 0), F4(d, 4), F4(d, 8) : "r"(a[0]), "r"(a[1]), "r"(a[2]), "r"(a[3]), "l"(db), "n"(SC), "n"(TB), "l"((uint64_t)ob));
}
template <int SC, int TB> __device__ __forceinline__ void wg_rs(float (&d)[16], const uint32_t* a, uint64_t db, int ob) {
  asm volatile("{\n.reg .pred p;\n.reg .b64 b;\nsetp.ne.b32 p, %21, 0;\nadd.s64 b, %20, %23;\n"
    "wgmma.mma_async.sync.aligned.m64n32k16.f32.bf16.bf16 {%0,%1,%2,%3,%4,%5,%6,%7,%8,%9,%10,%11,%12,%13,%14,%15}, {%16,%17,%18,%19}, b, p, 1, 1, %22;\n}\n"
    : F4(d, 0), F4(d, 4), F4(d, 8), F4(d, 12) : "r"(a[0]), "r"(a[1]), "r"(a[2]), "r"(a[3]), "l"(db), "n"(SC), "n"(TB), "l"((uint64_t)ob));
}
template <int SC, int TB> __device__ __forceinline__ void wg_rs(float (&d)[28], const uint32_t* a, uint64_t db, int ob) {
  asm volatile("{\n.reg .pred p;\n.reg .b64 b;\nsetp.ne.b32 p, %33, 0;\nadd.s64 b, %32, %35;\n"
    "wgmma.mma_async.sync.aligned.m64n56k16.f32.bf16.bf16 {%0,%1,%2,%3,%4,%5,%6,%7,%8,%9,%10,%11,%12,%13,%14,%15,%16,%17,%18,%19,%20,%21,%22,%23,%24,%25,%26,%27}, {%28,%29,%30,%31}, b, p, 1, 1, %34;\n}\n"
    : F4(d, 0), F4(d, 4), F4(d, 8), F4(d, 12), F4(d, 16), F4(d, 20), F4(d, 24) : "r"(a[0]), "r"(a[1]), "r"(a[2]), "r"(a[3]), "l"(db), "n"(SC), "n"(TB), "l"((uint64_t)ob));
}
template <int SC, int TB> __device__ __forceinline__ void wg_ss(float (&d)[8], uint64_t da, int oa, uint64_t db, int ob) {
  asm volatile("{\n.reg .pred p;\n.reg .b64 a, b;\nsetp.ne.b32 p, %10, 0;\nadd.s64 a, %8, %12;\nadd.s64 b, %9, %13;\n"
    "wgmma.mma_async.sync.aligned.m64n16k16.f32.bf16.bf16 {%0,%1,%2,%3,%4,%5,%6,%7}, a, b, p, 1, 1, 1, %11;\n}\n"
    : F4(d, 0), F4(d, 4) : "l"(da), "l"(db), "n"(SC), "n"(TB), "l"((uint64_t)oa), "l"((uint64_t)ob));
}
template <int SC, int TB> __device__ __forceinline__ void wg_ss(float (&d)[12], uint64_t da, int oa, uint64_t db, int ob) {
  asm volatile("{\n.reg .pred p;\n.reg .b64 a, b;\nsetp.ne.b32 p, %14, 0;\nadd.s64 a, %12, %16;\nadd.s64 b, %13, %17;\n"
    "wgmma.mma_async.sync.aligned.m64n24k16.f32.bf16.bf16 {%0,%1,%2,%3,%4,%5,%6,%7,%8,%9,%10,%11}, a, b, p, 1, 1, 1, %15;\n}\n"
    : F4(d, 0), F4(d, 4), F4(d, 8) : "l"(da), "l"(db), "n"(SC), "n"(TB), "l"((uint64_t)oa), "l"((uint64_t)ob));
}
template <int SC, int TB> __device__ __forceinline__ void wg_ss(float (&d)[16], uint64_t da, int oa, uint64_t db, int ob) {
  asm volatile("{\n.reg .pred p;\n.reg .b64 a, b;\nsetp.ne.b32 p, %18, 0;\nadd.s64 a, %16, %20;\nadd.s64 b, %17, %21;\n"
    "wgmma.mma_async.sync.aligned.m64n32k16.f32.bf16.bf16 {%0,%1,%2,%3,%4,%5,%6,%7,%8,%9,%10,%11,%12,%13,%14,%15}, a, b, p, 1, 1, 1, %19;\n}\n"
    : F4(d, 0), F4(d, 4), F4(d, 8), F4(d, 12) : "l"(da), "l"(db), "n"(SC), "n"(TB), "l"((uint64_t)oa), "l"((uint64_t)ob));
}
template <int SC, int TB> __device__ __forceinline__ void wg_ss(float (&d)[20], uint64_t da, int oa, uint64_t db, int ob) {
  asm volatile("{\n.reg .pred p;\n.reg .b64 a, b;\nsetp.ne.b32 p, %22, 0;\nadd.s64 a, %20, %24;\nadd.s64 b, %21, %25;\n"
    "wgmma.mma_async.sync.aligned.m64n40k16.f32.bf16.bf16 {%0,%1,%2,%3,%4,%5,%6,%7,%8,%9,%10,%11,%12,%13,%14,%15,%16,%17,%18,%19}, a, b, p, 1, 1, 1, %23;\n}\n"
    : F4(d, 0), F4(d, 4), F4(d, 8), F4(d, 12), F4(d, 16) : "l"(da), "l"(db), "n"(SC), "n"(TB), "l"((uint64_t)oa), "l"((uint64_t)ob));
}
template <int SC, int TB> __device__ __forceinline__ void wg_ss(float (&d)[28], uint64_t da, int oa, uint64_t db, int ob) {
  asm volatile("{\n.reg .pred p;\n.reg .b64 a, b;\nsetp.ne.b32 p, %30, 0;\nadd.s64 a, %28, %32;\nadd.s64 b, %29, %33;\n"
    "wgmma.mma_async.sync.aligned.m64n56k16.f32.bf16.bf16 {%0,%1,%2,%3,%4,%5,%6,%7,%8,%9,%10,%11,%12,%13,%14,%15,%16,%17,%18,%19,%20,%21,%22,%23,%24,%25,%26,%27}, a, b, p, 1, 1, 1, %31;\n}\n"
    : F4(d, 0), F4(d, 4), F4(d, 8), F4(d, 12), F4(d, 16), F4(d, 20), F4(d, 24) : "l"(da), "l"(db), "n"(SC), "n"(TB), "l"((uint64_t)oa), "l"((uint64_t)ob));
}

template <int SC> __device__ __forceinline__ void wg_sskk(float (&d)[16], uint64_t da, int oa, uint64_t db, int ob) {
  asm volatile("{\n.reg .pred p;\n.reg .b64 a, b;\nsetp.ne.b32 p, %18, 0;\nadd.s64 a, %16, %19;\nadd.s64 b, %17, %20;\n"
    "wgmma.mma_async.sync.aligned.m64n32k16.f32.bf16.bf16 {%0,%1,%2,%3,%4,%5,%6,%7,%8,%9,%10,%11,%12,%13,%14,%15}, a, b, p, 1, 1, 0, 0;\n}\n"
    : F4(d, 0), F4(d, 4), F4(d, 8), F4(d, 12) : "l"(da), "l"(db), "n"(SC), "l"((uint64_t)oa), "l"((uint64_t)ob));
}

template <int NB>
__device__ __forceinline__ void load_rows(uint32_t dst, const __nv_bfloat16* src, int pitch, int nrows, int tid, int nthr) {
  for (int i0 = tid; i0 < nrows * 8; i0 += nthr * NB) {
    uint4 v[NB];
#pragma unroll
    for (int u = 0; u < NB; u++) {
      const int i = i0 + u * nthr, r = i >> 3;
      if (i < nrows * 8) v[u] = __ldg((const uint4*)(src + (size_t)r * pitch + (i & 7) * 8));
    }
#pragma unroll
    for (int u = 0; u < NB; u++) {
      const int i = i0 + u * nthr, r = i >> 3;
      if (i < nrows * 8) sts4(dst + r * 128 + (((i & 7) ^ (r & 7)) << 4), v[u]);
    }
  }
}
template <int NK> __device__ __forceinline__ void load_afrags(uint32_t* a, uint32_t tile, int w, int lane) {
  int i = lane >> 3, r = lane & 7;
  uint32_t base = tile + ((i >> 1) * 8 + r) * 128 + (((2 * w + (i & 1)) ^ r) << 4);
#pragma unroll
  for (int kk = 0; kk < NK; kk++) ldsm4t(a[4 * kk], a[4 * kk + 1], a[4 * kk + 2], a[4 * kk + 3], base + kk * 2048);
}

constexpr uint32_t Q_WL = 0;
constexpr uint32_t Q_WO = 24576;
constexpr uint32_t Q_OX = Q_WO;
constexpr uint32_t Q_X = 73728;
constexpr uint32_t Q_CS = 10240;
constexpr uint32_t Q_STG = 165888;
constexpr uint32_t Q_OB = 190464;
constexpr uint32_t Q_SIN = 194560;
constexpr uint32_t Q_PX = 204800;
constexpr uint32_t Q_SOUT = Q_PX;
constexpr int Q_KR = 30;
constexpr uint32_t BARS = 228352;
constexpr uint32_t B_CP = BARS;
constexpr uint32_t B_OK = BARS + 408;
constexpr uint32_t B_G0 = BARS + 272;
constexpr uint32_t B_XF = BARS + 72;
constexpr uint32_t B_E = BARS + 224;
constexpr uint32_t B_SM = BARS + 160;
constexpr uint32_t B_O = BARS + 168;
constexpr uint32_t B_P = BARS + 176;
constexpr uint32_t B_OXREADY = BARS + 192;
constexpr uint32_t B_OXFREE = BARS + 200;
constexpr uint32_t B_REF = BARS + 208;
constexpr uint32_t B_AN = BARS + 264;
constexpr uint32_t B_PZ = BARS + 256;
constexpr uint32_t B_RES = BARS + 216;
constexpr uint32_t Q_REF = BARS + 288;
constexpr uint32_t Q_SEL = BARS + 304;
constexpr uint32_t Q_SET = BARS + 360;
constexpr uint32_t SM_BYTES = 4 * 1024, SX_BYTES = 2560, PX_BYTES = 2 * 14 * 128;
constexpr int W_KR = 29;
constexpr uint32_t W_RING = 0;
constexpr uint32_t W_WS = 196608;
constexpr uint32_t W_FT = 0;
constexpr uint32_t W_FO = 18688;
constexpr uint32_t W_Z = 30720;
constexpr uint32_t W_RS = 49152;
constexpr uint32_t W_ST = 28672;
constexpr int CT_A = 2, CT_B = 6, CT_C = 11;
static_assert(36 * CT_C <= 36 * CT_B + 192, "kv stages");
constexpr uint32_t C_U = 256 + 4096;
constexpr uint32_t C_CH = C_U + 64 + 8192 + 96;
constexpr uint32_t B_FULL = BARS;
constexpr uint32_t B_EMPTY = BARS + 128;
constexpr uint32_t B_FT = BARS + 160;
constexpr uint32_t B_RF = BARS + 176;
constexpr uint32_t W_K1 = BARS + 240;
constexpr uint32_t SMEM_TOTAL = BARS + 512;

struct Params {
  const __nv_bfloat16 *x0, *wq, *wk, *wv, *wo, *mem0, *ck, *cv, *shift, *ssm_k, *ssm_d;
  __nv_bfloat16* out;
  uint4 *part, *memx;
  uint64_t d_x, d_wl, d_ring, d_ws;
};

constexpr uint64_t D_QK = mkdesc(Q_STG, 768, 128, 0), D_WO = mkdesc(Q_WO, 16, 1024, 1), D_OB = mkdesc(Q_OB, 128, 2048, 0), D_PX = mkdesc(Q_PX, 128, 768, 0);
constexpr uint64_t D_V = mkdesc(Q_STG, 128, 768, 0);

#define g_flags (g_flagsets + lds1(sb + Q_SET))

__device__ __forceinline__ int rd_cid() { uint32_t v; asm volatile("mov.u32 %0, %%clusterid.x;" : "=r"(v)); return v; }
__device__ __forceinline__ int rd_rank() { uint32_t v; asm volatile("mov.u32 %0, %%cluster_ctarank;" : "=r"(v)); return v; }
__device__ __forceinline__ int rd_lane() { uint32_t v; asm volatile("mov.u32 %0, %%laneid;" : "=r"(v)); return v; }
__device__ __forceinline__ int rd_warp() { uint32_t v; asm volatile("mov.u32 %0, %%tid.x;" : "=r"(v)); return __shfl_sync(0xffffffffu, v >> 5, 0); }

template <int NA>
__device__ __forceinline__ void proj_step(float (&acc)[NA], const uint32_t* a, uint64_t db, uint64_t dwl, int k) {
  const int ob = (k >> 2) * (Q_CS / 16) + (k & 3) * 16;
  if (k == 0) wg_rs<0, 1>(acc, a, db, ob);
  else if (k % 6 != 5) wg_rs<1, 1>(acc, a + 4 * (k - k / 6), db, ob);
  else wg_ss<1, 1>(acc, dwl, 128 * (k / 6), db, ob);
}
__device__ __forceinline__ void stage_groups(uint32_t stl, const uint32_t (&pk)[14]) {
#pragma unroll
  for (int h = 0; h < 2; h++) {
    stsm4(stl + h * 768 + 256, pk[h], pk[2 + h], pk[4 + h], 0);
    stsm4(stl + h * 768 + 6144 + 128, pk[6 + h], pk[8 + h], pk[10 + h], pk[12 + h]);
  }
}
__device__ __forceinline__ void head_main(uint32_t sb, const Params& P) {
  const int lane = threadIdx.x & 31, warp = rd_warp(), w = warp & 3, wg = warp >> 2, rank = rd_rank();
  uint32_t a[4 * Q_KR];
  {
    const int tid = threadIdx.x & 127;
    const __nv_bfloat16* src = (rank == 2 ? P.wv + wg * 64 : (wg ? P.wk : P.wq) + rank * 64) + rd_cid() * 128 + (size_t)(tid >> 3) * 4096 + (tid & 7) * 8;
    const uint32_t so = (tid >> 3) * 128 + (((tid & 7) ^ ((tid >> 3) & 7)) << 4), st = sb + Q_X + wg * (Q_KR * 2048);
    uint4 v[36];
#pragma unroll
    for (int k = 0; k < 36; k++) v[k] = __ldg((const uint4*)(src + (size_t)k * 65536));
#pragma unroll
    for (int k = 0; k < 36; k++) sts4(so + (k % 6 == 5 ? sb + Q_WL + wg * 12288 + (k / 6) * 2048 : st + (k - k / 6) * 2048), v[k]);
    bar_sync_r(9 + wg, 128);
    PROF_G(7);
    load_afrags<Q_KR>(a, st, w, lane);
    fence_async_smem();
    bar_arrive<11, 384>();
  }
  cluster_sync();
  PROF_G(8);
  const uint64_t dwl = P.d_wl + wg * 768, dq = D_QK + wg * 384;
  const uint32_t stg = sb + Q_STG + wg * 12288 + 2 * w * 768;
  const uint32_t stm = pin(stg + (lane >> 4) * 6144 + ((lane >> 3) & 1) * 768 + (lane & 7) * 16), stl = pin(stg + lane * 16);
  const uint32_t rel = mapa(sb + B_E, 0), rev = mapa(sb + B_E, 2), sel = pin(threadIdx.x & 127), arm = pin(threadIdx.x - 128 > 8), xfa = pin(sb + B_XF + 8 * lane);
  const uint32_t sx = sb + (wg == rank ? Q_SIN + rank * 4096 : Q_SOUT + 2048), s0 = w ? sx + (2 * w - 1) * 512 : sb + Q_SOUT + wg * 1024, s1 = sx + 2 * w * 512;
  const uint32_t sd0 = pin(s0 + lane * 16), sd1 = pin(s1 + lane * 16), sr = sb + Q_SIN + rank * 4096;
  const int kp = rank == 2 ? KP_V : rank ? KP_1 : KP_0;
  const uint32_t selq = pin(sel | rank >> 1);
    const uint32_t pz = sb + (rank == 2 ? B_SM : B_PZ);
  uint32_t pk[14] = {};
#pragma unroll 1
  for (int t = 0;; t++) {
    const uint32_t par = t & 1;
    uint32_t paused = 0;
    if (t == 0) {
      mbar_wait(sb + B_XF, 0);
    } else {
      float m[12];
#pragma unroll
      for (int c = 0; c < 9; c++) {
        mbar_spin(sb + B_OK + 8 * c, par ^ 1);
        if (c == 0 || c == 3 || c == 8) PROF_W(warp == 0, c == 0 ? 0 : c == 3 ? 1 : 3);
        if (c == 8) mbar_rarrive_if0(selq, rev + 24);
        wg_fence();
#pragma unroll
        for (int k = 4 * c; k < 4 * c + 4; k++) proj_step(m, a, P.d_x, dwl, k);
        if (c == 0) { mbar_expect_if0(arm, xfa, 7168); mbar_rarrive_if0(sel | (rank ^ 2), rel); }
        if (c == XA_V) mbar_rarrive_if0(selq, rel);
        if (c == 3) mbar_rarrive_if0(sel, rev);
        if (c == ST_V && rank == 2) {
          if (t > 1) bar_sync<3, 384>();
          stage_groups(stl, pk);
        }
      }
      wg_commit();
      if (rank == 2 && t < NT) { mbar_wait(sb + B_XF, par); paused = mbar_test(pz, par ^ 1); }
      wg_wait<0>();
      reg_fence(m);
      PROF_W(warp == 0, 2);
      stsm4(stm, pack_bf16(m[0], m[1]), pack_bf16(m[2], m[3]), pack_bf16(m[4], m[5]), pack_bf16(m[6], m[7]));
      stsm2(stm + 128, pack_bf16(m[8], m[9]), pack_bf16(m[10], m[11]));
      if (rank == 2) {
        bar_arrive<1, 384>();
        if (t == NT) break;
        if (paused) mbar_wait(sb + B_RES, par ^ 1);
      } else {
        float s[20];
        bar_sync<1, 256>();
        fence_async_smem();
        wg_fence();
        wg_ss<0, 1>(s, dq, 0, dq, 768);
#pragma unroll
        for (int i = 1; i < 4; i++) wg_ss<1, 1>(s, dq, 96 * i, dq, 768 + 96 * i);
        wg_commit();
        if (t < NT) mbar_wait(sb + B_XF, par);
        wg_wait<0>();
        reg_fence(s);
        if (w < 3) {
          sts4(sd0, make_uint4(pack_bf16(s[0], s[1]), pack_bf16(s[4], s[5]), pack_bf16(s[8], s[9]), pack_bf16(s[12], s[13])));
          if (w != 1) sts1(sd0 + 512, pack_bf16(s[16], s[17]));
          if (w == 0) {
            fence_async_smem();
            __syncwarp();
            if (elect_one()) bulk_s2s(mapa(sr + wg * 1024, 2), s0, 1024, mapa(sb + B_SM, 2));
            __syncwarp();
            PROF_W(wg == 1, 4); PROF_W(wg == 0, 8);
          }
          if (w < 2) sts4(sd1, make_uint4(pack_bf16(s[2], s[3]), pack_bf16(s[6], s[7]), pack_bf16(s[10], s[11]), pack_bf16(s[14], s[15])));
          bar_arrive<8, 224>();
        }
        if (t == NT) break;
      }
    }
    float e[28];
#pragma unroll
    for (int k = 0; k < 36; k++) {
      if (k == 2 && t > 0) {
        mbar_rarrive_if0(sel, rel + 16);
        mbar_expect_if0(arm, xfa - (B_XF - B_CP), 2048);
        mbar_expect_if0(sel | wg, sb + B_G0, 9216);
      }
      if (k % 4 == 0 && k) mbar_wait(sb + B_XF + 2 * k, par);
      if (k == 0) PROF_W(warp == 0, 5);
      if (k % 2 == 0 && k && k <= KP_MAX) {
        mbar_wait_if(paused, pz, sb + B_RES, par ^ 1, k == kp);
      }
      if (k % 4 == 0 || (k % 2 == 0 && k <= KP_MAX)) wg_fence();
      proj_step(e, a, P.d_x + 192, dwl, k);
    }
    wg_commit();
    mbar_wait(sb + B_G0, par);
    wg_wait<0>();
    reg_fence(e);
    PROF_W(warp == 0, 10);
#pragma unroll
    for (int i = 0; i < 14; i++) pk[i] = pack_bf16(e[2 * i], e[2 * i + 1]);
    if (rank != 2) stage_groups(stl, pk);
    PROF_W(warp == 0, 12);
  }
  cluster_sync();
}

__device__ __forceinline__ uint32_t next_tick() {
  uint64_t g0, g1;
  asm volatile("mov.u64 %0, %%globaltimer;" : "=l"(g0) :: "memory");
#pragma unroll 1
  for (int n = 0; n < 8; n++) {
    asm volatile("mov.u64 %0, %%globaltimer;" : "=l"(g1) :: "memory");
    if (__any_sync(0xffffffffu, (uint32_t)g1 != (uint32_t)g0)) break;
  }
  return (uint32_t)g1;
}
__device__ __forceinline__ void wait_ns(uint32_t when) {
  uint32_t c;
  asm volatile("{\n.reg .pred p;\n.reg .b64 g;\n.reg .s32 lo;\nS_%=:\nmov.u64 g, %%globaltimer;\ncvt.u32.u64 lo, g;\nsub.s32 lo, %1, lo;\n"
               "setp.gt.s32 p, lo, 31;\n@p bra.uni S_%=;\nmov.u64 g, %%clock64;\ncvt.u32.u64 %0, g;\nshl.b32 lo, lo, 1;\nadd.s32 %0, %0, lo;\n}" : "=&r"(c) : "r"(when) : "memory");
  spin_until(c - 30);
}
template <bool TAG>
__device__ __forceinline__ uint32_t poll4(uint4 (&v)[4], const uint4* src, uint32_t tag) {
#pragma unroll
  for (int j = 0; j < 4; j++) v[j] = ld_poll(src + j * 32);
  uint32_t n = 0;
  while (__any_sync(0xffffffffu, TAG ? (((v[0].x ^ tag) | (v[1].x ^ tag) | (v[2].x ^ tag) | (v[3].x ^ tag)) & 1) != 0
                                     : (v[0].x == SENT || v[1].x == SENT || v[2].x == SENT || v[3].x == SENT))) {
#pragma unroll
    for (int j = 0; j < 4; j++) if (TAG ? ((v[j].x ^ tag) & 1) != 0 : v[j].x == SENT) v[j] = ld_poll(src + j * 32);
    if (++n > SPIN_LIMIT) __trap();
  }
  return n;
}

template <int STEP>
__device__ __forceinline__ void check_tiles(uint32_t sb, const Params& P, int w, int t) {
  const int lane = rd_lane();
  uint32_t chk = sb + Q_X + w * Q_CS + lane * 32 + (lane >> 2) * 4, bad = 0;
#pragma unroll 1
  for (uint32_t bar = sb + B_CP + 8 * w; bar <= sb + B_CP + 64; bar += 8 * STEP, chk += STEP * Q_CS) {
    uint32_t ok;
    asm volatile("{\n.reg .pred p, q;\n.reg .b32 a, b;\nsetp.eq.u32 q, %4, 0;\n"
                 "W_%=:\nmbarrier.try_wait.parity.shared::cta.b64 p, [%1], %2" CHINT ";\n@!p bra W_%=;\n"
                 "ld.shared.u32 a, [%3];\nld.shared.u32 b, [%3 + 1024];\nsetp.ne.u32 p, a, 0x80008000;\nsetp.ne.and.u32 p, b, 0x80008000, p;\n"
                 "vote.sync.all.pred p, p, 0xFFFFFFFF;\nand.pred q, q, p;\n@q mbarrier.arrive.shared::cta.b64 _, [%1 + %5];\nselp.u32 %0, 1, 0, p;\n}"
                 : "=r"(ok) : "r"(bar), "r"(~t & 1), "r"(chk), "r"(lane), "n"(B_OK - B_CP) : "memory");
    const int c = (bar - sb - B_CP) / 8;
    if (!ok) {
      uint4 v[4];
      poll4<false>(v, P.memx + c * 512 + (t & 1) * 128 + lds1(sb + Q_SEL + 4 * c) / 16 + lane, 0);
#pragma unroll
      for (int j = 0; j < 4; j++) sts4(sb + Q_X + c * Q_CS + j * 512 + lane * 16, v[j]);
      fence_async_smem();
      __syncwarp();
      mbar_arrive_if0(lane, bar + B_OK - B_CP);
      if (t > LAG + 4) sts1(sb + Q_REF + 4, lds1(sb + Q_REF + 4) + 1);
      PROF_OR(7, 1 << c);
      PROF_A(c, 1);
      bad |= c < 6;
    }
    if (STEP == 3) mbar_arrive_if0(lane | (c / 3 != 1 + bad), sb + B_E + 24);
  }
}
__device__ __forceinline__ void load_scores(float (&s)[10], uint32_t sa) {
  const uint4 a = lds4(sa), b = lds4(sa + 4096);
  const uint32_t a4 = lds1(sa + 512), b4 = lds1(sa + 4608);
  s[0] = bf_lo(a.x) + bf_lo(b.x); s[1] = bf_hi(a.x) + bf_hi(b.x); s[2] = bf_lo(a.y) + bf_lo(b.y); s[3] = bf_hi(a.y) + bf_hi(b.y);
  s[4] = bf_lo(a.z) + bf_lo(b.z); s[5] = bf_hi(a.z) + bf_hi(b.z); s[6] = bf_lo(a.w) + bf_lo(b.w); s[7] = bf_hi(a.w) + bf_hi(b.w);
  s[8] = bf_lo(a4) + bf_lo(b4); s[9] = bf_hi(a4) + bf_hi(b4);
}
__device__ __forceinline__ void softmax_num(float (&s)[10]) {
  float mx = fmaxf(fmaxf(fmaxf(s[0], s[1]), fmaxf(s[2], s[3])), fmaxf(fmaxf(s[4], s[5]), fmaxf(s[6], s[7])));
  mx = fmaxf(mx, fmaxf(s[8], s[9]));
  const float m1 = __shfl_xor_sync(0xffffffffu, mx, 1), m2 = __shfl_xor_sync(0xffffffffu, mx, 2), m3 = __shfl_xor_sync(0xffffffffu, mx, 3);
  mx = fmaxf(fmaxf(mx, m1), fmaxf(m2, m3));
  mx *= -SM_SCALE;
#pragma unroll
  for (int i = 0; i < 10; i++) s[i] = ex2(fmaf(s[i], SM_SCALE, mx));
}

__device__ __forceinline__ void wo_tiles(uint32_t sb, const uint32_t (&f)[76], char* d0, uint32_t pg, uint32_t rs, int t) {
  float d[2][8];
  auto mma = [&](int i, int k0, int k1) {
#pragma unroll
    for (int k = k0; k < k1; k++) {
      if (i == 2 && ((k & 1) || k == 6)) wg_ss<1, 0>(d[0], D_WO, 2048 + 128 * k, D_OB, 16 * k);
      else if (k == 0) wg_rs<0, 0>(d[i & 1], f + 32 * i, D_OB, 0);
      else wg_rs<1, 0>(d[i & 1], f + (i < 2 ? 32 * i + 4 * k : 64 + 2 * k), D_OB, 16 * k);
    }
    wg_commit();
  };
  auto put = [&](float (&q)[8]) {
    reg_fence(q);
    st_gpu4((uint4*)d0, (pack_bf16(q[0], q[1]) & ~1u) | ((t - 1) >> 1 & 1), pack_bf16(q[4], q[5]), pack_bf16(q[2], q[3]), pack_bf16(q[6], q[7]));
    __syncwarp();
  };
  wg_fence();
  mma(0, 0, 8);
  mma(1, 0, 8);
  wg_wait<1>();
  put(d[0]);
  PROF_W(threadIdx.x < 288, 14);
  wg_fence();
  mma(2, 0, RS_V);
  d0 += pg & 0xFFFF;
  wg_wait<1>();
  put(d[1]);
  PROF_W(threadIdx.x < 288, 15);
  mma(2, RS_V, 8);
  d0 += pg >> 16;
  wg_wait<1>();
  mbar_arrive_if0(rs, sb + B_RES);
  PROF_W(threadIdx.x < 288, 17);
  wg_wait<0>();
  put(d[0]);
  PROF_W(threadIdx.x < 288, 16);
}
__device__ __forceinline__ void head_aux(uint32_t sb, const Params& P) {
  const int tid = threadIdx.x & 127, w = rd_warp() & 3, rank = rd_rank(), head = __shfl_sync(0xffffffffu, rd_cid(), 0);
#pragma unroll 1
  for (int i = 0; i < 3; i++) {
    uint4 a[4], b[4];
#pragma unroll
    for (int u = 0; u < 4; u++) {
      const int r = u * 32 + (tid >> 2);
      const uint4* src = (const uint4*)(P.wo + (size_t)(head * 128 + (r & 64) + (r & 7) * 8 + ((r >> 3) & 7)) * DM + tile_of(rank, i) * 64) + (tid & 3) * 2;
      a[u] = __ldg(src); b[u] = __ldg(src + 1);
    }
#pragma unroll
    for (int u = 0; u < 4; u++) {
      const int r = u * 32 + (tid >> 2);
      const uint32_t dst = sb + Q_WO + i * 16384 + r * 128 + ((((tid & 3) * 2) ^ (r & 7) ^ ((head >> 2) & 1)) << 4);
      sts4(dst, make_uint4(__byte_perm(a[u].x, a[u].y, 0x5410), __byte_perm(a[u].z, a[u].w, 0x5410), __byte_perm(b[u].x, b[u].y, 0x5410), __byte_perm(b[u].z, b[u].w, 0x5410)));
      sts4(dst ^ 16, make_uint4(__byte_perm(a[u].x, a[u].y, 0x7632), __byte_perm(a[u].z, a[u].w, 0x7632), __byte_perm(b[u].x, b[u].y, 0x7632), __byte_perm(b[u].z, b[u].w, 0x7632)));
    }
  }
#pragma unroll
  for (int i = 0; i < 6; i++) sts4(sb + Q_PX + (i * 128 + tid) * 16, make_uint4(0, 0, 0, 0));
  char* pd;
  uint32_t pg;
  {
    const int lane = tid & 31, dcta = (w * 8 + (lane >> 2)) * 3 + rank;
    uint4 f;
    uint32_t n = 0;
    do {
      f = ld_poll((const uint4*)(g_flags + FL_SEL) + dcta);
      if (++n > SPIN_LIMIT) __trap();
    } while (__any_sync(0xffffffffu, !f.x || !f.y || !f.z));
    pd = (char*)P.part + (dcta * 1536 + head * 4 + (lane & 3) + (f.x - 1) * 256) * 16;
    pg = (8192 + (f.y - f.x) * 4096) | (8192 + (f.z - f.y) * 4096) << 16;
  }
  bar_sync<11, 384>();
#pragma unroll 1
  for (int k = tid; k < DM; k += 128) {
    uint32_t q[4];
#pragma unroll
    for (int j = 0; j < 4; j++) q[j] = bf2_add(__bfloat16_as_ushort(P.mem0[2 * j * DM + k]) | (uint32_t)__bfloat16_as_ushort(P.mem0[(2 * j + 1) * DM + k]) << 16, 0);
    sts4(sb + Q_X + (k >> 6) * Q_CS + (k & 63) * 16, make_uint4(q[0], q[1], q[2], q[3]));
    sts4(sb + Q_X + (k >> 6) * Q_CS + (k & 63) * 16 + 1024, make_uint4(q[0], q[1], q[2], q[3]));
  }
#pragma unroll
  for (int i = 0; i < 2; i++) sts4(sb + Q_STG + (i * 16 + (tid >> 3)) * 768 + 640 + (tid & 7) * 16, make_uint4(0, 0, 0, 0));
  fence_async_smem();
  PROF_G(2);
  const uint32_t wa = pin(sb + Q_WO + ((tid >> 4 & 1) * 8 + (tid & 7)) * 128 + (((2 * w + ((tid >> 3) & 1)) ^ (tid & 7)) << 4));
  uint32_t f[76];
  if (rank != 2) {
#pragma unroll
    for (int k = 0; k < 19; k++) ldsm4t(f[4 * k], f[4 * k + 1], f[4 * k + 2], f[4 * k + 3], wa + (k < 16 ? k : 2 * k - 16) * 2048);
    const uint32_t rs = pin(tid);
    cluster_sync();
#pragma unroll 1
    for (int t = 1;; t++) {
      pd = (char*)((uintptr_t)pd ^ 2048);
      check_tiles<4>(sb, P, w, t);
      if (w == 0) {
        bar_sync<8, 224>();
        fence_async_smem();
        if (elect_one()) {
          bulk_s2s(mapa(sb + Q_SIN + rank * 4096, rank ^ 1), sb + Q_SOUT + 2048, SX_BYTES, mapa(sb + B_SM, rank ^ 1));
          mbar_arrive(sb + B_SM);
        }
        __syncwarp();
      }
      if (t == NT) break;
      if (w == 1) {
        mbar_wait(sb + B_AN, (t - 1) & 1);
        spin_until(rd_clock() + (rank ? PA1_V : PA0_V));
        mbar_arrive_if0(rs - 32, sb + B_PZ);
      }
      mbar_spin(sb + B_O, (t - 1) & 1);
      PROF_W(w == 0, 13);
      wo_tiles(sb, f, pd, pg, rs, t);
      mbar_expect_if0(rs, sb + B_O, 4096);
    }
  } else {
#pragma unroll
    for (int k = 0; k < 8; k++) ldsm4t(f[4 * k], f[4 * k + 1], f[4 * k + 2], f[4 * k + 3], wa + k * 2048);
    cluster_sync();
    const int l = w & 1, tile = w >> 1;
    const uint32_t ob = pin(sb + Q_OB + (l ^ ((head >> 1) & 1)) * 2048 + tile * 1024 + (tid >> 2 & 7) * 128 + (tid & 3) * 16);
    const uint32_t ob0 = sb + Q_OB + ((head >> 1) & 1) * 2048;
    const uint32_t sa = pin(sb + Q_SIN + l * 1024 + (tid & 31) * 16);
#pragma unroll 1
    for (int t = 1; t <= NT; t++) {
      const uint32_t par = (t - 1) & 1;
      {
        uint32_t vf[4][10], p[5];
        float s[10], o[4][4];
        const int lane = rd_lane();
        const uint32_t vb = sb + Q_STG + tile * 12288 + l * 6144 + (lane & 7) * 16;
        const uint32_t ax = vb + ((lane >> 3) & 1) * 768 + (lane >> 4) * 128;
        pd = (char*)((uintptr_t)pd ^ 2048);
        bar_sync<1, 384>();
#pragma unroll
        for (int i = 0; i < 4; i++) ldsm4(vf[i][4], vf[i][5], vf[i][6], vf[i][7], ax + i * 1536 + 256);
        ldsm4(vf[0][8], vf[0][9], vf[1][8], vf[1][9], vb + (lane >> 3) * 768 + 512);
        ldsm4(vf[2][8], vf[2][9], vf[3][8], vf[3][9], vb + (lane >> 3) * 768 + 512 + 3072);
#pragma unroll
        for (int i = 0; i < 4; i++) ldsm4(vf[i][0], vf[i][1], vf[i][2], vf[i][3], ax + i * 1536);
        mbar_spin(sb + B_SM, par);
        PROF_W(w == 0, 20);
        if (t < NT) {
          load_scores(s, sa);
          __syncwarp();
          softmax_num(s);
#pragma unroll
          for (int j = 0; j < 5; j++) p[j] = pack_bf16(s[2 * j], s[2 * j + 1]);
          __syncwarp();
          PROF_W(w == 0, 9);
          float z[4] = {0.f, 0.f, 0.f, 0.f};
          const uint32_t ONE = 0x3F803F80u;
          mma16816(z, ONE, ONE, ONE, ONE, p[0], p[1]);
#pragma unroll
          for (int i = 0; i < 4; i++) { o[i][0] = o[i][1] = o[i][2] = o[i][3] = 0.f; mma16816(o[i], vf[i][0], vf[i][1], vf[i][2], vf[i][3], p[0], p[1]); }
#pragma unroll
          for (int k = 8; k < 12; k++) ldsm4t(f[4 * k], f[4 * k + 1], f[4 * k + 2], f[4 * k + 3], wa + k * 2048);
          mma16816(z, ONE, ONE, ONE, ONE, p[2], p[3]);
#pragma unroll
          for (int i = 0; i < 4; i++) mma16816(o[i], vf[i][4], vf[i][5], vf[i][6], vf[i][7], p[2], p[3]);
#pragma unroll
          for (int k = 12; k < 16; k++) ldsm4t(f[4 * k], f[4 * k + 1], f[4 * k + 2], f[4 * k + 3], wa + k * 2048);
          mma1688(z, ONE, ONE, p[4]);
#pragma unroll
          for (int i = 0; i < 4; i++) mma1688(o[i], vf[i][8], vf[i][9], p[4]);
#pragma unroll
          for (int k = 16; k < 19; k++) ldsm4t(f[4 * k], f[4 * k + 1], f[4 * k + 2], f[4 * k + 3], wa + (2 * k - 16) * 2048);
          const float r0 = rcp(z[0]), r1 = rcp(z[1]);
          const uint4 u0 = make_uint4(pack_bf16(o[0][0] * r0, o[0][2] * r0), pack_bf16(o[1][0] * r0, o[1][2] * r0),
                                      pack_bf16(o[2][0] * r0, o[2][2] * r0), pack_bf16(o[3][0] * r0, o[3][2] * r0));
          const uint4 u1 = make_uint4(pack_bf16(o[0][1] * r1, o[0][3] * r1), pack_bf16(o[1][1] * r1, o[1][3] * r1),
                                      pack_bf16(o[2][1] * r1, o[2][3] * r1), pack_bf16(o[3][1] * r1, o[3][3] * r1));
          PROF_W(w == 0, 8);
          sts4(ob, u0);
          sts4(ob + 64, u1);
          bar_sync<5, 160>();
          fence_async_smem();
          PROF_W(w == 0, 13);
          wo_tiles(sb, f, pd, pg, ob ^ ob0, t);
        }
      }
      const int lane = rd_lane();
      mbar_expect_if0(lane | w, sb + B_SM, SM_BYTES);
      if (t < NT) bar_sync<12, 160>();
      {
        float o[3][16];
        const uint32_t ox = sb + Q_OX + 2 * w * 512 + lane * 16;
        const uint64_t dp = D_PX + (t & 1) * 384;
        fence_async_smem();
        mbar_wait(sb + B_P + 8 * (t & 1), ((t - 1) >> 1) & 1);
        PROF_W(w == 0, 7);
#pragma unroll
        for (int j = 0; j < 7; j++) {
          if (j >= 3) {
            const int i = j - 3;
            if (i == 0) mbar_wait(sb + B_OXFREE, par ^ 1);
            if (i < 2) wg_wait<2>(); else if (i == 2) wg_wait<0>();
            if (i == 2 && t < NT) bar_arrive<3, 384>();
            reg_fence(o[i % 3]);
#pragma unroll
            for (int h = 0; h < 2; h++)
              stsm4(ox + i * 4096 + h * 512, pack_bf16(o[i % 3][2 * h], o[i % 3][2 * h + 1]), pack_bf16(o[i % 3][4 + 2 * h], o[i % 3][5 + 2 * h]),
                    pack_bf16(o[i % 3][8 + 2 * h], o[i % 3][9 + 2 * h]), pack_bf16(o[i % 3][12 + 2 * h], o[i % 3][13 + 2 * h]));
          }
          if (j < 4) {
            if (j % 3 == 0) wg_fence();
            wg_sskk<0>(o[j % 3], D_V, (j >> 1) * 384 + (j & 1) * 768, dp, (j >> 1) * 192);
            wg_sskk<1>(o[j % 3], D_V, (j >> 1) * 384 + (j & 1) * 768 + 16, dp, (j >> 1) * 192 + 16);
            wg_sskk<1>(o[j % 3], D_V, (j >> 1) * 384 + (j & 1) * 768 + 32, dp, (j >> 1) * 192 + 32);
            wg_commit();
          }
        }
        mbar_expect_if0(lane | w, sb + B_P + 8 * (t & 1), PX_BYTES);
      }
      fence_async_smem();
      __syncwarp();
      mbar_arrive_if0(lane, sb + B_OXREADY);
      PROF_W(w == 0, 23);
    }
  }
  cluster_sync();
}

__device__ __forceinline__ void softmax_x(uint32_t sb, int w, int rank, int t) {
  float s[10];
  const int lane = rd_lane();
  mbar_wait(sb + B_SM, (t - 1) & 1);
  PROF_W(w == 3, 20);
  load_scores(s, sb + Q_SIN + w * 512 + lane * 16);
  const int last = 8 + 8 * w + (lane >> 2) - 2 * (lane & 3);
#pragma unroll
  for (int i = 2; i < 10; i++) s[i] = (8 * (i >> 1) + (i & 1) <= last) ? s[i] : -INFINITY;
  softmax_num(s);
  float sum = ((s[0] + s[1]) + (s[2] + s[3])) + ((s[4] + s[5]) + (s[6] + s[7])) + (s[8] + s[9]);
  sum += __shfl_xor_sync(0xffffffffu, sum, 1);
  sum += __shfl_xor_sync(0xffffffffu, sum, 2);
  const float r = rcp(sum);
  const uint32_t po = sb + Q_SOUT + 6144 + w * 768;
#pragma unroll
  for (int j = 0; j < 5; j++) sts1(po + lane * 4 + j * 128, pack_bf16(s[2 * j] * r, s[2 * j + 1] * r));
  fence_async_smem();
  __syncwarp();
  if (elect_one()) bulk_s2s(mapa(sb + Q_PX + ((t & 1) * 2 + rank) * 3072 + w * 768, 2), po, 128 * (w + 2), mapa(sb + B_P + 8 * (t & 1), 2));
  __syncwarp();
  PROF_W(w == 3, 22);
}

__device__ __forceinline__ void head_service(uint32_t sb, const Params& P) {
  const int lane = threadIdx.x & 31, rank = rd_rank(), w = rd_warp() & 3, i3 = w - 1;
  const int head = rd_cid(), c = tile_of(rank, i3);
  uint32_t dof = c * 8192 + (lane & 4) * 1024 + (lane & 8) * 128 + head * 32 + (lane & 16) + (lane & 3) * 4;
  uint32_t sof = (blockIdx.x * 3 + i3) * 8192, gof = 0, dly = tile_delay(rank, i3), g0 = 0, c0 = 0, ref = 0;
  if (w) {
    sof += __shfl_sync(0xffffffffu, lds1(sb + Q_SEL + 36 + 4 * i3), 0);
    gof = c * 8192 + __shfl_sync(0xffffffffu, lds1(sb + Q_SEL + 4 * c), 0);
#pragma unroll 1
    for (int j = 0; j < 8; j++) st_gpu4((uint4*)((char*)P.part + sof) + j * 32 + lane, 1, 1, 1, 1);
    st_gpu1((uint32_t*)((char*)P.memx + dof), SENT);
    st_gpu1((uint32_t*)((char*)P.memx + dof + 2048), SENT);
    __syncwarp();
    asm volatile("st.release.gpu.global.u32 [%0], %1;" :: "l"(g_flags + FL_SEL + blockIdx.x * 4 + i3), "r"(((sof >> 12) & 1) + 1) : "memory");
  }
  cluster_sync();
#pragma unroll 1
  for (int t = 0; t <= NT; t++) {
    if (w == 0 && rank == 0 && t < NT) {
      const uint32_t* fl = g_flags + FL_XS + t * 32;
      warp_flag_wait(fl + (lane & 1 ? (t >= LAG ? 16 : 0) : (t <= NSEG ? 0 : 16)), 4);
      fence_async_global();
      const char* src = (const char*)g_xs + (size_t)t * 73728;
      if (t > 0) mbar_wait(sb + B_E, (t - 1) & 1);
      PROF_T(24);
      uint32_t at = rd_clock();
#pragma unroll 1
      for (int k = 0; k < 9; k++) {
        if (elect_one()) bulk_g2s_mc(sb + Q_X + 3072 + k * Q_CS, src + 1024 + k * 8192, 7168, sb + B_XF + 8 * k, 7);
        __syncwarp();
        at += XP_V;
        spin_until(at);
      }
      if (t == 0) PROF_G(31);
    }
    if (t > 0) {
    if (rank == 2 && w) check_tiles<3>(sb, P, w - 1, t);
    if (w == (rank == 2) && t < NT) {
      const uint32_t* tms = (const uint32_t*)(P.memx + 9 * 512 + lds1(sb + Q_SEL + 48) / 16 + (head >> 4) * 32 + lane) + rank;
      const uint32_t due = ref + D_GX + (D_DUE - rank_delay(rank)) * 9 / 16;
      if (rank == 2) {
        const uint32_t g1 = next_tick(), c1 = rd_clock();
        const uint32_t rate = t > 1 ? __float2uint_rn(65536.f * (g1 - g0) * rcp(c1 - c0)) : 36400;
        g0 = g1; c0 = c1;
        uint4* pub = P.memx + 9 * 512 + (lane & 1) * 256 + (lane & 2) * 16 + head;
        const uint32_t lead = D_RED * rate >> 16, late = D_LATE * rate >> 16, r1 = rank_delay(1) * rate >> 10, r0 = rank_delay(0) * rate >> 10;
        mbar_wait(sb + B_E, (t - 1) & 1);
        PROF_T(4);
        mbar_spin(sb + B_E + 24, (t - 1) & 1);
        uint32_t now = g0 + ((rd_clock() - c0) * rate >> 16);
        now = (now + (t < 3 ? lead + ST0_V : (int)(now + 90 - due) > 0 ? late : lead)) << 6;
        st_gpu4(pub, ((now + r0) & ~255u) | t, ((now + r1) & ~255u) | t, (now & ~255u) | t, 0);
        PROF_T(22);
        PROF_V(true, 1, now >> 6);
      } else {
        mbar_wait(sb + B_CP + 64, (t - 1) & 1);
      }
      if (t > 1) wait_ns(due); else ref = next_tick();
      uint32_t d, n = 0;
      do {
        asm volatile("ld.relaxed.gpu.global.u32 %0, [%1];" : "=r"(d) : "l"(tms) : "memory");
        if (++n > SPIN_LIMIT) __trap();
      } while (__any_sync(0xffffffffu, (d ^ t) & 255));
      ref += __reduce_max_sync(0xffffffffu, (int)(d - (ref << 6))) >> 6;
      sts1(sb + Q_REF, ref);
      __syncwarp();
      mbar_arrive_if0(lane, sb + B_REF);
      PROF_A(13, n);
      PROF_T(19);
    }
    if (w == 2 && rank == 2 && t < NT) {
      mbar_wait(sb + B_SM, (t - 1) & 1);
      mbar_rarrive_if0(lane >> 1, mapa(sb + B_AN, lane & 1));
      bar_sync<5, 160>();
      fence_async_smem();
      if (elect_one()) {
        bulk_s2s(mapa(sb + Q_OB, 1), sb + Q_OB, 4096, mapa(sb + B_O, 1));
        bulk_s2s(mapa(sb + Q_OB, 0), sb + Q_OB, 4096, mapa(sb + B_O, 0));
      }
      __syncwarp();
    }
    if (rank != 2) {
      softmax_x(sb, w, rank, t);
      if (w == 0 && t < NT) bar_arrive<7, 64>();
      mbar_expect_if0(lane | (w - 1), sb + B_SM, SX_BYTES);
    }
    }
    if (w == 0 && rank == 0 && t < NT) {
      if (t > 0) mbar_wait(sb + B_E + 16, (t - 1) & 1);
      if (elect_one()) {
#pragma unroll 1
        for (int k = 0; k < 9; k++) bulk_g2s_mc(sb + Q_X + 2048 + k * Q_CS, (const char*)g_xs + (size_t)t * 73728 + k * 8192, 1024, sb + B_G0, 7);
      }
      __syncwarp();
    }
    if (t == 0) continue;
    if (w == 3) PROF_MID();
    if (w && t < NT) {
      mbar_wait(sb + B_REF, (t - 1) & 1);
      uint32_t when = lds1(sb + Q_REF) + dly;
      sof ^= 2048; dof ^= 2048;
      uint4* src = (uint4*)((char*)P.part + sof) + lane;
      uint32_t* dst = (uint32_t*)((char*)P.memx + (dof ^ 2048));
      const bool inj = t == LAG && (lane & 8);
      if (t == LAG) {
        const __nv_bfloat16* m0 = P.mem0 + (lane & 3) * 2 * DM + c * 64 + head * 2 + (lane >> 4);
        st_gpu1_if(inj, dst, bf2_add(__bfloat16_as_ushort(m0[0]) | (uint32_t)__bfloat16_as_ushort(m0[DM]) << 16, 0));
      }
      asm volatile("" : "+l"(dst), "+l"(src));
      uint4 v[4];
      wait_ns(when);
      PROF_W(i3 == 0, 18);
      const uint32_t nr = poll4<true>(v, src, (t - 1) >> 1);
      PROF_T(26 + i3);
      const uint32_t z = bf2_add(bf2_add(v[0].z, v[1].z), bf2_add(v[2].z, v[3].z)), u = bf2_add(bf2_add(v[0].w, v[1].w), bf2_add(v[2].w, v[3].w));
      const uint32_t x = bf2_add(bf2_add(v[0].x, v[1].x), bf2_add(v[2].x, v[3].x)), y = bf2_add(bf2_add(v[0].y, v[1].y), bf2_add(v[2].y, v[3].y));
      const uint32_t x2 = bf2_add(bf2_add(x, 0), __shfl_xor_sync(0xffffffffu, z, 16)), y2 = bf2_add(y, __shfl_xor_sync(0xffffffffu, u, 16));
      const uint32_t x3 = bf2_add(x2, __shfl_xor_sync(0xffffffffu, y2, 8));
      st_gpu1_if(!inj, dst, bf2_add(x3, __shfl_xor_sync(0xffffffffu, x3, 4)));
      if (w == 3 && rank == 2) bar_arrive<12, 160>();
      PROF_T(29 + i3);
      PROF_A(10 + i3, nr);
      when += D_GX + min(lds1(sb + Q_REF + 4), 8u) * D_ADAPT;
      if (nr && t > LAG + 3 && dly < tile_delay(rank, i3) + 8 * D_ADAPT) dly += D_ADAPT;
      fence_async_global();
      if (w == 3 && rank != 2) bar_sync<7, 64>();
      wait_ns(when);
      if (elect_one()) bulk_g2s_mc(sb + Q_X + c * Q_CS, (const char*)P.memx + gof + (~t & 1) * 2048, 2048, sb + B_CP + 8 * c, 7);
      __syncwarp();
      if (i3 == 0) PROF_T(21);
      st_gpu1((uint32_t*)((char*)P.memx + dof), SENT);
    }
    if (w == 0 && rank == 2) {
      if (t < NT) mbar_wait(sb + B_XF, t & 1); else warp_flag_wait(g_flags + FL_XS + NT * 32 + 16, 4);
      mbar_wait(sb + B_OXREADY, (t - 1) & 1);
      if (elect_one()) {
        uint4* od = g_ox + (size_t)(t & (OXRING - 1)) * 32768 + head * 512;
        if (t <= NSEG) bulk_s2g(od, sb + Q_OX, 8192);
        if (t > LAG) bulk_s2g(od + 16384, sb + Q_OX + 8192, 8192);
        bulk_commit_wait();
        mbar_arrive(sb + B_OXFREE);
        flag_add(g_flags + FL_OX + t * 32 + head);
      }
      __syncwarp();
      PROF_T(25);
    }
  }
  cluster_sync();
}

__global__ void __cluster_dims__(3, 1, 1) __launch_bounds__(512, 1) head_kernel(const Params P) {
  extern __shared__ uint8_t smem_raw[];
  const uint32_t sb = (uint32_t)__cvta_generic_to_shared(smem_raw);
  if ((sb & 0xFFFFFFu) != SB0) __trap();
  asm volatile("griddepcontrol.launch_dependents;");
  if (threadIdx.x < 96) {
    const int i = blockIdx.x * 24 + threadIdx.x % 24, m = threadIdx.x / 24;
    const __nv_bfloat16* p = m == 3 ? P.ssm_k + (size_t)(i >> 2) * SEQ + (i & 3) * 64 : (m == 0 ? P.ck : m == 1 ? P.cv : P.x0) + (size_t)i * 64;
    asm volatile("prefetch.global.L2 [%0];" :: "l"(p));
  } else if (threadIdx.x == 96 && blockIdx.x < 45) {
    asm volatile("prefetch.global.L2 [%0];" :: "l"(blockIdx.x < 36 ? P.shift + blockIdx.x * 64 : P.ssm_d + (blockIdx.x - 36) * 64));
  }
  PROF_BEGIN();
  {
    const int wp = rd_warp();
    if (wp == 13) sts1(sb + Q_SET, (__ldcg(&g_epoch) & 1) * FL_TOTAL);
    if (wp <= 12) {
      const uint32_t sel = __shfl_sync(0xffffffffu, near_page(wp < 9 ? P.memx + wp * 512 + (blockIdx.x & 63) * 2 :
          wp < 12 ? P.part + (blockIdx.x * 3 + wp - 9) * 512 : P.memx + 9 * 512 + 128 + (blockIdx.x & 63) * 2, wp < 9 ? SENT : 1), 0);
      sts1(sb + Q_SEL + 4 * wp, sel * 4096);
    }
  }
  const int rank = rd_rank(), wg = rd_warp() >> 2;
  if (threadIdx.x == 448) {
    for (int c = 0; c < 9; c++) { mbar_init(sb + B_CP + 8 * c, 1); mbar_arrive(sb + B_CP + 8 * c); mbar_init(sb + B_OK + 8 * c, 1); mbar_init(sb + B_XF + 8 * c, 1); mbar_expect(sb + B_XF + 8 * c, 7168); }
    mbar_init(sb + B_E, 6); mbar_init(sb + B_G0, 1); mbar_expect(sb + B_G0, 9216); mbar_init(sb + B_E + 16, 6); mbar_init(sb + B_E + 24, 7);
    mbar_init(sb + B_SM, rank == 2 ? 1 : 2); mbar_init(sb + B_O, 1); mbar_init(sb + B_P, 1); mbar_init(sb + B_P + 8, 1);
    mbar_init(sb + B_REF, 1); mbar_init(sb + B_RES, 1); mbar_init(sb + B_PZ, 1); mbar_init(sb + B_AN, 1); mbar_init(sb + B_OXREADY, 4); mbar_init(sb + B_OXFREE, 1);
    mbar_expect(sb + B_SM, rank == 2 ? SM_BYTES : SX_BYTES); mbar_expect(sb + B_P, PX_BYTES); mbar_expect(sb + B_P + 8, PX_BYTES);
    mbar_expect(sb + B_O, 4096);
    sts1(sb + Q_REF + 4, 0);
    asm volatile("fence.mbarrier_init.release.cluster;" ::: "memory");
  }
  __syncthreads();
  PROF_G(6);
  if (wg < 2) {
    asm volatile("setmaxnreg.inc.sync.aligned.u32 176;");
    head_main(sb, P);
    PROF_END();
  } else if (wg == 2) {
    asm volatile("setmaxnreg.dec.sync.aligned.u32 120;");
    head_aux(sb, P);
    PROF_END();
  } else {
    asm volatile("setmaxnreg.dec.sync.aligned.u32 40;");
    head_service(sb, P);
    PROF_END();
  }
}

__device__ __forceinline__ void tail_gemm(uint32_t sb, const Params& P) {
  const int lane = threadIdx.x & 31, warp = rd_warp(), w = warp & 3, wg = warp >> 2, tid = threadIdx.x & 127;
  const __nv_bfloat16* wsrc = P.wo + (size_t)(blockIdx.x / 3) * 512 * DM + (blockIdx.x % 3) * 192 + wg * 64;
  uint32_t a[4 * W_KR];
  load_rows<29>(sb + wg * 65536, wsrc, DM, W_KR * 16, tid, 128);
  load_rows<3>(sb + W_WS + wg * 6144, wsrc + (size_t)W_KR * 16 * DM, DM, 512 - W_KR * 16, tid, 128);
  bar_sync_r(9 + wg, 128);
  load_afrags<W_KR>(a, sb + wg * 65536, w, lane);
  fence_async_smem();
  bar_sync<1, 416>();
  PROF_G(26);
  if (wg == 2) bar_arrive<2, 256>();
  const uint64_t dw = P.d_ws + wg * 384;
  float4* dst0 = g_acc + ((blockIdx.x % 3) * 12 + warp) * 32 + lane;
#pragma unroll 1
  for (int t = 1; t <= NT; t++) {
#pragma unroll 1
    for (int l = t > NSEG; l <= (t > LAG); l++) {
      const int seg = t - 1 - l * LAG, grp = (seg & 1) * 2 + l;
      const uint64_t db = P.d_ring + grp * 2048;
      float acc[16];
      bar_sync_r(2 + wg, 256);
#pragma unroll
      for (int c = 0; c < 4; c++) {
        if (wg == 0) mbar_wait(sb + B_FULL + 32 * grp + 8 * c, (seg >> 1) & 1);
        if (c == 0) PROF_T(6 * l + wg);
        wg_fence();
#pragma unroll
        for (int i = 0; i < 8; i++) {
          if (c == 0 && i == 0) wg_rs<0, 1>(acc, a, db, 0);
          else if (8 * c + i < W_KR) wg_rs<1, 1>(acc, a + 32 * c + 4 * i, db, 512 * c + 64 * i);
          else wg_ss<1, 1>(acc, dw, 128 * (8 * c + i - W_KR), db, 512 * c + 64 * i);
        }
      }
      wg_commit();
      bar_arrive_r(wg == 2 ? 2 : 3 + wg, 256);
      wg_wait<0>();
      reg_fence(acc);
      mbar_arrive_if0(tid, sb + B_EMPTY + 8 * grp);
      float4* dst = dst0 + (size_t)(l * 256 + seg * 4) * 1152;
#pragma unroll
      for (int j = 0; j < 4; j++)
        asm volatile("red.relaxed.gpu.global.add.v4.f32 [%0], {%1,%2,%3,%4};" :: "l"(dst + j * 1152),
                     "f"(acc[4 * j]), "f"(acc[4 * j + 1]), "f"(acc[4 * j + 2]), "f"(acc[4 * j + 3]) : "memory");
      bar_sync_r(5 + wg, 160);
    }
  }
}
__device__ __forceinline__ void tail_service(uint32_t sb) {
  const int lane = threadIdx.x & 31, warp = rd_warp();
  if (warp == 12) bar_sync<1, 416>();
#pragma unroll 1
  for (int t = 1; t <= NT; t++) {
    if (warp == 12) {
      const int h0 = (blockIdx.x / 3) * 4;
      warp_flag_wait(g_flags + FL_OX + t * 32 + h0 + (lane & 3), 1);
      fence_async_global();
#pragma unroll 1
      for (int l = t > NSEG; l <= (t > LAG); l++) {
        const int seg = t - 1 - l * LAG, grp = (seg & 1) * 2 + l;
        const uint4* src = g_ox + (size_t)(t % OXRING) * 32768 + l * 16384 + h0 * 512;
        const uint32_t bar = sb + B_FULL + 32 * grp;
        mbar_wait_lim(sb + B_EMPTY + 8 * grp, ((seg >> 1) & 1) ^ 1);
        mbar_expect_if0(lane > 3, bar + 8 * lane, 8192);
        if (elect_one()) {
#pragma unroll
          for (int j = 0; j < 4; j++) bulk_g2s(sb + W_RING + (grp * 4 + j) * 8192, src + j * 512, 8192, bar + 8 * j);
        }
        __syncwarp();
      }
      PROF_T(12);
      PROF_MID();
    } else {
#pragma unroll 1
      for (int l = t > NSEG; l <= (t > LAG); l++) {
        bar_sync_r(warp - 8, 160);
        if (lane == 0) flag_add(g_flags + FL_ACC + (l * 64 + t - 1 - l * LAG) * 32);
        __syncwarp();
        PROF_T(6 * l + warp - 10);
      }
    }
  }
}

__device__ __forceinline__ void wait_k1(uint32_t sb, int n) {
  uint32_t c = 0;
  while ((int)lds1(sb + W_K1) < n) {
    __nanosleep(64);
    if (++c > SPIN_LIMIT) __trap();
  }
}
__device__ __forceinline__ void tail_finisher(uint32_t sb, const Params& P) {
  const int lane = threadIdx.x & 31, warp = rd_warp(), kind = warp < 12 ? warp / 6 : warp & 1, f = warp - 6 * kind, tg = blockIdx.x & 3;
  if (warp >= 14) {
    const uint32_t set = lds1(sb + Q_SET), ft = sb + W_FO + kind * 576;
    if (tg == 0) for (int i = kind * 32 + lane; i < FL_TOTAL; i += 64) g_flagsets[FL_TOTAL - set + i] = 0;
#pragma unroll 1
    for (int t = 0; t < NSEG; t++) {
      warp_flag_wait(g_flags + FL_ACC + (64 + t) * 32, 72);
      PROF_T(17);
      if (t == 0 && tg == 0 && threadIdx.x == 448) g_epoch = set ? 0 : 1;
      const float4* ac = g_acc + ((size_t)(256 + t * 4 + tg) * 36 + kind * 18) * 32 + lane;
      float4 v[18];
#pragma unroll
      for (int i = 0; i < 18; i++) v[i] = __ldcg(ac + i * 32);
#pragma unroll
      for (int i = 0; i < 9; i++) {
        const uint4 r = lds4(sb + W_RS + (8 + (t & 7)) * 9216 + (kind * 9 + i) * 512 + lane * 16);
        stsm4t(ft + (lane & 7) * 1168 + (lane >> 3) * 16 + 64 * i, bf2_add(r.x, pack_bf16(v[2 * i].x, v[2 * i].y)), bf2_add(r.y, pack_bf16(v[2 * i].z, v[2 * i].w)),
               bf2_add(r.z, pack_bf16(v[2 * i + 1].x, v[2 * i + 1].y)), bf2_add(r.w, pack_bf16(v[2 * i + 1].z, v[2 * i + 1].w)));
      }
      fence_async_smem();
      __syncwarp();
      mbar_arrive_if0(lane, sb + B_RF + 8 * (t & 7));
      wait_k1(sb, min(t + LAG + 1, NSEG));
      if (lane < 8) {
        bulk_s2g(P.out + (size_t)((t * 4 + tg) * 8 + lane) * DM + kind * 288, ft + lane * 1168, 576);
        bulk_commit_wait();
      }
      __syncwarp();
      PROF_T(18);
    }
    return;
  }
  if (warp >= 12) {
    for (int i = kind * 32 + lane; i < 1152; i += 64) sts4(sb + W_Z + i * 16, make_uint4(0, 0, 0, 0));
    fence_async_smem();
    bar_sync<12, 64>();
#pragma unroll 1
    for (int t = -1; t <= NSEG; t++) {
      if (kind == 0 && t + 1 < NSEG) {
        const uint32_t bar = sb + B_FT + 8 * ((t + 1) & 1);
        mbar_expect_if0(lane, bar, 9216);
        __syncwarp();
        if (lane < 8) bulk_g2s(sb + W_FT + ((t + 1) & 1) * 9344 + lane * 1168, P.x0 + (size_t)(((t + 1) * 4 + tg) * 8 + lane) * DM, 1152, bar);
      }
      if (t < 0) continue;
      if (t < NSEG) bar_sync_r(9 + 2 * kind, 224);
      if (lane == 0) {
        flag_add(g_flags + FL_XS + (t + kind * LAG) * 32 + kind * 16);
        if (kind) { sts1(sb + W_K1, t + 1); PROF_T(14); }
        if (kind ? t < NSEG : t < LAG) bulk_s2g(g_acc + (size_t)(kind * 256 + t * 4 + tg) * 1152, sb + W_Z, 18432);
        if (kind && t + LAG < NSEG) bulk_s2g(g_acc + (size_t)((t + LAG) * 4 + tg) * 1152, sb + W_Z, 18432);
        bulk_commit_wait();
      }
      __syncwarp();
      if (kind) PROF_MID();
    }
    return;
  }
  const uint32_t BF_1 = 0x3F803F80u;
  const uint32_t* ys = (const uint32_t*)(g_y + ((tg >> 1) * DM + f * 96 + (lane >> 2)) * 2 + (tg & 1)) + (lane & 3);
  const uint32_t rs = sb + W_RS + f * 1536 + lane * 16;
  uint32_t y[12] = {};
#pragma unroll 1
  for (int t = 0; t < NSEG; t++) {
    uint32_t x[12];
    if (kind == 0) {
      wait_k1(sb, t - 6);
      mbar_wait(sb + B_FT + 8 * (t & 1), (t >> 1) & 1);
#pragma unroll
      for (int i = 0; i < 3; i++)
        ldsm4t(x[4 * i], x[4 * i + 1], x[4 * i + 2], x[4 * i + 3], sb + W_FT + (t & 1) * 9344 + (lane & 7) * 1168 + f * 192 + (lane >> 3) * 16 + 64 * i);
    } else {
      warp_flag_wait(g_flags + FL_ACC + t * 32, 72);
      PROF_T(13);
#pragma unroll
      for (int i = 0; i < 6; i++) {
        const float4 v = __ldcg(g_acc + ((size_t)(t * 4 + tg) * 36 + f * 6 + i) * 32 + lane);
        x[2 * i] = pack_bf16(v.x, v.y); x[2 * i + 1] = pack_bf16(v.z, v.w);
      }
#pragma unroll
      for (int i = 0; i < 3; i++) {
        const uint4 r = lds4(rs + (t & 7) * 9216 + i * 512);
        x[4 * i] = bf2_add(x[4 * i], r.x); x[4 * i + 1] = bf2_add(x[4 * i + 1], r.y); x[4 * i + 2] = bf2_add(x[4 * i + 2], r.z); x[4 * i + 3] = bf2_add(x[4 * i + 3], r.w);
      }
      mbar_wait(sb + B_RF + 8 * (t & 7), ((t >> 3) & 1) ^ 1);
      PROF_T(15);
    }
    {
      if (t == 0) PROF_G(27);
#pragma unroll 1
      for (int pass = 0; pass < 2; pass++) {
        float g[2][4] = {};
#pragma unroll
        for (int i = 0; i < 12; i++) {
          uint32_t u;
          asm volatile("movmatrix.sync.aligned.m8n8.trans.b16 %0, %1;" : "=r"(u) : "r"(x[i]));
          mma1688(g[i & 1], u, BF_1, u);
        }
        const uint32_t st = sb + W_ST + kind * 1024 + pass * 512 + (lane & 3) * 16;
        if ((lane >> 3) == (lane & 3))
          asm volatile("st.shared.v2.f32 [%0], {%1,%2};" :: "r"(st + f * 64 + (lane & 4) * 2), "f"(lane & 4 ? g[0][3] + g[1][3] : g[0][2] + g[1][2]),
                       "f"(lane & 4 ? g[0][1] + g[1][1] : g[0][0] + g[1][0]) : "memory");
        bar_sync_r(8 + 2 * kind, 192);
        float s0 = 0.f, s1 = 0.f, q0 = 0.f, q1 = 0.f;
        if (kind && pass == 0) PROF_T(19);
        if (kind && pass == 1) PROF_T(21);
#pragma unroll
        for (int i = 0; i < 6; i++) {
          const float4 e = lds4f(st + i * 64);
          s0 += e.x; q0 += e.y; s1 += e.z; q1 += e.w;
        }
        s0 *= 1.f / 576.f; s1 *= 1.f / 576.f;
        const float v0 = fmaf(q0, 1.f / 576.f, -s0 * s0), v1 = fmaf(q1, 1.f / 576.f, -s1 * s1);
        const uint32_t nmean = pack_bf16(-s0, -s1), vb = pack_bf16(fmaxf(v0, 0.f), fmaxf(v1, 0.f));
        const uint32_t ve = pack_bf16(bf_lo(vb) + 1e-5f, bf_hi(vb) + 1e-5f), sd = pack_bf16(sqr(bf_lo(ve)), sqr(bf_hi(ve)));
        const float r0 = rcp(bf_lo(sd)), r1 = rcp(bf_hi(sd));
        const uint32_t rh = pack_bf16(r0, r1), rl = pack_bf16(r0 - bf_lo(rh), r1 - bf_hi(rh));
        if (pass == 0 && (t == 0 || t == 4 * CT_A || t == 4 * CT_B || t == 4 * CT_C)) {
          if (t == 0) PROF_G(25);
          warp_flag_wait(g_flags + FL_Y + t * 8, t < 4 * CT_B ? 32 : DM);
          if (t == 0) PROF_G(26);
#pragma unroll
          for (int i = 0; i < 12; i++) y[i] = __ldcg(ys + t * (DM * 16) + i * 64);
        }
        uint32_t* xd = (uint32_t*)(g_xs + (size_t)(t + kind * LAG) * 4608 + (kind * 4 + tg) * 64 + (f * 3 >> 1) * 512 + (f & 1) * 32) + lane;
#pragma unroll
        for (int i = 0; i < 12; i++) {
          const uint32_t d = bf2_add(x[i], nmean), q = bf2_op(d, rh, bf2_mul(d, rl));
          if (pass == 0) x[i] = bf2_add(x[i], bf2_mul(q, y[i]));
          else xd[i < 4 ? i * 32 : i < 8 ? i * 32 + (f & 1) * 1792 : i * 32 + 1792] = q;
        }
        if (pass == 0) {
#pragma unroll
          for (int i = 0; i < 3; i++) sts4(rs + (kind * 8 + (t & 7)) * 9216 + i * 512, make_uint4(x[4 * i], x[4 * i + 1], x[4 * i + 2], x[4 * i + 3]));
        }
        if (kind && pass == 0) PROF_T(20);
        if (kind && pass == 1) PROF_T(22);
      }
      if (kind) PROF_T(16);
      if (t < 3) PROF_G(28 + t);
      bar_sync_r(9 + 2 * kind, 224);
#pragma unroll
      for (int i = 0; i < 12; i++) y[i] = __ldcg(ys + ((t + 1) & 63) * (DM * 16) + i * 64);
    }
  }
}

template <int NP, typename V>
__device__ __forceinline__ void kv_block(uint4 (&o)[2 * NP], const Params& P, int r0, int c0) {
  V kk[11], vv[8];
  uint4 sw[NP];
#pragma unroll
  for (int i = 0; i < NP; i++) sw[i] = __ldg((const uint4*)(P.shift + (c0 + 2 * i) * 4));
#pragma unroll
  for (int i = 0; i < 11; i++) kk[i] = r0 + i >= 3 ? __ldg((const V*)(P.ck + (size_t)(r0 + i - 3) * DM + c0)) : V{};
#pragma unroll
  for (int i = 0; i < 8; i++) vv[i] = __ldg((const V*)(P.cv + (size_t)(r0 + i) * DM + c0));
#pragma unroll
  for (int cp = 0; cp < NP; cp++) {
    const uint32_t wt[4] = {__byte_perm(sw[cp].y, sw[cp].w, 0x7632), __byte_perm(sw[cp].y, sw[cp].w, 0x5410),
                            __byte_perm(sw[cp].x, sw[cp].z, 0x7632), __byte_perm(sw[cp].x, sw[cp].z, 0x5410)};
    uint32_t e[8];
#pragma unroll
    for (int i = 0; i < 8; i++) {
      uint32_t a = bf2_mul(((const uint32_t*)&kk[i])[cp], wt[0]);
#pragma unroll
      for (int j = 1; j < 4; j++) a = bf2_add(a, bf2_mul(((const uint32_t*)&kk[i + j])[cp], wt[j]));
      e[i] = bf2_mul(a, ((const uint32_t*)&vv[i])[cp]);
    }
    o[2 * cp] = make_uint4(__byte_perm(e[0], e[1], 0x5410), __byte_perm(e[2], e[3], 0x5410), __byte_perm(e[4], e[5], 0x5410), __byte_perm(e[6], e[7], 0x5410));
    o[2 * cp + 1] = make_uint4(__byte_perm(e[0], e[1], 0x7632), __byte_perm(e[2], e[3], 0x7632), __byte_perm(e[4], e[5], 0x7632), __byte_perm(e[6], e[7], 0x7632));
  }
}
__device__ __forceinline__ void kv_task(const Params& P, int id) {
  const int lane = threadIdx.x & 31, tq = id / 9, c0 = (id % 9) * 64 + (lane >> 2) * 8;
  uint4 o[8];
  kv_block<4, uint4>(o, P, tq * 32 + (lane & 3) * 8, c0);
#pragma unroll
  for (int c = 0; c < 8; c++) g_kv[((size_t)tq * DM + c0 + c) * 4 + (lane & 3)] = o[c];
}
__device__ __forceinline__ int next_job(uint32_t sb) {
  int j = 0;
  if ((threadIdx.x & 31) == 0) j = atomicAdd(g_flags + FL_KV + 96, 1);
  return __shfl_sync(0xffffffffu, j, 0);
}
__device__ __forceinline__ uint2 lds2_ro(uint32_t a) { uint2 v; asm("ld.shared.v2.u32 {%0,%1}, [%2];" : "=r"(v.x), "=r"(v.y) : "r"(a)); return v; }

template <int T0, int T1>
__device__ __forceinline__ void conv_job(uint32_t sb, const Params& P, int ch) {
  const int lane = threadIdx.x & 31, w = threadIdx.x >> 5;
  const uint32_t ub = sb + w * C_CH, zb = ub + C_U;
  constexpr int NL = (T1 + 1) / 2;
  constexpr bool CTA = T1 <= CT_B;
  PROF_G(13 + 4 * (T0 == 0 ? 0 : T0 == CT_A ? 1 : 2));
  uint2 q[T1];
#pragma unroll
  for (int u = 0; u < T1; u++) q[u] = __ldg((const uint2*)(P.ssm_k + (size_t)ch * SEQ) + u * 32 + lane);
  const uint32_t dd = (uint32_t)__bfloat16_as_ushort(P.ssm_d[ch]) * 0x10001u;
  if (CTA) {
#pragma unroll
    for (int tq = w; tq < 4 * T1; tq += 16) {
      uint4 o[2];
      const int tgp = tq * 4 + (lane & 3), c0 = (lane >> 2) * 2;
      kv_block<1, uint32_t>(o, P, tgp * 8, ch - w + c0);
#pragma unroll
      for (int c = 0; c < 2; c++) {
        sts4(sb + (c0 + c) * C_CH + 256 + tgp * 16, o[c]);
        if (T0) g_kv[((size_t)tq * DM + ch - w + c0 + c) * 4 + (lane & 3)] = o[c];
      }
    }
    __syncwarp();
  } else {
    uint4 o[NL];
#pragma unroll
    for (int u = 0; u < NL; u++) o[u] = __ldcg(g_kv + ((size_t)(u * 8 + (lane >> 2)) * DM + ch) * 4 + (lane & 3));
#pragma unroll
    for (int u = 0; u < NL; u++) sts4(ub + 256 + (u * 32 + lane) * 16, o[u]);
  }
  if (lane < 16) { sts4(ub + lane * 16, make_uint4(0, 0, 0, 0)); sts1(zb + lane * 4, 0); }
#pragma unroll
  for (int u = 0; u < T1; u++) {
    const uint32_t pv = __shfl_sync(0xffffffffu, lane == 31 ? (u ? q[u ? u - 1 : 0].y : 0u) : q[u].y, (lane + 31) & 31);
    sts4(zb + 64 + (u * 32 + lane) * 16, make_uint4(__byte_perm(q[u].x, pv, 0x7610), __byte_perm(q[u].x, q[u].x, 0x1032),
                                                   __byte_perm(q[u].y, q[u].x, 0x7610), __byte_perm(q[u].y, q[u].y, 0x1032)));
  }
  if (CTA) __syncthreads(); else __syncwarp();
  PROF_G(14 + 4 * (T0 == 0 ? 0 : T0 == CT_A ? 1 : 2));
  float acc[T1 - T0][4];
#pragma unroll
  for (int i = 0; i < T1 - T0; i++) acc[i][0] = acc[i][1] = acc[i][2] = acc[i][3] = 0.f;
#pragma unroll(T0 == 0 ? 4 : 1)
  for (int r = 0; r < 8; r++) {
    uint2 b[T1];
    uint32_t ba = ub + 256 - r * 32 + lane * 8, zp = zb + 64 + (16 * r + 2 * (lane >> 2) - 4 * (lane & 3)) * 4;
    asm volatile("" : "+r"(zp), "+r"(ba) :: "memory");
#pragma unroll
    for (int i = 0; i < T1; i++) b[i] = lds2_ro(ba + i * 256);
#pragma unroll
    for (int mu = 0; mu < T1; mu++) {
      const uint2 a01 = lds2_ro(zp + 512 * mu), a23 = lds2_ro(zp + 512 * mu - 8);
#pragma unroll
      for (int i = (mu > T0 ? mu : T0); i < T1; i++) mma16816(acc[i - T0], a01.x, a01.y, a23.x, a23.y, b[i - mu].x, b[i - mu].y);
    }
  }
  PROF_G(15 + 4 * (T0 == 0 ? 0 : T0 == CT_A ? 1 : 2));
#pragma unroll
  for (int i = 0; i < T1 - T0; i++)
#pragma unroll
    for (int e = 0; e < 2; e++) {
      const int col = (T0 + i) * 8 + 2 * (lane & 3) + e;
      ((uint32_t*)g_y)[((size_t)col * DM + ch) * 8 + (lane >> 2)] =
          bf2_add(pack_bf16(acc[i][e], acc[i][2 + e]), bf2_mul(lds1(ub + 256 + col * 32 + (lane >> 2) * 4), dd));
    }
  if (CTA) __syncthreads(); else __syncwarp();
  PROF_G(16 + 4 * (T0 == 0 ? 0 : T0 == CT_A ? 1 : 2));
  if (CTA ? threadIdx.x == 480 && ch < 512 : lane == 0) flag_add(g_flags + FL_Y + T0 * 32);
  __syncwarp();
}

__global__ void __launch_bounds__(512, 1) tail_kernel(const Params P) {
  extern __shared__ uint8_t smem_raw[];
  const uint32_t sb = (uint32_t)__cvta_generic_to_shared(smem_raw);
  if (sb != SB0) __trap();
  PROF_BEGIN();
  if (threadIdx.x == 0) {
    for (int c = 0; c < 16; c++) mbar_init(sb + B_FULL + 8 * c, 1);
    for (int c = 0; c < 4; c++) mbar_init(sb + B_EMPTY + 8 * c, 3);
    for (int c = 0; c < 2; c++) mbar_init(sb + B_FT + 8 * c, 1);
    for (int c = 0; c < 8; c++) mbar_init(sb + B_RF + 8 * c, 2);
    sts1(sb + W_K1, 0);
    sts1(sb + Q_SET, (__ldcg(&g_epoch) & 1) * FL_TOTAL);
    fence_async_smem();
  }
  const int b = blockIdx.x, w = threadIdx.x >> 5;
  if ((b >> 2) == 6) {
    __syncthreads();
  } else {
#pragma unroll 1
    for (int g = b; g == b || (g >> 2) == 6; g -= 8) conv_job<0, CT_A>(sb, P, g * 16 + w);
    PROF_G(3);
#pragma unroll 1
    for (int g = b; g == b || (g >> 2) == 6; g -= 8) conv_job<CT_A, CT_B>(sb, P, g * 16 + w);
    PROF_G(4);
    constexpr int KV0 = 36 * CT_B, KV1 = KV0 + 192;
    int job = b < 32 ? KV0 + (b - 28) * 16 + w : -1;
#pragma unroll 1
    for (int k = 0; b >= 28; k++) {
      if (job >= 0) {
        kv_task(P, job);
        __syncwarp();
        if ((threadIdx.x & 31) == 0) flag_add(g_flags + FL_KV + (job < KV1 ? 0 : 32));
        if (job + 64 < KV1) { job += 64; continue; }
      }
      if (job < KV1) {
        warp_flag_wait(g_flags + FL_Y + CT_A * 32, 32);
        warp_flag_wait(g_flags + FL_KV, 192);
        spin_until(rd_clock() + (w >> 2) * 2000);
      }
      while ((job = next_job(sb)) < DM) conv_job<CT_B, CT_C>(sb, P, job);
      if (job < DM + 128) PROF_G(6);
      job -= DM - KV1;
      if (job >= 576) break;
    }
    if (b >= 28) {
      warp_flag_wait(g_flags + FL_KV + 32, 576 - KV1);
#pragma unroll 1
      for (job -= 576; job < DM; job = next_job(sb) - DM - (576 - KV1)) conv_job<CT_C, 16>(sb, P, job);
      PROF_G(5);
      PROF_END();
      return;
    }
    __syncwarp();
  }
  if (blockIdx.x >= 24) {
    PROF_G(24);
    tail_finisher(sb, P);
    PROF_END();
    asm volatile("griddepcontrol.wait;" ::: "memory");
  } else if (rd_warp() < 12) {
    asm volatile("setmaxnreg.inc.sync.aligned.u32 160;");
    tail_gemm(sb, P);
    PROF_END();
  } else {
    asm volatile("setmaxnreg.dec.sync.aligned.u32 32;");
    tail_service(sb);
    PROF_END();
  }
}

}

extern "C" void kernel_launch(void* const* d_in, const int* in_sizes, int n_in, void* d_out, int out_size) {
  typedef const __nv_bfloat16* bp;
  Params P;
  P.x0 = (bp)d_in[0]; P.ck = (bp)d_in[1]; P.cv = (bp)d_in[2]; P.shift = (bp)d_in[3]; P.ssm_k = (bp)d_in[4]; P.ssm_d = (bp)d_in[5];
  P.mem0 = (bp)d_in[7]; P.wq = (bp)d_in[8]; P.wk = (bp)d_in[9]; P.wv = (bp)d_in[10]; P.wo = (bp)d_in[11];
  P.out = (__nv_bfloat16*)d_out;
  void* xc = nullptr;
  cudaGetSymbolAddress(&xc, g_xchg);
  P.part = (uint4*)(((uintptr_t)xc + 8191) & ~(uintptr_t)8191);
  P.memx = P.part + 288 * 512;
  P.d_x = mkdesc(Q_X, 128, 1024, 0); P.d_wl = mkdesc(Q_WL, 16, 1024, 1);
  P.d_ring = mkdesc(W_RING, 512, 128, 0); P.d_ws = mkdesc(W_WS, 16, 1024, 1);
  cudaFuncSetAttribute(head_kernel, cudaFuncAttributeMaxDynamicSharedMemorySize, SMEM_TOTAL);
  cudaFuncSetAttribute(tail_kernel, cudaFuncAttributeMaxDynamicSharedMemorySize, SMEM_TOTAL);
  head_kernel<<<96, 512, SMEM_TOTAL>>>(P);
  cudaLaunchConfig_t cfg = {};
  cfg.gridDim = dim3(36); cfg.blockDim = dim3(512); cfg.dynamicSmemBytes = SMEM_TOTAL; cfg.stream = 0;
  cudaLaunchAttribute attr[1];
  attr[0].id = cudaLaunchAttributeProgrammaticStreamSerialization;
  attr[0].val.programmaticStreamSerializationAllowed = 1;
  cfg.attrs = attr; cfg.numAttrs = 1;
  cudaLaunchKernelEx(&cfg, tail_kernel, P);
}
```

```cpp
#include <cuda.h>
#include <cuda_runtime.h>
#include <cuda_bf16.h>
#include <stdint.h>

namespace {

constexpr int SEQ = 2048, DM = 576, NSEG = 64;
#define LAG_V 5
#define RV_V 2000
#define R1_V 380
#define R0_V 590
#define V1_V 80
#define V2_V 200
#define Q1_V 150
#define Q2_V 290
#define SWAP_V 1
#define ST0_V 200
#define GX_V 1130
#define AD_V 0
#define RS_V 5
#define CALIB 0
#define RF_V 2350
#define RL_V 2000
#define PA1_V 500
#define PA0_V 700
#define ST_V 5
#define XA_V 1
#define XP_V 160
#define KPV_V 16
#define KP1_V 24
#define KP0_V 28
constexpr int LAG = LAG_V;
constexpr int NT = NSEG + LAG;
constexpr int OXRING = 8;
static_assert(LAG >= 3 && LAG < OXRING, "pipeline lag");
constexpr uint32_t D_RED = RV_V;
__host__ __device__ constexpr uint32_t rank_delay(int r) { return r == 2 ? 0 : r ? R1_V : R0_V; }
__host__ __device__ constexpr int tile_of(int r, int i) { return r == 2 ? i : SWAP_V ? (r ? 3 + i + (i >> 1) : 5 + i + (i > 0)) : 6 - 3 * r + i; }
__host__ __device__ constexpr uint32_t tile_delay(int r, int i) { return (i == 0 ? 0 : r == 2 ? (i == 1 ? V1_V : V2_V) : i == 1 ? Q1_V : Q2_V) * 9 / 16; }
constexpr uint32_t D_DUE = RF_V, D_LATE = RL_V;
constexpr uint32_t D_GX = GX_V * 9 / 16, D_ADAPT = AD_V * 9 / 16;
constexpr int KP_V = KPV_V, KP_1 = KP1_V, KP_0 = KP0_V;
constexpr int KP_MAX = KP_0 > KP_1 ? KP_0 : KP_1;
constexpr uint32_t SB0 = 1024;
constexpr float SM_SCALE = 0.08838834764831845f * 1.4426950408889634f;
constexpr uint32_t SENT = 0x80008000u;
constexpr uint32_t SPIN_LIMIT = 1u << 21;

constexpr int FL_XS = 0;
constexpr int FL_ACC = (NT + 2) * 32;
constexpr int FL_OX = FL_ACC + 128 * 32;
constexpr int FL_SEL = FL_OX + (NT + 1) * 32;
constexpr int FL_Y = FL_SEL + 96 * 4;
constexpr int FL_KV = FL_Y + 512;
constexpr int FL_TOTAL = FL_KV + 128;

__device__ __align__(1024) uint4 g_y[256 * DM];
__device__ __align__(1024) uint4 g_kv[256 * DM];
__device__ __align__(1024) float4 g_acc[2 * 256 * 36 * 32];
__device__ __align__(1024) uint4 g_xs[NT * 4608];
__device__ __align__(1024) uint4 g_ox[OXRING * 512 * 8 * 8];
__device__ __align__(1024) uint4 g_xchg[(256 + 256 + 45) * 512];
__host__ __device__ constexpr uint32_t part_of(int cta) { return (cta < 81 ? 12 + cta * 3 : 13 + cta * 3) * 8192; }
__device__ __align__(1024) uint32_t g_flagsets[2 * FL_TOTAL];
__device__ uint32_t g_epoch;
#define PROF_T(slot) do {} while (0)
#define PROF_END() do {} while (0)
#define PROF_W(cond, slot) do {} while (0)
#define PROF_V(cond, slot, val) do { (void)(val); } while (0)
#define PROF_G(slot) do {} while (0)
#define PROF_OR(slot, val) do {} while (0)
#define PROF_A(idx, val) do { (void)(val); } while (0)
#define PROF_BEGIN() do {} while (0)
#define PROF_MID() do {} while (0)

#define CHINT ""
#define HINT ", 100000"
__device__ __forceinline__ uint32_t pack_bf16(float lo, float hi) {
  uint32_t r; asm("cvt.rn.bf16x2.f32 %0, %1, %2;" : "=r"(r) : "f"(hi), "f"(lo)); return r;
}
__device__ __forceinline__ float bf_lo(uint32_t w) { return __uint_as_float(__byte_perm(w, 0, 0x1044)); }
__device__ __forceinline__ float bf_hi(uint32_t w) { return __uint_as_float(w & 0xFFFF0000u); }
__device__ __forceinline__ uint32_t mapa(uint32_t a, uint32_t r) {
  uint32_t o; asm("mapa.shared::cluster.u32 %0, %1, %2;" : "=r"(o) : "r"(a), "r"(r)); return o;
}
__device__ __forceinline__ void mbar_init(uint32_t bar, uint32_t cnt) {
  asm volatile("mbarrier.init.shared::cta.b64 [%0], %1;" :: "r"(bar), "r"(cnt) : "memory");
}
__device__ __forceinline__ void mbar_expect(uint32_t bar, uint32_t bytes) {
  asm volatile("mbarrier.arrive.expect_tx.shared::cta.b64 _, [%0], %1;" :: "r"(bar), "r"(bytes) : "memory");
}
__device__ __forceinline__ void mbar_arrive(uint32_t bar) {
  asm volatile("mbarrier.arrive.shared::cta.b64 _, [%0];" :: "r"(bar) : "memory");
}
__device__ __forceinline__ void mbar_arrive_if0(uint32_t sel, uint32_t bar) {
  asm volatile("{\n.reg .pred p;\nsetp.eq.u32 p, %1, 0;\n@p mbarrier.arrive.shared::cta.b64 _, [%0];\n}" :: "r"(bar), "r"(sel) : "memory");
}
__device__ __forceinline__ void mbar_expect_if0(uint32_t sel, uint32_t bar, uint32_t bytes) {
  asm volatile("{\n.reg .pred p;\nsetp.eq.u32 p, %1, 0;\n@p mbarrier.arrive.expect_tx.shared::cta.b64 _, [%0], %2;\n}" :: "r"(bar), "r"(sel), "r"(bytes) : "memory");
}
__device__ __forceinline__ void mbar_rarrive_if0(uint32_t sel, uint32_t bar) {
  asm volatile("{\n.reg .pred p;\nsetp.eq.u32 p, %1, 0;\n@p mbarrier.arrive.relaxed.cluster.shared::cluster.b64 _, [%0];\n}" :: "r"(bar), "r"(sel) : "memory");
}
__device__ __forceinline__ void mbar_wait_lim(uint32_t bar, uint32_t par) {
  asm volatile(
    "{\n.reg .pred p;\n.reg .u32 c;\nmov.u32 c, 0;\n"
    "W_%=:\n"
    "mbarrier.try_wait.parity.shared::cta.b64 p, [%0], %1;\n"
    "@p bra D_%=;\n"
    "add.u32 c, c, 1;\nsetp.lt.u32 p, c, %2;\n@p bra W_%=;\ntrap;\n"
    "D_%=:\n}\n" :: "r"(bar), "r"(par), "n"(SPIN_LIMIT) : "memory");
}
__device__ __forceinline__ void mbar_wait(uint32_t bar, uint32_t par) {
  asm volatile(
    "{\n.reg .pred p;\n"
    "W_%=:\n"
    "mbarrier.try_wait.parity.shared::cta.b64 p, [%0], %1" HINT ";\n"
    "@!p bra W_%=;\n}\n" :: "r"(bar), "r"(par) : "memory");
}
__device__ __forceinline__ void mbar_spin(uint32_t bar, uint32_t par) {
  asm volatile("{\n.reg .pred p;\nW_%=:\nmbarrier.try_wait.parity.shared::cta.b64 p, [%0], %1;\n@!p bra W_%=;\n}\n" :: "r"(bar), "r"(par) : "memory");
}
__device__ __forceinline__ uint32_t mbar_test(uint32_t bar, uint32_t par) {
  uint32_t r;
  asm volatile("{\n.reg .pred p;\nmbarrier.test_wait.parity.shared::cta.b64 p, [%1], %2;\nselp.u32 %0, 1, 0, p;\n}" : "=r"(r) : "r"(bar), "r"(par) : "memory");
  return __shfl_sync(0xffffffffu, r, 0);
}
__device__ __forceinline__ void mbar_wait_if(uint32_t& done, uint32_t test, uint32_t bar, uint32_t par, bool force) {
  asm volatile(
    "{\n.reg .pred p, q;\nsetp.ne.u32 p, %0, 0;\n@p bra.uni D_%=;\nsetp.ne.u32 q, %4, 0;\n"
    "mbarrier.test_wait.parity.shared::cta.b64 p, [%1], %3;\n"
    "or.pred p, p, q;\n@!p bra D_%=;\n"
    "W_%=:\n"
    "mbarrier.try_wait.parity.shared::cta.b64 p, [%2], %3, 100000;\n"
    "@!p bra W_%=;\nmov.u32 %0, 1;\nD_%=:\n}\n" : "+r"(done) : "r"(test), "r"(bar), "r"(par), "r"((uint32_t)force) : "memory");
}
template <int ID, int N> __device__ __forceinline__ void bar_sync() { asm volatile("bar.sync %0, %1;" :: "n"(ID), "n"(N) : "memory"); }
template <int ID, int N> __device__ __forceinline__ void bar_arrive() { asm volatile("bar.arrive %0, %1;" :: "n"(ID), "n"(N) : "memory"); }
__device__ __forceinline__ void bar_sync_r(int id, int n) { asm volatile("bar.sync %0, %1;" :: "r"(id), "r"(n) : "memory"); }
__device__ __forceinline__ void bar_arrive_r(int id, int n) { asm volatile("bar.arrive %0, %1;" :: "r"(id), "r"(n) : "memory"); }
__device__ __forceinline__ uint32_t pin(uint32_t x) { return __shfl_sync(0xffffffffu, x, threadIdx.x); }
__device__ __forceinline__ void cluster_sync() {
  asm volatile("barrier.cluster.arrive.aligned;\nbarrier.cluster.wait.aligned;" ::: "memory");
}
__device__ __forceinline__ void fence_async_smem() { asm volatile("fence.proxy.async.shared::cta;" ::: "memory"); }
__device__ __forceinline__ void fence_async_global() { asm volatile("fence.proxy.async.global;" ::: "memory"); }
__device__ __forceinline__ uint4 ld_poll(const uint4* p) {
  uint4 v;
  asm volatile("ld.relaxed.gpu.global.v4.u32 {%0,%1,%2,%3}, [%4];" : "=r"(v.x), "=r"(v.y), "=r"(v.z), "=r"(v.w) : "l"(p) : "memory");
  return v;
}
__device__ __forceinline__ uint32_t rd_clock() { uint64_t c; asm volatile("mov.u64 %0, %%clock64;" : "=l"(c) :: "memory"); return (uint32_t)c; }
__device__ __forceinline__ void spin_until(uint32_t when) {
  asm volatile("{\n.reg .pred p;\n.reg .b64 c;\n.reg .s32 lo;\nS_%=:\nmov.u64 c, %%clock64;\ncvt.u32.u64 lo, c;\nsub.s32 lo, lo, %0;\n"
               "setp.lt.s32 p, lo, 0;\n@p bra.uni S_%=;\n}" :: "r"(when) : "memory");
}
__device__ __forceinline__ uint32_t near_page(uint4* pair, uint32_t mark) {
  uint32_t best0 = ~0u, best1 = ~0u;
  const int lane = threadIdx.x & 31;
#pragma unroll 1
  for (int r = 0; r < 8; r++) {
    if (r >= 4 && !(r & 1) && __all_sync(0xffffffffu, max(best0, best1) - min(best0, best1) > 110u && min(best0, best1) < 420u)) break;
    uint32_t t0, t1, v;
    asm volatile("mov.u32 %0, %%clock;" : "=r"(t0) :: "memory");
    asm volatile("{\n.reg .pred p;\nsetp.eq.u32 p, %2, 0;\nmov.u32 %0, 0;\n@p atom.relaxed.gpu.global.exch.b32 %0, [%1], %3;\n}"
                 : "=&r"(v) : "l"(pair + (r & 1) * 256), "r"(lane), "r"(mark) : "memory");
    asm volatile("{\n.reg .pred p;\nsetp.ne.u32 p, %1, 0x9E3779B9;\nmov.u32 %0, %2;\n@p mov.u32 %0, %%clock;\n}" : "=&r"(t1) : "r"(v), "r"(t0 - 1) : "memory");
    if (r & 1) best1 = min(best1, t1 - t0); else best0 = min(best0, t1 - t0);
  }
  return best1 < best0;
}
__device__ __forceinline__ void st_gpu4(uint4* p, uint32_t a, uint32_t b, uint32_t c, uint32_t d) {
  asm volatile("st.relaxed.gpu.global.v4.u32 [%0], {%1,%2,%3,%4};" :: "l"(p), "r"(a), "r"(b), "r"(c), "r"(d) : "memory");
}
__device__ __forceinline__ void st_gpu1(uint32_t* p, uint32_t a) {
  asm volatile("st.relaxed.gpu.global.u32 [%0], %1;" :: "l"(p), "r"(a) : "memory");
}
__device__ __forceinline__ void st_gpu1_if(bool c, uint32_t* p, uint32_t a) {
  asm volatile("{\n.reg .pred p;\nsetp.ne.u32 p, %2, 0;\n@p st.relaxed.gpu.global.u32 [%0], %1;\n}" :: "l"(p), "r"(a), "r"((uint32_t)c) : "memory");
}
__device__ __forceinline__ void warp_flag_wait(const uint32_t* p, uint32_t target) {
  uint32_t v, n = 0;
  do {
    asm volatile("ld.relaxed.gpu.global.u32 %0, [%1];" : "=r"(v) : "l"(p) : "memory");
    if (++n > SPIN_LIMIT) __trap();
  } while (__any_sync(0xffffffffu, v < target));
}
__device__ __forceinline__ void flag_add(uint32_t* p) {
  asm volatile("red.release.gpu.global.add.u32 [%0], 1;" :: "l"(p) : "memory");
}
__device__ __forceinline__ void bulk_g2s(uint32_t dst, const void* src, uint32_t bytes, uint32_t bar) {
  asm volatile("cp.async.bulk.shared::cluster.global.mbarrier::complete_tx::bytes [%0], [%1], %2, [%3];"
               :: "r"(dst), "l"(src), "r"(bytes), "r"(bar) : "memory");
}
__device__ __forceinline__ void bulk_g2s_mc(uint32_t dst, const void* src, uint32_t bytes, uint32_t bar, uint16_t mask) {
  asm volatile("cp.async.bulk.shared::cluster.global.mbarrier::complete_tx::bytes.multicast::cluster [%0], [%1], %2, [%3], %4;"
               :: "r"(dst), "l"(src), "r"(bytes), "r"(bar), "h"(mask) : "memory");
}
__device__ __forceinline__ void tma_box(uint32_t dst, const CUtensorMap* tm, int col, int row, uint32_t bar) {
  asm volatile("cp.async.bulk.tensor.2d.shared::cluster.global.mbarrier::complete_tx::bytes [%0], [%1, {%2, %3}], [%4];"
               :: "r"(dst), "l"(tm), "r"(col), "r"(row), "r"(bar) : "memory");
}
__device__ __forceinline__ void bulk_s2s(uint32_t dst, uint32_t src, uint32_t bytes, uint32_t bar) {
  asm volatile("cp.async.bulk.shared::cluster.shared::cta.mbarrier::complete_tx::bytes [%0], [%1], %2, [%3];"
               :: "r"(dst), "r"(src), "r"(bytes), "r"(bar) : "memory");
}
__device__ __forceinline__ void bulk_s2g(void* dst, uint32_t src, uint32_t bytes) {
  asm volatile("cp.async.bulk.global.shared::cta.bulk_group [%0], [%1], %2;" :: "l"(dst), "r"(src), "r"(bytes) : "memory");
}
__device__ __forceinline__ void bulk_commit_wait() {
  asm volatile("cp.async.bulk.commit_group;\ncp.async.bulk.wait_group 0;" ::: "memory");
}
__device__ __forceinline__ bool elect_one() {
  uint32_t p; asm volatile("{\n.reg .pred p;\nelect.sync _|p, 0xffffffff;\nselp.u32 %0, 1, 0, p;\n}" : "=r"(p)); return p;
}
__device__ __forceinline__ void ldsm4(uint32_t& r0, uint32_t& r1, uint32_t& r2, uint32_t& r3, uint32_t a) {
  asm volatile("ldmatrix.sync.aligned.m8n8.x4.shared.b16 {%0,%1,%2,%3}, [%4];" : "=r"(r0), "=r"(r1), "=r"(r2), "=r"(r3) : "r"(a) : "memory");
}
__device__ __forceinline__ void ldsm4t(uint32_t& r0, uint32_t& r1, uint32_t& r2, uint32_t& r3, uint32_t a) {
  asm volatile("ldmatrix.sync.aligned.m8n8.x4.trans.shared.b16 {%0,%1,%2,%3}, [%4];" : "=r"(r0), "=r"(r1), "=r"(r2), "=r"(r3) : "r"(a) : "memory");
}
__device__ __forceinline__ void stsm4(uint32_t a, uint32_t r0, uint32_t r1, uint32_t r2, uint32_t r3) {
  asm volatile("stmatrix.sync.aligned.m8n8.x4.shared.b16 [%0], {%1,%2,%3,%4};" :: "r"(a), "r"(r0), "r"(r1), "r"(r2), "r"(r3) : "memory");
}
__device__ __forceinline__ void stsm2(uint32_t a, uint32_t r0, uint32_t r1) {
  asm volatile("stmatrix.sync.aligned.m8n8.x2.shared.b16 [%0], {%1,%2};" :: "r"(a), "r"(r0), "r"(r1) : "memory");
}
__device__ __forceinline__ void stsm4t(uint32_t a, uint32_t r0, uint32_t r1, uint32_t r2, uint32_t r3) {
  asm volatile("stmatrix.sync.aligned.m8n8.x4.trans.shared.b16 [%0], {%1,%2,%3,%4};" :: "r"(a), "r"(r0), "r"(r1), "r"(r2), "r"(r3) : "memory");
}
__device__ __forceinline__ float4 lds4f(uint32_t a) {
  float4 v; asm volatile("ld.shared.v4.f32 {%0,%1,%2,%3}, [%4];" : "=f"(v.x), "=f"(v.y), "=f"(v.z), "=f"(v.w) : "r"(a) : "memory"); return v;
}
__device__ __forceinline__ uint4 lds4(uint32_t a) {
  uint4 v; asm volatile("ld.shared.v4.u32 {%0,%1,%2,%3}, [%4];" : "=r"(v.x), "=r"(v.y), "=r"(v.z), "=r"(v.w) : "r"(a) : "memory"); return v;
}
__device__ __forceinline__ uint32_t lds1(uint32_t a) {
  uint32_t v; asm volatile("ld.shared.u32 %0, [%1];" : "=r"(v) : "r"(a) : "memory"); return v;
}
__device__ __forceinline__ void sts4(uint32_t a, uint4 v) {
  asm volatile("st.shared.v4.u32 [%0], {%1,%2,%3,%4};" :: "r"(a), "r"(v.x), "r"(v.y), "r"(v.z), "r"(v.w) : "memory");
}
__device__ __forceinline__ void sts1(uint32_t a, uint32_t v) { asm volatile("st.shared.u32 [%0], %1;" :: "r"(a), "r"(v) : "memory"); }
__device__ __forceinline__ void mma16816(float (&d)[4], uint32_t a0, uint32_t a1, uint32_t a2, uint32_t a3, uint32_t b0, uint32_t b1) {
  asm volatile("mma.sync.aligned.m16n8k16.row.col.f32.bf16.bf16.f32 {%0,%1,%2,%3}, {%4,%5,%6,%7}, {%8,%9}, {%0,%1,%2,%3};"
               : "+f"(d[0]), "+f"(d[1]), "+f"(d[2]), "+f"(d[3]) : "r"(a0), "r"(a1), "r"(a2), "r"(a3), "r"(b0), "r"(b1));
}
__device__ __forceinline__ void mma1688(float (&d)[4], uint32_t a0, uint32_t a1, uint32_t b0) {
  asm volatile("mma.sync.aligned.m16n8k8.row.col.f32.bf16.bf16.f32 {%0,%1,%2,%3}, {%4,%5}, {%6}, {%0,%1,%2,%3};"
               : "+f"(d[0]), "+f"(d[1]), "+f"(d[2]), "+f"(d[3]) : "r"(a0), "r"(a1), "r"(b0));
}
__device__ __forceinline__ float rcp(float x) { float r; asm("rcp.approx.ftz.f32 %0, %1;" : "=f"(r) : "f"(x)); return r; }
__device__ __forceinline__ float sqr(float x) { float r; asm("sqrt.approx.f32 %0, %1;" : "=f"(r) : "f"(x)); return r; }
__device__ __forceinline__ float ex2(float x) { float r; asm("ex2.approx.ftz.f32 %0, %1;" : "=f"(r) : "f"(x)); return r; }

__device__ __forceinline__ uint32_t bf2_op(uint32_t a, uint32_t b, uint32_t c) {
  uint32_t r; asm("fma.rn.bf16x2 %0, %1, %2, %3;" : "=r"(r) : "r"(a), "r"(b), "r"(c)); return r;
}
__device__ __forceinline__ uint32_t bf2_mul(uint32_t a, uint32_t b) {
  uint32_t r; asm("mul.rn.bf16x2 %0, %1, %2;" : "=r"(r) : "r"(a), "r"(b)); return r;
}
__device__ __forceinline__ uint32_t bf2_add(uint32_t a, uint32_t b) {
  uint32_t r; asm("add.rn.bf16x2 %0, %1, %2;" : "=r"(r) : "r"(a), "r"(b)); return r;
}

__host__ __device__ constexpr uint64_t mkdesc(uint32_t off, uint32_t lbo, uint32_t sbo, uint32_t sw) {
  return (uint64_t)((SB0 + off) >> 4) | ((uint64_t)(lbo >> 4) << 16) | ((uint64_t)(sbo >> 4) << 32) | ((uint64_t)sw << 62);
}
__device__ __forceinline__ void wg_fence() { asm volatile("wgmma.fence.sync.aligned;" ::: "memory"); }
__device__ __forceinline__ void wg_commit() { asm volatile("wgmma.commit_group.sync.aligned;" ::: "memory"); }
template <int N> __device__ __forceinline__ void wg_wait() { asm volatile("wgmma.wait_group.sync.aligned %0;" :: "n"(N) : "memory"); }
template <int N> __device__ __forceinline__ void reg_fence(float (&d)[N]) {
#pragma unroll
  for (int i = 0; i < N; i++) asm volatile("" : "+f"(d[i]) :: "memory");
}

#define F4(d, o) "+f"(d[o]), "+f"(d[o + 1]), "+f"(d[o + 2]), "+f"(d[o + 3])
template <int SC, int TB> __device__ __forceinline__ void wg_rs(float (&d)[8], const uint32_t* a, uint64_t db, int ob) {
  asm volatile("{\n.reg .pred p;\n.reg .b64 b;\nsetp.ne.b32 p, %13, 0;\nadd.s64 b, %12, %15;\n"
    "wgmma.mma_async.sync.aligned.m64n16k16.f32.bf16.bf16 {%0,%1,%2,%3,%4,%5,%6,%7}, {%8,%9,%10,%11}, b, p, 1, 1, %14;\n}\n"
    : F4(d, 0), F4(d, 4) : "r"(a[0]), "r"(a[1]), "r"(a[2]), "r"(a[3]), "l"(db), "n"(SC), "n"(TB), "l"((uint64_t)ob));
}
template <int SC, int TB> __device__ __forceinline__ void wg_rs(float (&d)[12], const uint32_t* a, uint64_t db, int ob) {
  asm volatile("{\n.reg .pred p;\n.reg .b64 b;\nsetp.ne.b32 p, %17, 0;\nadd.s64 b, %16, %19;\n"
    "wgmma.mma_async.sync.aligned.m64n24k16.f32.bf16.bf16 {%0,%1,%2,%3,%4,%5,%6,%7,%8,%9,%10,%11}, {%12,%13,%14,%15}, b, p, 1, 1, %18;\n}\n"
    : F4(d, 0), F4(d, 4), F4(d, 8) : "r"(a[0]), "r"(a[1]), "r"(a[2]), "r"(a[3]), "l"(db), "n"(SC), "n"(TB), "l"((uint64_t)ob));
}
template <int SC, int TB> __device__ __forceinline__ void wg_rs(float (&d)[16], const uint32_t* a, uint64_t db, int ob) {
  asm volatile("{\n.reg .pred p;\n.reg .b64 b;\nsetp.ne.b32 p, %21, 0;\nadd.s64 b, %20, %23;\n"
    "wgmma.mma_async.sync.aligned.m64n32k16.f32.bf16.bf16 {%0,%1,%2,%3,%4,%5,%6,%7,%8,%9,%10,%11,%12,%13,%14,%15}, {%16,%17,%18,%19}, b, p, 1, 1, %22;\n}\n"
    : F4(d, 0), F4(d, 4), F4(d, 8), F4(d, 12) : "r"(a[0]), "r"(a[1]), "r"(a[2]), "r"(a[3]), "l"(db), "n"(SC), "n"(TB), "l"((uint64_t)ob));
}
template <int SC, int TB> __device__ __forceinline__ void wg_rs(float (&d)[28], const uint32_t* a, uint64_t db, int ob) {
  asm volatile("{\n.reg .pred p;\n.reg .b64 b;\nsetp.ne.b32 p, %33, 0;\nadd.s64 b, %32, %35;\n"
    "wgmma.mma_async.sync.aligned.m64n56k16.f32.bf16.bf16 {%0,%1,%2,%3,%4,%5,%6,%7,%8,%9,%10,%11,%12,%13,%14,%15,%16,%17,%18,%19,%20,%21,%22,%23,%24,%25,%26,%27}, {%28,%29,%30,%31}, b, p, 1, 1, %34;\n}\n"
    : F4(d, 0), F4(d, 4), F4(d, 8), F4(d, 12), F4(d, 16), F4(d, 20), F4(d, 24) : "r"(a[0]), "r"(a[1]), "r"(a[2]), "r"(a[3]), "l"(db), "n"(SC), "n"(TB), "l"((uint64_t)ob));
}
template <int SC, int TB> __device__ __forceinline__ void wg_ss(float (&d)[8], uint64_t da, int oa, uint64_t db, int ob) {
  asm volatile("{\n.reg .pred p;\n.reg .b64 a, b;\nsetp.ne.b32 p, %10, 0;\nadd.s64 a, %8, %12;\nadd.s64 b, %9, %13;\n"
    "wgmma.mma_async.sync.aligned.m64n16k16.f32.bf16.bf16 {%0,%1,%2,%3,%4,%5,%6,%7}, a, b, p, 1, 1, 1, %11;\n}\n"
    : F4(d, 0), F4(d, 4) : "l"(da), "l"(db), "n"(SC), "n"(TB), "l"((uint64_t)oa), "l"((uint64_t)ob));
}
template <int SC, int TB> __device__ __forceinline__ void wg_ss(float (&d)[12], uint64_t da, int oa, uint64_t db, int ob) {
  asm volatile("{\n.reg .pred p;\n.reg .b64 a, b;\nsetp.ne.b32 p, %14, 0;\nadd.s64 a, %12, %16;\nadd.s64 b, %13, %17;\n"
    "wgmma.mma_async.sync.aligned.m64n24k16.f32.bf16.bf16 {%0,%1,%2,%3,%4,%5,%6,%7,%8,%9,%10,%11}, a, b, p, 1, 1, 1, %15;\n}\n"
    : F4(d, 0), F4(d, 4), F4(d, 8) : "l"(da), "l"(db), "n"(SC), "n"(TB), "l"((uint64_t)oa), "l"((uint64_t)ob));
}
template <int SC, int TB> __device__ __forceinline__ void wg_ss(float (&d)[16], uint64_t da, int oa, uint64_t db, int ob) {
  asm volatile("{\n.reg .pred p;\n.reg .b64 a, b;\nsetp.ne.b32 p, %18, 0;\nadd.s64 a, %16, %20;\nadd.s64 b, %17, %21;\n"
    "wgmma.mma_async.sync.aligned.m64n32k16.f32.bf16.bf16 {%0,%1,%2,%3,%4,%5,%6,%7,%8,%9,%10,%11,%12,%13,%14,%15}, a, b, p, 1, 1, 1, %19;\n}\n"
    : F4(d, 0), F4(d, 4), F4(d, 8), F4(d, 12) : "l"(da), "l"(db), "n"(SC), "n"(TB), "l"((uint64_t)oa), "l"((uint64_t)ob));
}
template <int SC, int TB> __device__ __forceinline__ void wg_ss(float (&d)[20], uint64_t da, int oa, uint64_t db, int ob) {
  asm volatile("{\n.reg .pred p;\n.reg .b64 a, b;\nsetp.ne.b32 p, %22, 0;\nadd.s64 a, %20, %24;\nadd.s64 b, %21, %25;\n"
    "wgmma.mma_async.sync.aligned.m64n40k16.f32.bf16.bf16 {%0,%1,%2,%3,%4,%5,%6,%7,%8,%9,%10,%11,%12,%13,%14,%15,%16,%17,%18,%19}, a, b, p, 1, 1, 1, %23;\n}\n"
    : F4(d, 0), F4(d, 4), F4(d, 8), F4(d, 12), F4(d, 16) : "l"(da), "l"(db), "n"(SC), "n"(TB), "l"((uint64_t)oa), "l"((uint64_t)ob));
}
template <int SC, int TB> __device__ __forceinline__ void wg_ss(float (&d)[28], uint64_t da, int oa, uint64_t db, int ob) {
  asm volatile("{\n.reg .pred p;\n.reg .b64 a, b;\nsetp.ne.b32 p, %30, 0;\nadd.s64 a, %28, %32;\nadd.s64 b, %29, %33;\n"
    "wgmma.mma_async.sync.aligned.m64n56k16.f32.bf16.bf16 {%0,%1,%2,%3,%4,%5,%6,%7,%8,%9,%10,%11,%12,%13,%14,%15,%16,%17,%18,%19,%20,%21,%22,%23,%24,%25,%26,%27}, a, b, p, 1, 1, 1, %31;\n}\n"
    : F4(d, 0), F4(d, 4), F4(d, 8), F4(d, 12), F4(d, 16), F4(d, 20), F4(d, 24) : "l"(da), "l"(db), "n"(SC), "n"(TB), "l"((uint64_t)oa), "l"((uint64_t)ob));
}

template <int SC> __device__ __forceinline__ void wg_sskk(float (&d)[16], uint64_t da, int oa, uint64_t db, int ob) {
  asm volatile("{\n.reg .pred p;\n.reg .b64 a, b;\nsetp.ne.b32 p, %18, 0;\nadd.s64 a, %16, %19;\nadd.s64 b, %17, %20;\n"
    "wgmma.mma_async.sync.aligned.m64n32k16.f32.bf16.bf16 {%0,%1,%2,%3,%4,%5,%6,%7,%8,%9,%10,%11,%12,%13,%14,%15}, a, b, p, 1, 1, 0, 0;\n}\n"
    : F4(d, 0), F4(d, 4), F4(d, 8), F4(d, 12) : "l"(da), "l"(db), "n"(SC), "l"((uint64_t)oa), "l"((uint64_t)ob));
}

template <int NK> __device__ __forceinline__ void load_afrags(uint32_t* a, uint32_t tile, int w, int lane) {
  int i = lane >> 3, r = lane & 7;
  uint32_t base = tile + ((i >> 1) * 8 + r) * 128 + (((2 * w + (i & 1)) ^ r) << 4);
#pragma unroll
  for (int kk = 0; kk < NK; kk++) ldsm4t(a[4 * kk], a[4 * kk + 1], a[4 * kk + 2], a[4 * kk + 3], base + kk * 2048);
}

constexpr uint32_t Q_WL = 0;
constexpr uint32_t Q_WO = 24576;
constexpr uint32_t Q_OX = Q_WO;
constexpr uint32_t Q_X = 73728;
constexpr uint32_t Q_CS = 10240;
constexpr uint32_t Q_STG = 165888;
constexpr uint32_t Q_OB = 190464;
constexpr uint32_t Q_SIN = 194560;
constexpr uint32_t Q_PX = 204800;
constexpr uint32_t Q_SOUT = Q_PX;
constexpr int Q_KR = 30;
constexpr uint32_t BARS = 228352;
constexpr uint32_t B_CP = BARS;
constexpr uint32_t B_OK = BARS + 408;
constexpr uint32_t B_G0 = BARS + 272;
constexpr uint32_t B_XF = BARS + 72;
constexpr uint32_t B_E = BARS + 224;
constexpr uint32_t B_SM = BARS + 160;
constexpr uint32_t B_O = BARS + 168;
constexpr uint32_t B_P = BARS + 176;
constexpr uint32_t B_OXREADY = BARS + 192;
constexpr uint32_t B_OXFREE = BARS + 200;
constexpr uint32_t B_REF = BARS + 208;
constexpr uint32_t B_AN = BARS + 264;
constexpr uint32_t B_PZ = BARS + 256;
constexpr uint32_t B_RES = BARS + 216;
constexpr uint32_t Q_REF = BARS + 288;
constexpr uint32_t Q_SEL = BARS + 304;
constexpr uint32_t Q_SET = BARS + 360;
constexpr uint32_t SM_BYTES = 4 * 1024, SX_BYTES = 2560, PX_BYTES = 2 * 14 * 128;
constexpr int W_KR = 29;
constexpr uint32_t W_RING = 0;
constexpr uint32_t W_WS = 196608;
constexpr uint32_t W_FT = 0;
constexpr uint32_t W_FO = 18688;
constexpr uint32_t W_Z = 30720;
constexpr uint32_t W_RS = 49152;
constexpr uint32_t W_ST = 28672;
constexpr int CT_A = 2, CT_B = 6, CT_C = 11;
static_assert(36 * CT_C <= 36 * CT_B + 192, "kv stages");
constexpr uint32_t C_U = 256 + 4096;
constexpr uint32_t C_CH = C_U + 64 + 8192 + 96;
constexpr uint32_t B_FULL = BARS;
constexpr uint32_t B_EMPTY = BARS + 128;
constexpr uint32_t B_FT = BARS + 160;
constexpr uint32_t B_RF = BARS + 176;
constexpr uint32_t B_WT = BARS + 248;
constexpr uint32_t W_K1 = BARS + 240;
constexpr uint32_t SMEM_TOTAL = BARS + 512;

struct Params {
  CUtensorMap tm;
  const __nv_bfloat16 *x0, *wq, *wk, *wv, *wo, *mem0, *ck, *cv, *shift, *ssm_k, *ssm_d;
  __nv_bfloat16* out;
  uint4* memx;
  uint64_t d_x, d_wl, d_ring, d_ws;
};

constexpr uint64_t D_QK = mkdesc(Q_STG, 768, 128, 0), D_WO = mkdesc(Q_WO, 16, 1024, 1), D_OB = mkdesc(Q_OB, 128, 2048, 0), D_PX = mkdesc(Q_PX, 128, 768, 0);
constexpr uint64_t D_V = mkdesc(Q_STG, 128, 768, 0);

#define g_flags (g_flagsets + lds1(sb + Q_SET))

__device__ __forceinline__ int rd_cid() { uint32_t v; asm volatile("mov.u32 %0, %%clusterid.x;" : "=r"(v)); return v; }
__device__ __forceinline__ int rd_rank() { uint32_t v; asm volatile("mov.u32 %0, %%cluster_ctarank;" : "=r"(v)); return v; }
__device__ __forceinline__ int rd_lane() { uint32_t v; asm volatile("mov.u32 %0, %%laneid;" : "=r"(v)); return v; }
__device__ __forceinline__ int rd_warp() { uint32_t v; asm volatile("mov.u32 %0, %%tid.x;" : "=r"(v)); return __shfl_sync(0xffffffffu, v >> 5, 0); }

template <int NA>
__device__ __forceinline__ void proj_step(float (&acc)[NA], const uint32_t* a, uint64_t db, uint64_t dwl, int k) {
  const int ob = (k >> 2) * (Q_CS / 16) + (k & 3) * 16;
  if (k == 0) wg_rs<0, 1>(acc, a, db, ob);
  else if (k % 6 != 5) wg_rs<1, 1>(acc, a + 4 * (k - k / 6), db, ob);
  else wg_ss<1, 1>(acc, dwl, 128 * (k / 6), db, ob);
}
__device__ __forceinline__ void stage_groups(uint32_t stl, const uint32_t (&pk)[14]) {
#pragma unroll
  for (int h = 0; h < 2; h++) {
    stsm4(stl + h * 768 + 256, pk[h], pk[2 + h], pk[4 + h], 0);
    stsm4(stl + h * 768 + 6144 + 128, pk[6 + h], pk[8 + h], pk[10 + h], pk[12 + h]);
  }
}
__device__ __forceinline__ void head_main(uint32_t sb, const Params& P) {
  const int lane = threadIdx.x & 31, warp = rd_warp(), w = warp & 3, wg = warp >> 2, rank = rd_rank();
  uint32_t a[4 * Q_KR];
  {
    const int tid = threadIdx.x & 127;
    const __nv_bfloat16* src = (rank == 2 ? P.wv + wg * 64 : (wg ? P.wk : P.wq) + rank * 64) + rd_cid() * 128 + (size_t)(tid >> 3) * 4096 + (tid & 7) * 8;
    const uint32_t so = (tid >> 3) * 128 + (((tid & 7) ^ ((tid >> 3) & 7)) << 4), st = sb + Q_X + wg * (Q_KR * 2048);
    uint4 v[36];
#pragma unroll
    for (int k = 0; k < 36; k++) v[k] = __ldg((const uint4*)(src + (size_t)k * 65536));
#pragma unroll
    for (int k = 0; k < 36; k++) sts4(so + (k % 6 == 5 ? sb + Q_WL + wg * 12288 + (k / 6) * 2048 : st + (k - k / 6) * 2048), v[k]);
    bar_sync_r(9 + wg, wg ? 128 : 224);
    PROF_G(7);
    load_afrags<Q_KR>(a, st, w, lane);
    fence_async_smem();
    bar_arrive<11, 384>();
  }
  cluster_sync();
  PROF_G(8);
  const uint64_t dwl = P.d_wl + wg * 768, dq = D_QK + wg * 384;
  const uint32_t stg = sb + Q_STG + wg * 12288 + 2 * w * 768;
  const uint32_t stm = pin(stg + (lane >> 4) * 6144 + ((lane >> 3) & 1) * 768 + (lane & 7) * 16), stl = pin(stg + lane * 16);
  const uint32_t rel = mapa(sb + B_E, 0), rev = mapa(sb + B_E, 2), sel = pin(threadIdx.x & 127), arm = pin(threadIdx.x - 128 > 8), xfa = pin(sb + B_XF + 8 * lane);
  const uint32_t sx = sb + (wg == rank ? Q_SIN + rank * 4096 : Q_SOUT + 2048), s0 = w ? sx + (2 * w - 1) * 512 : sb + Q_SOUT + wg * 1024, s1 = sx + 2 * w * 512;
  const uint32_t sd0 = pin(s0 + lane * 16), sd1 = pin(s1 + lane * 16), sr = sb + Q_SIN + rank * 4096;
  const int kp = rank == 2 ? KP_V : rank ? KP_1 : KP_0;
  const uint32_t selq = pin(sel | rank >> 1);
    const uint32_t pz = sb + (rank == 2 ? B_SM : B_PZ);
  uint32_t pk[14] = {};
#pragma unroll 1
  for (int t = 0;; t++) {
    const uint32_t par = t & 1;
    uint32_t paused = 0;
    if (t == 0) {
      mbar_wait(sb + B_XF, 0);
    } else {
      float m[12];
#pragma unroll
      for (int c = 0; c < 9; c++) {
        mbar_spin(sb + B_OK + 8 * c, par ^ 1);
        if (c == 0 || c == 3 || c == 8) PROF_W(warp == 0, c == 0 ? 0 : c == 3 ? 1 : 3);
        if (c == 8) mbar_rarrive_if0(selq, rev + 24);
        wg_fence();
#pragma unroll
        for (int k = 4 * c; k < 4 * c + 4; k++) proj_step(m, a, P.d_x, dwl, k);
        if (c == 0) { mbar_expect_if0(arm, xfa, 7168); mbar_rarrive_if0(sel | (rank ^ 2), rel); }
        if (c == XA_V) mbar_rarrive_if0(selq, rel);
        if (c == 3) mbar_rarrive_if0(sel, rev);
        if (c == ST_V && rank == 2) {
          if (t > 1) bar_sync<3, 384>();
          stage_groups(stl, pk);
        }
      }
      wg_commit();
      if (rank == 2 && t < NT) { mbar_wait(sb + B_XF, par); paused = mbar_test(pz, par ^ 1); }
      wg_wait<0>();
      reg_fence(m);
      PROF_W(warp == 0, 2);
      stsm4(stm, pack_bf16(m[0], m[1]), pack_bf16(m[2], m[3]), pack_bf16(m[4], m[5]), pack_bf16(m[6], m[7]));
      stsm2(stm + 128, pack_bf16(m[8], m[9]), pack_bf16(m[10], m[11]));
      if (rank == 2) {
        bar_arrive<1, 384>();
        if (t == NT) break;
        if (paused) mbar_wait(sb + B_RES, par ^ 1);
      } else {
        float s[20];
        bar_sync<1, 256>();
        fence_async_smem();
        wg_fence();
        wg_ss<0, 1>(s, dq, 0, dq, 768);
#pragma unroll
        for (int i = 1; i < 4; i++) wg_ss<1, 1>(s, dq, 96 * i, dq, 768 + 96 * i);
        wg_commit();
        if (t < NT) mbar_wait(sb + B_XF, par);
        wg_wait<0>();
        reg_fence(s);
        if (w < 3) {
          sts4(sd0, make_uint4(pack_bf16(s[0], s[1]), pack_bf16(s[4], s[5]), pack_bf16(s[8], s[9]), pack_bf16(s[12], s[13])));
          if (w != 1) sts1(sd0 + 512, pack_bf16(s[16], s[17]));
          if (w == 0) {
            fence_async_smem();
            __syncwarp();
            if (elect_one()) bulk_s2s(mapa(sr + wg * 1024, 2), s0, 1024, mapa(sb + B_SM, 2));
            __syncwarp();
            PROF_W(wg == 1, 4); PROF_W(wg == 0, 8);
          }
          if (w < 2) sts4(sd1, make_uint4(pack_bf16(s[2], s[3]), pack_bf16(s[6], s[7]), pack_bf16(s[10], s[11]), pack_bf16(s[14], s[15])));
          bar_arrive<8, 224>();
        }
        if (t == NT) break;
      }
    }
    float e[28];
#pragma unroll
    for (int k = 0; k < 36; k++) {
      if (k == 2 && t > 0) {
        mbar_rarrive_if0(sel, rel + 16);
        mbar_expect_if0(arm, xfa - (B_XF - B_CP), 2048);
        mbar_expect_if0(sel | wg, sb + B_G0, 9216);
      }
      if (k % 4 == 0 && k) mbar_wait(sb + B_XF + 2 * k, par);
      if (k == 0) PROF_W(warp == 0, 5);
      if (k % 2 == 0 && k && k <= KP_MAX) {
        mbar_wait_if(paused, pz, sb + B_RES, par ^ 1, k == kp);
      }
      if (k % 4 == 0 || (k % 2 == 0 && k <= KP_MAX)) wg_fence();
      proj_step(e, a, P.d_x + 192, dwl, k);
    }
    wg_commit();
    mbar_wait(sb + B_G0, par);
    wg_wait<0>();
    reg_fence(e);
    PROF_W(warp == 0, 10);
#pragma unroll
    for (int i = 0; i < 14; i++) pk[i] = pack_bf16(e[2 * i], e[2 * i + 1]);
    if (rank != 2) stage_groups(stl, pk);
    PROF_W(warp == 0, 12);
  }
  cluster_sync();
}

__device__ __forceinline__ uint32_t next_tick() {
  uint64_t g0, g1;
  asm volatile("mov.u64 %0, %%globaltimer;" : "=l"(g0) :: "memory");
#pragma unroll 1
  for (int n = 0; n < 8; n++) {
    asm volatile("mov.u64 %0, %%globaltimer;" : "=l"(g1) :: "memory");
    if (__any_sync(0xffffffffu, (uint32_t)g1 != (uint32_t)g0)) break;
  }
  return (uint32_t)g1;
}
__device__ __forceinline__ void wait_ns(uint32_t when) {
  uint32_t c;
  asm volatile("{\n.reg .pred p;\n.reg .b64 g;\n.reg .s32 lo;\nS_%=:\nmov.u64 g, %%globaltimer;\ncvt.u32.u64 lo, g;\nsub.s32 lo, %1, lo;\n"
               "setp.gt.s32 p, lo, 31;\n@p bra.uni S_%=;\nmov.u64 g, %%clock64;\ncvt.u32.u64 %0, g;\nshl.b32 lo, lo, 1;\nadd.s32 %0, %0, lo;\n}" : "=&r"(c) : "r"(when) : "memory");
  spin_until(c - 30);
}
template <bool TAG>
__device__ __forceinline__ uint32_t poll4(uint4 (&v)[4], const uint4* src, uint32_t tag) {
#pragma unroll
  for (int j = 0; j < 4; j++) v[j] = ld_poll(src + j * 32);
  uint32_t n = 0;
  while (__any_sync(0xffffffffu, TAG ? (((v[0].x ^ tag) | (v[1].x ^ tag) | (v[2].x ^ tag) | (v[3].x ^ tag)) & 1) != 0
                                     : (v[0].x == SENT || v[1].x == SENT || v[2].x == SENT || v[3].x == SENT))) {
#pragma unroll
    for (int j = 0; j < 4; j++) if (TAG ? ((v[j].x ^ tag) & 1) != 0 : v[j].x == SENT) v[j] = ld_poll(src + j * 32);
    if (++n > SPIN_LIMIT) __trap();
  }
  return n;
}

template <int STEP>
__device__ __forceinline__ void check_tiles(uint32_t sb, const Params& P, int w, int t) {
  const int lane = rd_lane();
  uint32_t chk = sb + Q_X + w * Q_CS + lane * 32 + (lane >> 2) * 4, bad = 0;
#pragma unroll 1
  for (uint32_t bar = sb + B_CP + 8 * w; bar <= sb + B_CP + 64; bar += 8 * STEP, chk += STEP * Q_CS) {
    uint32_t ok;
    asm volatile("{\n.reg .pred p, q;\n.reg .b32 a, b;\nsetp.eq.u32 q, %4, 0;\n"
                 "W_%=:\nmbarrier.try_wait.parity.shared::cta.b64 p, [%1], %2" CHINT ";\n@!p bra W_%=;\n"
                 "ld.shared.u32 a, [%3];\nld.shared.u32 b, [%3 + 1024];\nsetp.ne.u32 p, a, 0x80008000;\nsetp.ne.and.u32 p, b, 0x80008000, p;\n"
                 "vote.sync.all.pred p, p, 0xFFFFFFFF;\nand.pred q, q, p;\n@q mbarrier.arrive.shared::cta.b64 _, [%1 + %5];\nselp.u32 %0, 1, 0, p;\n}"
                 : "=r"(ok) : "r"(bar), "r"(~t & 1), "r"(chk), "r"(lane), "n"(B_OK - B_CP) : "memory");
    const int c = (bar - sb - B_CP) / 8;
    if (!ok) {
      uint4 v[4];
      poll4<false>(v, P.memx + c * 512 + (t & 1) * 128 + lds1(sb + Q_SEL + 4 * c) / 16 + lane, 0);
#pragma unroll
      for (int j = 0; j < 4; j++) sts4(sb + Q_X + c * Q_CS + j * 512 + lane * 16, v[j]);
      fence_async_smem();
      __syncwarp();
      mbar_arrive_if0(lane, bar + B_OK - B_CP);
      if (t > LAG + 4) sts1(sb + Q_REF + 4, lds1(sb + Q_REF + 4) + 1);
      PROF_OR(7, 1 << c);
      PROF_A(c, 1);
      bad |= c < 6;
    }
    if (STEP == 3) mbar_arrive_if0(lane | (c / 3 != 1 + bad), sb + B_E + 24);
  }
}
__device__ __forceinline__ void load_scores(float (&s)[10], uint32_t sa) {
  const uint4 a = lds4(sa), b = lds4(sa + 4096);
  const uint32_t a4 = lds1(sa + 512), b4 = lds1(sa + 4608);
  s[0] = bf_lo(a.x) + bf_lo(b.x); s[1] = bf_hi(a.x) + bf_hi(b.x); s[2] = bf_lo(a.y) + bf_lo(b.y); s[3] = bf_hi(a.y) + bf_hi(b.y);
  s[4] = bf_lo(a.z) + bf_lo(b.z); s[5] = bf_hi(a.z) + bf_hi(b.z); s[6] = bf_lo(a.w) + bf_lo(b.w); s[7] = bf_hi(a.w) + bf_hi(b.w);
  s[8] = bf_lo(a4) + bf_lo(b4); s[9] = bf_hi(a4) + bf_hi(b4);
}
__device__ __forceinline__ void softmax_num(float (&s)[10]) {
  float mx = fmaxf(fmaxf(fmaxf(s[0], s[1]), fmaxf(s[2], s[3])), fmaxf(fmaxf(s[4], s[5]), fmaxf(s[6], s[7])));
  mx = fmaxf(mx, fmaxf(s[8], s[9]));
  const float m1 = __shfl_xor_sync(0xffffffffu, mx, 1), m2 = __shfl_xor_sync(0xffffffffu, mx, 2), m3 = __shfl_xor_sync(0xffffffffu, mx, 3);
  mx = fmaxf(fmaxf(mx, m1), fmaxf(m2, m3));
  mx *= -SM_SCALE;
#pragma unroll
  for (int i = 0; i < 10; i++) s[i] = ex2(fmaf(s[i], SM_SCALE, mx));
}

__device__ __forceinline__ void wo_tiles(uint32_t sb, const uint32_t (&f)[76], char* d0, uint32_t pg, uint32_t rs, int t) {
  float d[2][8];
  auto mma = [&](int i, int k0, int k1) {
#pragma unroll
    for (int k = k0; k < k1; k++) {
      if (i == 2 && ((k & 1) || k == 6)) wg_ss<1, 0>(d[0], D_WO, 2048 + 128 * k, D_OB, 16 * k);
      else if (k == 0) wg_rs<0, 0>(d[i & 1], f + 32 * i, D_OB, 0);
      else wg_rs<1, 0>(d[i & 1], f + (i < 2 ? 32 * i + 4 * k : 64 + 2 * k), D_OB, 16 * k);
    }
    wg_commit();
  };
  auto put = [&](float (&q)[8]) {
    reg_fence(q);
    st_gpu4((uint4*)d0, (pack_bf16(q[0], q[1]) & ~1u) | ((t - 1) >> 1 & 1), pack_bf16(q[4], q[5]), pack_bf16(q[2], q[3]), pack_bf16(q[6], q[7]));
    __syncwarp();
  };
  wg_fence();
  mma(0, 0, 8);
  mma(1, 0, 8);
  wg_wait<1>();
  put(d[0]);
  PROF_W(threadIdx.x < 288, 14);
  wg_fence();
  mma(2, 0, RS_V);
  d0 += pg & 0xFFFF;
  wg_wait<1>();
  put(d[1]);
  PROF_W(threadIdx.x < 288, 15);
  mma(2, RS_V, 8);
  d0 += pg >> 16;
  wg_wait<1>();
  mbar_arrive_if0(rs, sb + B_RES);
  PROF_W(threadIdx.x < 288, 17);
  wg_wait<0>();
  put(d[0]);
  PROF_W(threadIdx.x < 288, 16);
}
__device__ __forceinline__ void probe_pages(uint32_t sb, const Params& P, int own) {
  const int lane = threadIdx.x & 31;
  const uint32_t first = own ? part_of(blockIdx.x) : 0;
  const uint32_t sel = __shfl_sync(0xffffffffu, near_page(P.memx + first / 16 + (own ? 0 : (blockIdx.x & 63) * 2), own ? 1 : SENT), 0);
  if (lane < (own ? 3 : 10))
    sts1(sb + Q_SEL + 4 * (own ? 9 + lane : lane == 9 ? 12 : lane), ((sel ^ __popc(((first + lane * 8192) ^ first) & 0xB2000)) & 1) * 4096);
}
__device__ __forceinline__ void head_aux(uint32_t sb, const Params& P) {
  const int tid = threadIdx.x & 127, w = rd_warp() & 3, rank = rd_rank(), head = __shfl_sync(0xffffffffu, rd_cid(), 0);
  uint32_t m0[20];
  {
    uint4 a[12], b[12];
#pragma unroll
    for (int j = 0; j < 12; j++) {
      const int u = j;
      const int r = (u & 3) * 32 + (tid >> 2);
      const uint4* src = (const uint4*)(P.wo + (size_t)(head * 128 + (r & 64) + (r & 7) * 8 + ((r >> 3) & 7)) * DM + tile_of(rank, u >> 2) * 64) + (tid & 3) * 2;
      a[j] = __ldg(src); b[j] = __ldg(src + 1);
    }
#pragma unroll
    for (int j = 0; j < 12; j++) {
      const int u = j;
      const int r = (u & 3) * 32 + (tid >> 2);
      const uint32_t dst = sb + Q_WO + (u >> 2) * 16384 + r * 128 + ((((tid & 3) * 2) ^ (r & 7) ^ ((head >> 2) & 1)) << 4);
      sts4(dst, make_uint4(__byte_perm(a[j].x, a[j].y, 0x5410), __byte_perm(a[j].z, a[j].w, 0x5410), __byte_perm(b[j].x, b[j].y, 0x5410), __byte_perm(b[j].z, b[j].w, 0x5410)));
      sts4(dst ^ 16, make_uint4(__byte_perm(a[j].x, a[j].y, 0x7632), __byte_perm(a[j].z, a[j].w, 0x7632), __byte_perm(b[j].x, b[j].y, 0x7632), __byte_perm(b[j].z, b[j].w, 0x7632)));
    }
  }
#pragma unroll
  for (int j = 0; j < 20; j++) {
    const int k = min(tid + (j >> 2) * 128, DM - 1);
    m0[j] = bf2_add(__bfloat16_as_ushort(P.mem0[2 * (j & 3) * DM + k]) | (uint32_t)__bfloat16_as_ushort(P.mem0[(2 * (j & 3) + 1) * DM + k]) << 16, 0);
  }
#pragma unroll
  for (int i = 0; i < 6; i++) sts4(sb + Q_PX + (i * 128 + tid) * 16, make_uint4(0, 0, 0, 0));
  bar_sync<11, 384>();
#pragma unroll
  for (int j = 0; j < 5; j++) {
    const int k = min(tid + j * 128, DM - 1);
    sts4(sb + Q_X + (k >> 6) * Q_CS + (k & 63) * 16, make_uint4(m0[4 * j], m0[4 * j + 1], m0[4 * j + 2], m0[4 * j + 3]));
    sts4(sb + Q_X + (k >> 6) * Q_CS + (k & 63) * 16 + 1024, make_uint4(m0[4 * j], m0[4 * j + 1], m0[4 * j + 2], m0[4 * j + 3]));
  }
#pragma unroll
  for (int i = 0; i < 2; i++) sts4(sb + Q_STG + (i * 16 + (tid >> 3)) * 768 + 640 + (tid & 7) * 16, make_uint4(0, 0, 0, 0));
  fence_async_smem();
  PROF_G(2);
  const uint32_t wa = pin(sb + Q_WO + ((tid >> 4 & 1) * 8 + (tid & 7)) * 128 + (((2 * w + ((tid >> 3) & 1)) ^ (tid & 7)) << 4));
  char* pd = nullptr;
  uint32_t pg = 0;
  auto find_pieces = [&]() {
    const int lane = tid & 31, dcta = (w * 8 + (lane >> 2)) * 3 + rank;
    uint4 f;
    uint32_t n = 0;
    do {
      f = ld_poll((const uint4*)(g_flags + FL_SEL) + dcta);
      if (++n > SPIN_LIMIT) __trap();
    } while (__any_sync(0xffffffffu, !f.x || !f.y || !f.z));
    pd = (char*)P.memx + part_of(dcta) + (head * 4 + (lane & 3) + (f.x - 1) * 256) * 16;
    pg = (8192 + (f.y - f.x) * 4096) | (8192 + (f.z - f.y) * 4096) << 16;
  };
  uint32_t f[76];
  if (rank != 2) {
#pragma unroll
    for (int k = 0; k < 19; k++) ldsm4t(f[4 * k], f[4 * k + 1], f[4 * k + 2], f[4 * k + 3], wa + (k < 16 ? k : 2 * k - 16) * 2048);
    const uint32_t rs = pin(tid);
    cluster_sync();
#pragma unroll 1
    for (int t = 1;; t++) {
      if (t > 1) check_tiles<4>(sb, P, w, t);
      if (w == 0) {
        bar_sync<8, 224>();
        fence_async_smem();
        if (elect_one()) {
          bulk_s2s(mapa(sb + Q_SIN + rank * 4096, rank ^ 1), sb + Q_SOUT + 2048, SX_BYTES, mapa(sb + B_SM, rank ^ 1));
          mbar_arrive(sb + B_SM);
        }
        __syncwarp();
      }
      if (t == NT) break;
      if (t == 1) find_pieces();
      pd = (char*)((uintptr_t)pd ^ 2048);
      if (w == 1) {
        mbar_wait(sb + B_AN, (t - 1) & 1);
        spin_until(rd_clock() + (rank ? PA1_V : PA0_V));
        mbar_arrive_if0(rs - 32, sb + B_PZ);
      }
      mbar_spin(sb + B_O, (t - 1) & 1);
      PROF_W(w == 0, 13);
      wo_tiles(sb, f, pd, pg, rs, t);
      mbar_expect_if0(rs, sb + B_O, 4096);
    }
  } else {
#pragma unroll
    for (int k = 0; k < 8; k++) ldsm4t(f[4 * k], f[4 * k + 1], f[4 * k + 2], f[4 * k + 3], wa + k * 2048);
    cluster_sync();
    find_pieces();
    const int l = w & 1, tile = w >> 1;
    const uint32_t ob = pin(sb + Q_OB + (l ^ ((head >> 1) & 1)) * 2048 + tile * 1024 + (tid >> 2 & 7) * 128 + (tid & 3) * 16);
    const uint32_t ob0 = sb + Q_OB + ((head >> 1) & 1) * 2048;
    const uint32_t sa = pin(sb + Q_SIN + l * 1024 + (tid & 31) * 16);
#pragma unroll 1
    for (int t = 1; t <= NT; t++) {
      const uint32_t par = (t - 1) & 1;
      {
        uint32_t vf[4][10], p[5];
        float s[10], o[4][4];
        const int lane = rd_lane();
        const uint32_t vb = sb + Q_STG + tile * 12288 + l * 6144 + (lane & 7) * 16;
        const uint32_t ax = vb + ((lane >> 3) & 1) * 768 + (lane >> 4) * 128;
        pd = (char*)((uintptr_t)pd ^ 2048);
        bar_sync<1, 384>();
#pragma unroll
        for (int i = 0; i < 4; i++) ldsm4(vf[i][4], vf[i][5], vf[i][6], vf[i][7], ax + i * 1536 + 256);
        ldsm4(vf[0][8], vf[0][9], vf[1][8], vf[1][9], vb + (lane >> 3) * 768 + 512);
        ldsm4(vf[2][8], vf[2][9], vf[3][8], vf[3][9], vb + (lane >> 3) * 768 + 512 + 3072);
#pragma unroll
        for (int i = 0; i < 4; i++) ldsm4(vf[i][0], vf[i][1], vf[i][2], vf[i][3], ax + i * 1536);
        mbar_spin(sb + B_SM, par);
        PROF_W(w == 0, 20);
        if (t < NT) {
          load_scores(s, sa);
          __syncwarp();
          softmax_num(s);
#pragma unroll
          for (int j = 0; j < 5; j++) p[j] = pack_bf16(s[2 * j], s[2 * j + 1]);
          __syncwarp();
          PROF_W(w == 0, 9);
          float z[4] = {0.f, 0.f, 0.f, 0.f};
          const uint32_t ONE = 0x3F803F80u;
          mma16816(z, ONE, ONE, ONE, ONE, p[0], p[1]);
#pragma unroll
          for (int i = 0; i < 4; i++) { o[i][0] = o[i][1] = o[i][2] = o[i][3] = 0.f; mma16816(o[i], vf[i][0], vf[i][1], vf[i][2], vf[i][3], p[0], p[1]); }
#pragma unroll
          for (int k = 8; k < 12; k++) ldsm4t(f[4 * k], f[4 * k + 1], f[4 * k + 2], f[4 * k + 3], wa + k * 2048);
          mma16816(z, ONE, ONE, ONE, ONE, p[2], p[3]);
#pragma unroll
          for (int i = 0; i < 4; i++) mma16816(o[i], vf[i][4], vf[i][5], vf[i][6], vf[i][7], p[2], p[3]);
#pragma unroll
          for (int k = 12; k < 16; k++) ldsm4t(f[4 * k], f[4 * k + 1], f[4 * k + 2], f[4 * k + 3], wa + k * 2048);
          mma1688(z, ONE, ONE, p[4]);
#pragma unroll
          for (int i = 0; i < 4; i++) mma1688(o[i], vf[i][8], vf[i][9], p[4]);
#pragma unroll
          for (int k = 16; k < 19; k++) ldsm4t(f[4 * k], f[4 * k + 1], f[4 * k + 2], f[4 * k + 3], wa + (2 * k - 16) * 2048);
          const float r0 = rcp(z[0]), r1 = rcp(z[1]);
          const uint4 u0 = make_uint4(pack_bf16(o[0][0] * r0, o[0][2] * r0), pack_bf16(o[1][0] * r0, o[1][2] * r0),
                                      pack_bf16(o[2][0] * r0, o[2][2] * r0), pack_bf16(o[3][0] * r0, o[3][2] * r0));
          const uint4 u1 = make_uint4(pack_bf16(o[0][1] * r1, o[0][3] * r1), pack_bf16(o[1][1] * r1, o[1][3] * r1),
                                      pack_bf16(o[2][1] * r1, o[2][3] * r1), pack_bf16(o[3][1] * r1, o[3][3] * r1));
          PROF_W(w == 0, 8);
          sts4(ob, u0);
          sts4(ob + 64, u1);
          bar_sync<5, 160>();
          fence_async_smem();
          PROF_W(w == 0, 13);
          wo_tiles(sb, f, pd, pg, ob ^ ob0, t);
        }
      }
      const int lane = rd_lane();
      mbar_expect_if0(lane | w, sb + B_SM, SM_BYTES);
      if (t < NT) bar_sync<12, 160>();
      {
        float o[3][16];
        const uint32_t ox = sb + Q_OX + 2 * w * 512 + lane * 16;
        const uint64_t dp = D_PX + (t & 1) * 384;
        fence_async_smem();
        mbar_wait(sb + B_P + 8 * (t & 1), ((t - 1) >> 1) & 1);
        PROF_W(w == 0, 7);
#pragma unroll
        for (int j = 0; j < 7; j++) {
          if (j >= 3) {
            const int i = j - 3;
            if (i == 0) mbar_wait(sb + B_OXFREE, par ^ 1);
            if (i < 2) wg_wait<2>(); else if (i == 2) wg_wait<0>();
            if (i == 2 && t < NT) bar_arrive<3, 384>();
            reg_fence(o[i % 3]);
#pragma unroll
            for (int h = 0; h < 2; h++)
              stsm4(ox + i * 4096 + h * 512, pack_bf16(o[i % 3][2 * h], o[i % 3][2 * h + 1]), pack_bf16(o[i % 3][4 + 2 * h], o[i % 3][5 + 2 * h]),
                    pack_bf16(o[i % 3][8 + 2 * h], o[i % 3][9 + 2 * h]), pack_bf16(o[i % 3][12 + 2 * h], o[i % 3][13 + 2 * h]));
          }
          if (j < 4) {
            if (j % 3 == 0) wg_fence();
            wg_sskk<0>(o[j % 3], D_V, (j >> 1) * 384 + (j & 1) * 768, dp, (j >> 1) * 192);
            wg_sskk<1>(o[j % 3], D_V, (j >> 1) * 384 + (j & 1) * 768 + 16, dp, (j >> 1) * 192 + 16);
            wg_sskk<1>(o[j % 3], D_V, (j >> 1) * 384 + (j & 1) * 768 + 32, dp, (j >> 1) * 192 + 32);
            wg_commit();
          }
        }
        mbar_expect_if0(lane | w, sb + B_P + 8 * (t & 1), PX_BYTES);
      }
      fence_async_smem();
      __syncwarp();
      mbar_arrive_if0(lane, sb + B_OXREADY);
      PROF_W(w == 0, 23);
    }
  }
  cluster_sync();
}

__device__ __forceinline__ void softmax_x(uint32_t sb, int w, int rank, int t) {
  float s[10];
  const int lane = rd_lane();
  mbar_wait(sb + B_SM, (t - 1) & 1);
  PROF_W(w == 3, 20);
  load_scores(s, sb + Q_SIN + w * 512 + lane * 16);
  const int last = 8 + 8 * w + (lane >> 2) - 2 * (lane & 3);
#pragma unroll
  for (int i = 2; i < 10; i++) s[i] = (8 * (i >> 1) + (i & 1) <= last) ? s[i] : -INFINITY;
  softmax_num(s);
  float sum = ((s[0] + s[1]) + (s[2] + s[3])) + ((s[4] + s[5]) + (s[6] + s[7])) + (s[8] + s[9]);
  sum += __shfl_xor_sync(0xffffffffu, sum, 1);
  sum += __shfl_xor_sync(0xffffffffu, sum, 2);
  const float r = rcp(sum);
  const uint32_t po = sb + Q_SOUT + 6144 + w * 768;
#pragma unroll
  for (int j = 0; j < 5; j++) sts1(po + lane * 4 + j * 128, pack_bf16(s[2 * j] * r, s[2 * j + 1] * r));
  fence_async_smem();
  __syncwarp();
  if (elect_one()) bulk_s2s(mapa(sb + Q_PX + ((t & 1) * 2 + rank) * 3072 + w * 768, 2), po, 128 * (w + 2), mapa(sb + B_P + 8 * (t & 1), 2));
  __syncwarp();
  PROF_W(w == 3, 22);
}

__device__ __forceinline__ void head_service(uint32_t sb, const Params& P) {
  const int lane = threadIdx.x & 31, rank = rd_rank(), w = rd_warp() & 3, i3 = w - 1;
  const int head = rd_cid(), c = tile_of(rank, i3);
  uint32_t dof = c * 8192 + (lane & 4) * 1024 + (lane & 8) * 128 + head * 32 + (lane & 16) + (lane & 3) * 4;
  uint32_t sof = part_of(blockIdx.x) + i3 * 8192, gof = 0, dly = tile_delay(rank, i3), g0 = 0, c0 = 0, ref = 0;
  asm volatile("barrier.cluster.arrive.aligned;" ::: "memory");
  if (w) {
#pragma unroll 1
    for (int j = 0; j < 16; j++) st_gpu4((uint4*)((char*)P.memx + sof) + j * 32 + lane, 1, 1, 1, 1);
    st_gpu1((uint32_t*)((char*)P.memx + dof), SENT);
    st_gpu1((uint32_t*)((char*)P.memx + dof + 2048), SENT);
    if (w == 2 && lane < 4) st_gpu4(P.memx + (blockIdx.x & 63) * 2 + (lane & 2) * 128 + (lane & 1), SENT, SENT, SENT, SENT);
    bar_sync<9, 224>();
    if (w < 3) probe_pages(sb, P, w == 1);
    if (w == 2 && rank != 2) bar_arrive<13, 64>();
    bar_sync<12, 96>();
    if (w == 1) PROF_G(0);
    sof += __shfl_sync(0xffffffffu, lds1(sb + Q_SEL + 36 + 4 * i3), 0);
    asm volatile("st.release.gpu.global.u32 [%0], %1;" :: "l"(g_flags + FL_SEL + blockIdx.x * 4 + i3), "r"(((sof >> 12) & 1) + 1) : "memory");
    if (w == 1) PROF_G(1);
    gof = c * 8192 + __shfl_sync(0xffffffffu, lds1(sb + Q_SEL + 4 * c), 0);
  }
  asm volatile("barrier.cluster.wait.aligned;" ::: "memory");
#pragma unroll 1
  for (int t = 0; t <= NT; t++) {
    if (w == 0 && rank == 0 && t < NT) {
      const uint32_t* fl = g_flags + FL_XS + t * 32;
      warp_flag_wait(fl + (lane & 1 ? (t >= LAG ? 16 : 0) : (t <= NSEG ? 0 : 16)), 4);
      fence_async_global();
      const char* src = (const char*)g_xs + (size_t)t * 73728;
      if (t > 0) mbar_wait(sb + B_E, (t - 1) & 1);
      PROF_T(24);
      uint32_t at = rd_clock();
#pragma unroll 1
      for (int k = 0; k < 9; k++) {
        if (elect_one()) bulk_g2s_mc(sb + Q_X + 3072 + k * Q_CS, src + 1024 + k * 8192, 7168, sb + B_XF + 8 * k, 7);
        __syncwarp();
        at += t ? XP_V : 0;
        spin_until(at);
      }
      if (t == 0) PROF_G(31);
    }
    if (t > 0) {
    if (rank == 2 && w) { if (t > 1) check_tiles<3>(sb, P, w - 1, t); else mbar_arrive_if0(lane, sb + B_E + 24); }
    if (w == (rank == 2) && t < NT) {
      if (t == 1 && rank != 2) bar_sync<13, 64>();
      const uint32_t* tms = (const uint32_t*)(P.memx + 9 * 512 + lds1(sb + Q_SEL + 48) / 16 + (head >> 4) * 32 + lane) + rank;
      const uint32_t due = ref + D_GX + (D_DUE - rank_delay(rank)) * 9 / 16;
      if (rank == 2) {
        const uint32_t g1 = next_tick(), c1 = rd_clock();
        const uint32_t rate = t > 1 ? __float2uint_rn(65536.f * (g1 - g0) * rcp(c1 - c0)) : 36400;
        g0 = g1; c0 = c1;
        uint4* pub = P.memx + 9 * 512 + (lane & 1) * 256 + (lane & 2) * 16 + head;
        const uint32_t lead = D_RED * rate >> 16, late = D_LATE * rate >> 16, r1 = rank_delay(1) * rate >> 10, r0 = rank_delay(0) * rate >> 10;
        mbar_wait(sb + B_E, (t - 1) & 1);
        PROF_T(4);
        mbar_spin(sb + B_E + 24, (t - 1) & 1);
        uint32_t now = g0 + ((rd_clock() - c0) * rate >> 16);
        now = (now + (t < 3 ? lead + ST0_V : (int)(now + 90 - due) > 0 ? late : lead)) << 6;
        st_gpu4(pub, ((now + r0) & ~255u) | t, ((now + r1) & ~255u) | t, (now & ~255u) | t, 0);
        PROF_T(22);
        PROF_V(true, 1, now >> 6);
      } else {
        mbar_wait(sb + B_CP + 64, (t - 1) & 1);
      }
      if (t > 1) wait_ns(due); else ref = next_tick();
      uint32_t d, n = 0;
      do {
        asm volatile("ld.relaxed.gpu.global.u32 %0, [%1];" : "=r"(d) : "l"(tms) : "memory");
        if (++n > SPIN_LIMIT) __trap();
      } while (__any_sync(0xffffffffu, (d ^ t) & 255));
      ref += __reduce_max_sync(0xffffffffu, (int)(d - (ref << 6))) >> 6;
      sts1(sb + Q_REF, ref);
      __syncwarp();
      mbar_arrive_if0(lane, sb + B_REF);
      PROF_A(13, n);
      PROF_T(19);
    }
    if (w == 2 && rank == 2 && t < NT) {
      mbar_wait(sb + B_SM, (t - 1) & 1);
      mbar_rarrive_if0(lane >> 1, mapa(sb + B_AN, lane & 1));
      bar_sync<5, 160>();
      fence_async_smem();
      if (elect_one()) {
        bulk_s2s(mapa(sb + Q_OB, 1), sb + Q_OB, 4096, mapa(sb + B_O, 1));
        bulk_s2s(mapa(sb + Q_OB, 0), sb + Q_OB, 4096, mapa(sb + B_O, 0));
      }
      __syncwarp();
    }
    if (rank != 2) {
      softmax_x(sb, w, rank, t);
      if (w == 0 && t < NT) bar_arrive<7, 64>();
      mbar_expect_if0(lane | (w - 1), sb + B_SM, SX_BYTES);
    }
    }
    if (w == 0 && rank == 0 && t < NT) {
      if (t > 0) mbar_wait(sb + B_E + 16, (t - 1) & 1);
      if (elect_one()) {
#pragma unroll 1
        for (int k = 0; k < 9; k++) bulk_g2s_mc(sb + Q_X + 2048 + k * Q_CS, (const char*)g_xs + (size_t)t * 73728 + k * 8192, 1024, sb + B_G0, 7);
      }
      __syncwarp();
    }
    if (t == 0) continue;
    if (w == 3) PROF_MID();
    if (w && t < NT) {
      mbar_wait(sb + B_REF, (t - 1) & 1);
      uint32_t when = lds1(sb + Q_REF) + dly;
      sof ^= 2048; dof ^= 2048;
      uint4* src = (uint4*)((char*)P.memx + sof) + lane;
      uint32_t* dst = (uint32_t*)((char*)P.memx + (dof ^ 2048));
      const bool inj = t == LAG && (lane & 8);
      if (t == LAG) {
        const __nv_bfloat16* m0 = P.mem0 + (lane & 3) * 2 * DM + c * 64 + head * 2 + (lane >> 4);
        st_gpu1_if(inj, dst, bf2_add(__bfloat16_as_ushort(m0[0]) | (uint32_t)__bfloat16_as_ushort(m0[DM]) << 16, 0));
      }
      asm volatile("" : "+l"(dst), "+l"(src));
      uint4 v[4];
      wait_ns(when);
      PROF_W(i3 == 0, 18);
      const uint32_t nr = poll4<true>(v, src, (t - 1) >> 1);
      PROF_T(26 + i3);
      const uint32_t z = bf2_add(bf2_add(v[0].z, v[1].z), bf2_add(v[2].z, v[3].z)), u = bf2_add(bf2_add(v[0].w, v[1].w), bf2_add(v[2].w, v[3].w));
      const uint32_t x = bf2_add(bf2_add(v[0].x, v[1].x), bf2_add(v[2].x, v[3].x)), y = bf2_add(bf2_add(v[0].y, v[1].y), bf2_add(v[2].y, v[3].y));
      const uint32_t x2 = bf2_add(bf2_add(x, 0), __shfl_xor_sync(0xffffffffu, z, 16)), y2 = bf2_add(y, __shfl_xor_sync(0xffffffffu, u, 16));
      const uint32_t x3 = bf2_add(x2, __shfl_xor_sync(0xffffffffu, y2, 8));
      st_gpu1_if(!inj, dst, bf2_add(x3, __shfl_xor_sync(0xffffffffu, x3, 4)));
      if (w == 3 && rank == 2) bar_arrive<12, 160>();
      PROF_T(29 + i3);
      PROF_A(10 + i3, nr);
      when += D_GX + min(lds1(sb + Q_REF + 4), 8u) * D_ADAPT;
      if (nr && t > LAG + 3 && dly < tile_delay(rank, i3) + 8 * D_ADAPT) dly += D_ADAPT;
      fence_async_global();
      if (w == 3 && rank != 2) bar_sync<7, 64>();
      wait_ns(when);
      if (elect_one()) bulk_g2s_mc(sb + Q_X + c * Q_CS, (const char*)P.memx + gof + (~t & 1) * 2048, 2048, sb + B_CP + 8 * c, 7);
      __syncwarp();
      if (i3 == 0) PROF_T(21);
      st_gpu1((uint32_t*)((char*)P.memx + dof), SENT);
    }
    if (w == 0 && rank == 2) {
      if (t < NT) mbar_wait(sb + B_XF, t & 1); else warp_flag_wait(g_flags + FL_XS + NT * 32 + 16, 4);
      mbar_wait(sb + B_OXREADY, (t - 1) & 1);
      if (elect_one()) {
        uint4* od = g_ox + (size_t)(t & (OXRING - 1)) * 32768 + head * 512;
        if (t <= NSEG) bulk_s2g(od, sb + Q_OX, 8192);
        if (t > LAG) bulk_s2g(od + 16384, sb + Q_OX + 8192, 8192);
        bulk_commit_wait();
        mbar_arrive(sb + B_OXFREE);
        flag_add(g_flags + FL_OX + t * 32 + head);
      }
      __syncwarp();
      PROF_T(25);
    }
  }
  cluster_sync();
}

__global__ void __cluster_dims__(3, 1, 1) __launch_bounds__(512, 1) head_kernel(const __grid_constant__ Params P) {
  extern __shared__ uint8_t smem_raw[];
  const uint32_t sb = (uint32_t)__cvta_generic_to_shared(smem_raw);
  if ((sb & 0xFFFFFFu) != SB0) __trap();
  asm volatile("griddepcontrol.launch_dependents;");
  if (threadIdx.x < 96) {
    const int i = blockIdx.x * 24 + threadIdx.x % 24, m = threadIdx.x / 24;
    const __nv_bfloat16* p = m == 3 ? P.ssm_k + (size_t)(i >> 2) * SEQ + (i & 3) * 64 : (m == 0 ? P.ck : m == 1 ? P.cv : P.x0) + (size_t)i * 64;
    asm volatile("prefetch.global.L2 [%0];" :: "l"(p));
  } else if (threadIdx.x == 96 && blockIdx.x < 45) {
    asm volatile("prefetch.global.L2 [%0];" :: "l"(blockIdx.x < 36 ? P.shift + blockIdx.x * 64 : P.ssm_d + (blockIdx.x - 36) * 64));
  } else if (threadIdx.x == 97 && blockIdx.x < 72) {
    asm volatile("prefetch.global.L2 [%0];" :: "l"(P.mem0 + blockIdx.x * 64));
  }
  PROF_BEGIN();
  if (threadIdx.x == 416) sts1(sb + Q_SET, (__ldcg(&g_epoch) & 1) * FL_TOTAL);
  const int rank = rd_rank(), wg = rd_warp() >> 2;
  if (threadIdx.x == 448) {
    for (int c = 0; c < 9; c++) { mbar_init(sb + B_CP + 8 * c, 1); mbar_arrive(sb + B_CP + 8 * c); mbar_init(sb + B_OK + 8 * c, 1); mbar_arrive(sb + B_OK + 8 * c); mbar_init(sb + B_XF + 8 * c, 1); mbar_expect(sb + B_XF + 8 * c, 7168); }
    mbar_init(sb + B_E, 6); mbar_init(sb + B_G0, 1); mbar_expect(sb + B_G0, 9216); mbar_init(sb + B_E + 16, 6); mbar_init(sb + B_E + 24, 7);
    mbar_init(sb + B_SM, rank == 2 ? 1 : 2); mbar_init(sb + B_O, 1); mbar_init(sb + B_P, 1); mbar_init(sb + B_P + 8, 1);
    mbar_init(sb + B_REF, 1); mbar_init(sb + B_RES, 1); mbar_init(sb + B_PZ, 1); mbar_init(sb + B_AN, 1); mbar_init(sb + B_OXREADY, 4); mbar_init(sb + B_OXFREE, 1);
    mbar_expect(sb + B_SM, rank == 2 ? SM_BYTES : SX_BYTES); mbar_expect(sb + B_P, PX_BYTES); mbar_expect(sb + B_P + 8, PX_BYTES);
    mbar_expect(sb + B_O, 4096);
    sts1(sb + Q_REF + 4, 0);
    asm volatile("fence.mbarrier_init.release.cluster;" ::: "memory");
  }
  __syncthreads();
  PROF_G(6);
  if (wg < 2) {
    asm volatile("setmaxnreg.inc.sync.aligned.u32 176;");
    head_main(sb, P);
    PROF_END();
  } else if (wg == 2) {
    asm volatile("setmaxnreg.dec.sync.aligned.u32 120;");
    head_aux(sb, P);
    PROF_END();
  } else {
    asm volatile("setmaxnreg.dec.sync.aligned.u32 40;");
    head_service(sb, P);
    PROF_END();
  }
}

__device__ __forceinline__ void tail_gemm(uint32_t sb, const Params& P) {
  const int lane = threadIdx.x & 31, warp = rd_warp(), w = warp & 3, wg = warp >> 2, tid = threadIdx.x & 127;
  uint32_t a[4 * W_KR];
  fence_async_smem();
  if (elect_one()) {
#pragma unroll 1
    for (int k = w; k < 32; k += 4)
      tma_box(k < W_KR ? sb + wg * 65536 + k * 2048 : sb + W_WS + wg * 6144 + (k - W_KR) * 2048, &P.tm, (blockIdx.x % 3) * 192 + wg * 64, (blockIdx.x / 3) * 512 + k * 16, sb + B_WT + 8 * wg);
  }
  __syncwarp();
  mbar_wait(sb + B_WT + 8 * wg, 0);
  load_afrags<W_KR>(a, sb + wg * 65536, w, lane);
  fence_async_smem();
  bar_sync<1, 416>();
  PROF_G(26);
  if (wg == 2) bar_arrive<2, 256>();
  const uint64_t dw = P.d_ws + wg * 384;
  float4* dst0 = g_acc + ((blockIdx.x % 3) * 12 + warp) * 32 + lane;
#pragma unroll 1
  for (int t = 1; t <= NT; t++) {
#pragma unroll 1
    for (int l = t > NSEG; l <= (t > LAG); l++) {
      const int seg = t - 1 - l * LAG, grp = (seg & 1) * 2 + l;
      const uint64_t db = P.d_ring + grp * 2048;
      float acc[16];
      bar_sync_r(2 + wg, 256);
#pragma unroll
      for (int c = 0; c < 4; c++) {
        if (wg == 0) mbar_wait(sb + B_FULL + 32 * grp + 8 * c, (seg >> 1) & 1);
        if (c == 0) PROF_T(6 * l + wg);
        wg_fence();
#pragma unroll
        for (int i = 0; i < 8; i++) {
          if (c == 0 && i == 0) wg_rs<0, 1>(acc, a, db, 0);
          else if (8 * c + i < W_KR) wg_rs<1, 1>(acc, a + 32 * c + 4 * i, db, 512 * c + 64 * i);
          else wg_ss<1, 1>(acc, dw, 128 * (8 * c + i - W_KR), db, 512 * c + 64 * i);
        }
      }
      wg_commit();
      bar_arrive_r(wg == 2 ? 2 : 3 + wg, 256);
      wg_wait<0>();
      reg_fence(acc);
      mbar_arrive_if0(tid, sb + B_EMPTY + 8 * grp);
      float4* dst = dst0 + (size_t)(l * 256 + seg * 4) * 1152;
#pragma unroll
      for (int j = 0; j < 4; j++)
        asm volatile("red.relaxed.gpu.global.add.v4.f32 [%0], {%1,%2,%3,%4};" :: "l"(dst + j * 1152),
                     "f"(acc[4 * j]), "f"(acc[4 * j + 1]), "f"(acc[4 * j + 2]), "f"(acc[4 * j + 3]) : "memory");
      bar_sync_r(5 + wg, 160);
    }
  }
}
__device__ __forceinline__ void tail_service(uint32_t sb) {
  const int lane = threadIdx.x & 31, warp = rd_warp();
  if (warp == 12) bar_sync<1, 416>();
#pragma unroll 1
  for (int t = 1; t <= NT; t++) {
    if (warp == 12) {
      const int h0 = (blockIdx.x / 3) * 4;
      warp_flag_wait(g_flags + FL_OX + t * 32 + h0 + (lane & 3), 1);
      fence_async_global();
#pragma unroll 1
      for (int l = t > NSEG; l <= (t > LAG); l++) {
        const int seg = t - 1 - l * LAG, grp = (seg & 1) * 2 + l;
        const uint4* src = g_ox + (size_t)(t % OXRING) * 32768 + l * 16384 + h0 * 512;
        const uint32_t bar = sb + B_FULL + 32 * grp;
        mbar_wait_lim(sb + B_EMPTY + 8 * grp, ((seg >> 1) & 1) ^ 1);
        mbar_expect_if0(lane > 3, bar + 8 * lane, 8192);
        if (elect_one()) {
#pragma unroll
          for (int j = 0; j < 4; j++) bulk_g2s(sb + W_RING + (grp * 4 + j) * 8192, src + j * 512, 8192, bar + 8 * j);
        }
        __syncwarp();
      }
      PROF_T(12);
      PROF_MID();
    } else {
#pragma unroll 1
      for (int l = t > NSEG; l <= (t > LAG); l++) {
        bar_sync_r(warp - 8, 160);
        if (lane == 0) flag_add(g_flags + FL_ACC + (l * 64 + t - 1 - l * LAG) * 32);
        __syncwarp();
        PROF_T(6 * l + warp - 10);
      }
    }
  }
}

__device__ __forceinline__ void wait_k1(uint32_t sb, int n) {
  uint32_t c = 0;
  while ((int)lds1(sb + W_K1) < n) {
    __nanosleep(64);
    if (++c > SPIN_LIMIT) __trap();
  }
}
__device__ __forceinline__ void tail_finisher(uint32_t sb, const Params& P) {
  const int lane = threadIdx.x & 31, warp = rd_warp(), kind = warp < 12 ? warp / 6 : warp & 1, f = warp - 6 * kind, tg = blockIdx.x & 3;
  if (warp >= 14) {
    const uint32_t set = lds1(sb + Q_SET), ft = sb + W_FO + kind * 576;
    if (tg == 0) for (int i = kind * 32 + lane; i < FL_TOTAL; i += 64) g_flagsets[FL_TOTAL - set + i] = 0;
#pragma unroll 1
    for (int t = 0; t < NSEG; t++) {
      warp_flag_wait(g_flags + FL_ACC + (64 + t) * 32, 72);
      PROF_T(17);
      if (t == 0 && tg == 0 && threadIdx.x == 448) g_epoch = set ? 0 : 1;
      const float4* ac = g_acc + ((size_t)(256 + t * 4 + tg) * 36 + kind * 18) * 32 + lane;
      float4 v[18];
#pragma unroll
      for (int i = 0; i < 18; i++) v[i] = __ldcg(ac + i * 32);
#pragma unroll
      for (int i = 0; i < 9; i++) {
        const uint4 r = lds4(sb + W_RS + (8 + (t & 7)) * 9216 + (kind * 9 + i) * 512 + lane * 16);
        stsm4t(ft + (lane & 7) * 1168 + (lane >> 3) * 16 + 64 * i, bf2_add(r.x, pack_bf16(v[2 * i].x, v[2 * i].y)), bf2_add(r.y, pack_bf16(v[2 * i].z, v[2 * i].w)),
               bf2_add(r.z, pack_bf16(v[2 * i + 1].x, v[2 * i + 1].y)), bf2_add(r.w, pack_bf16(v[2 * i + 1].z, v[2 * i + 1].w)));
      }
      fence_async_smem();
      __syncwarp();
      mbar_arrive_if0(lane, sb + B_RF + 8 * (t & 7));
      wait_k1(sb, min(t + LAG + 1, NSEG));
      if (lane < 8) {
        bulk_s2g(P.out + (size_t)((t * 4 + tg) * 8 + lane) * DM + kind * 288, ft + lane * 1168, 576);
        bulk_commit_wait();
      }
      __syncwarp();
      PROF_T(18);
    }
    return;
  }
  if (warp >= 12) {
    for (int i = kind * 32 + lane; i < 1152; i += 64) sts4(sb + W_Z + i * 16, make_uint4(0, 0, 0, 0));
    fence_async_smem();
    bar_sync<12, 64>();
#pragma unroll 1
    for (int t = -1; t <= NSEG; t++) {
      if (kind == 0 && t + 1 < NSEG) {
        const uint32_t bar = sb + B_FT + 8 * ((t + 1) & 1);
        mbar_expect_if0(lane, bar, 9216);
        __syncwarp();
        if (lane < 8) bulk_g2s(sb + W_FT + ((t + 1) & 1) * 9344 + lane * 1168, P.x0 + (size_t)(((t + 1) * 4 + tg) * 8 + lane) * DM, 1152, bar);
      }
      if (t < 0) continue;
      if (t < NSEG) bar_sync_r(9 + 2 * kind, 224);
      if (lane == 0) {
        flag_add(g_flags + FL_XS + (t + kind * LAG) * 32 + kind * 16);
        if (kind) { sts1(sb + W_K1, t + 1); PROF_T(14); }
        if (kind ? t < NSEG : t < LAG) bulk_s2g(g_acc + (size_t)(kind * 256 + t * 4 + tg) * 1152, sb + W_Z, 18432);
        if (kind && t + LAG < NSEG) bulk_s2g(g_acc + (size_t)((t + LAG) * 4 + tg) * 1152, sb + W_Z, 18432);
        bulk_commit_wait();
      }
      __syncwarp();
      if (kind) PROF_MID();
    }
    return;
  }
  const uint32_t BF_1 = 0x3F803F80u;
  const uint32_t* ys = (const uint32_t*)(g_y + ((tg >> 1) * DM + f * 96 + (lane >> 2)) * 2 + (tg & 1)) + (lane & 3);
  const uint32_t rs = sb + W_RS + f * 1536 + lane * 16;
  uint32_t y[12] = {};
#pragma unroll 1
  for (int t = 0; t < NSEG; t++) {
    uint32_t x[12];
    if (kind == 0) {
      wait_k1(sb, t - 6);
      mbar_wait(sb + B_FT + 8 * (t & 1), (t >> 1) & 1);
#pragma unroll
      for (int i = 0; i < 3; i++)
        ldsm4t(x[4 * i], x[4 * i + 1], x[4 * i + 2], x[4 * i + 3], sb + W_FT + (t & 1) * 9344 + (lane & 7) * 1168 + f * 192 + (lane >> 3) * 16 + 64 * i);
    } else {
      warp_flag_wait(g_flags + FL_ACC + t * 32, 72);
      PROF_T(13);
#pragma unroll
      for (int i = 0; i < 6; i++) {
        const float4 v = __ldcg(g_acc + ((size_t)(t * 4 + tg) * 36 + f * 6 + i) * 32 + lane);
        x[2 * i] = pack_bf16(v.x, v.y); x[2 * i + 1] = pack_bf16(v.z, v.w);
      }
#pragma unroll
      for (int i = 0; i < 3; i++) {
        const uint4 r = lds4(rs + (t & 7) * 9216 + i * 512);
        x[4 * i] = bf2_add(x[4 * i], r.x); x[4 * i + 1] = bf2_add(x[4 * i + 1], r.y); x[4 * i + 2] = bf2_add(x[4 * i + 2], r.z); x[4 * i + 3] = bf2_add(x[4 * i + 3], r.w);
      }
      mbar_wait(sb + B_RF + 8 * (t & 7), ((t >> 3) & 1) ^ 1);
      PROF_T(15);
    }
    {
      if (t == 0) PROF_G(27);
#pragma unroll 1
      for (int pass = 0; pass < 2; pass++) {
        float g[2][4] = {};
#pragma unroll
        for (int i = 0; i < 12; i++) {
          uint32_t u;
          asm volatile("movmatrix.sync.aligned.m8n8.trans.b16 %0, %1;" : "=r"(u) : "r"(x[i]));
          mma1688(g[i & 1], u, BF_1, u);
        }
        const uint32_t st = sb + W_ST + kind * 1024 + pass * 512 + (lane & 3) * 16;
        if ((lane >> 3) == (lane & 3))
          asm volatile("st.shared.v2.f32 [%0], {%1,%2};" :: "r"(st + f * 64 + (lane & 4) * 2), "f"(lane & 4 ? g[0][3] + g[1][3] : g[0][2] + g[1][2]),
                       "f"(lane & 4 ? g[0][1] + g[1][1] : g[0][0] + g[1][0]) : "memory");
        bar_sync_r(8 + 2 * kind, 192);
        float s0 = 0.f, s1 = 0.f, q0 = 0.f, q1 = 0.f;
        if (kind && pass == 0) PROF_T(19);
        if (kind && pass == 1) PROF_T(21);
#pragma unroll
        for (int i = 0; i < 6; i++) {
          const float4 e = lds4f(st + i * 64);
          s0 += e.x; q0 += e.y; s1 += e.z; q1 += e.w;
        }
        s0 *= 1.f / 576.f; s1 *= 1.f / 576.f;
        const float v0 = fmaf(q0, 1.f / 576.f, -s0 * s0), v1 = fmaf(q1, 1.f / 576.f, -s1 * s1);
        const uint32_t nmean = pack_bf16(-s0, -s1), vb = pack_bf16(fmaxf(v0, 0.f), fmaxf(v1, 0.f));
        const uint32_t ve = pack_bf16(bf_lo(vb) + 1e-5f, bf_hi(vb) + 1e-5f), sd = pack_bf16(sqr(bf_lo(ve)), sqr(bf_hi(ve)));
        const float r0 = rcp(bf_lo(sd)), r1 = rcp(bf_hi(sd));
        const uint32_t rh = pack_bf16(r0, r1), rl = pack_bf16(r0 - bf_lo(rh), r1 - bf_hi(rh));
        if (pass == 0 && (t == 0 || t == 4 * CT_A || t == 4 * CT_B || t == 4 * CT_C)) {
          if (t == 0) PROF_G(25);
          warp_flag_wait(g_flags + FL_Y + t * 8, t < 4 * CT_B ? 32 : DM);
          if (t == 0) PROF_G(26);
#pragma unroll
          for (int i = 0; i < 12; i++) y[i] = __ldcg(ys + t * (DM * 16) + i * 64);
        }
        uint32_t* xd = (uint32_t*)(g_xs + (size_t)(t + kind * LAG) * 4608 + (kind * 4 + tg) * 64 + (f * 3 >> 1) * 512 + (f & 1) * 32) + lane;
#pragma unroll
        for (int i = 0; i < 12; i++) {
          const uint32_t d = bf2_add(x[i], nmean), q = bf2_op(d, rh, bf2_mul(d, rl));
          if (pass == 0) x[i] = bf2_add(x[i], bf2_mul(q, y[i]));
          else xd[i < 4 ? i * 32 : i < 8 ? i * 32 + (f & 1) * 1792 : i * 32 + 1792] = q;
        }
        if (pass == 0) {
#pragma unroll
          for (int i = 0; i < 3; i++) sts4(rs + (kind * 8 + (t & 7)) * 9216 + i * 512, make_uint4(x[4 * i], x[4 * i + 1], x[4 * i + 2], x[4 * i + 3]));
        }
        if (kind && pass == 0) PROF_T(20);
        if (kind && pass == 1) PROF_T(22);
      }
      if (kind) PROF_T(16);
      if (t < 3) PROF_G(28 + t);
      bar_sync_r(9 + 2 * kind, 224);
#pragma unroll
      for (int i = 0; i < 12; i++) y[i] = __ldcg(ys + ((t + 1) & 63) * (DM * 16) + i * 64);
    }
  }
}

template <int NP, typename V>
__device__ __forceinline__ void kv_block(uint4 (&o)[2 * NP], const Params& P, int r0, int c0) {
  V kk[11], vv[8];
  uint4 sw[NP];
#pragma unroll
  for (int i = 0; i < NP; i++) sw[i] = __ldg((const uint4*)(P.shift + (c0 + 2 * i) * 4));
#pragma unroll
  for (int i = 0; i < 11; i++) kk[i] = r0 + i >= 3 ? __ldg((const V*)(P.ck + (size_t)(r0 + i - 3) * DM + c0)) : V{};
#pragma unroll
  for (int i = 0; i < 8; i++) vv[i] = __ldg((const V*)(P.cv + (size_t)(r0 + i) * DM + c0));
#pragma unroll
  for (int cp = 0; cp < NP; cp++) {
    const uint32_t wt[4] = {__byte_perm(sw[cp].y, sw[cp].w, 0x7632), __byte_perm(sw[cp].y, sw[cp].w, 0x5410),
                            __byte_perm(sw[cp].x, sw[cp].z, 0x7632), __byte_perm(sw[cp].x, sw[cp].z, 0x5410)};
    uint32_t e[8];
#pragma unroll
    for (int i = 0; i < 8; i++) {
      uint32_t a = bf2_mul(((const uint32_t*)&kk[i])[cp], wt[0]);
#pragma unroll
      for (int j = 1; j < 4; j++) a = bf2_add(a, bf2_mul(((const uint32_t*)&kk[i + j])[cp], wt[j]));
      e[i] = bf2_mul(a, ((const uint32_t*)&vv[i])[cp]);
    }
    o[2 * cp] = make_uint4(__byte_perm(e[0], e[1], 0x5410), __byte_perm(e[2], e[3], 0x5410), __byte_perm(e[4], e[5], 0x5410), __byte_perm(e[6], e[7], 0x5410));
    o[2 * cp + 1] = make_uint4(__byte_perm(e[0], e[1], 0x7632), __byte_perm(e[2], e[3], 0x7632), __byte_perm(e[4], e[5], 0x7632), __byte_perm(e[6], e[7], 0x7632));
  }
}
__device__ __forceinline__ void kv_task(const Params& P, int id) {
  const int lane = threadIdx.x & 31, tq = id / 9, c0 = (id % 9) * 64 + (lane >> 2) * 8;
  uint4 o[8];
  kv_block<4, uint4>(o, P, tq * 32 + (lane & 3) * 8, c0);
#pragma unroll
  for (int c = 0; c < 8; c++) g_kv[((size_t)tq * DM + c0 + c) * 4 + (lane & 3)] = o[c];
}
__device__ __forceinline__ int next_job(uint32_t sb) {
  int j = 0;
  if ((threadIdx.x & 31) == 0) j = atomicAdd(g_flags + FL_KV + 96, 1);
  return __shfl_sync(0xffffffffu, j, 0);
}
__device__ __forceinline__ uint2 lds2_ro(uint32_t a) { uint2 v; asm("ld.shared.v2.u32 {%0,%1}, [%2];" : "=r"(v.x), "=r"(v.y) : "r"(a)); return v; }

template <int T0, int T1>
__device__ __forceinline__ void conv_job(uint32_t sb, const Params& P, int ch, int sets = 1) {
  const int lane = threadIdx.x & 31, w = threadIdx.x >> 5;
  uint32_t ub = sb + w * C_CH, zb = ub + C_U;
  constexpr int NL = (T1 + 1) / 2, NS = T0 == 0 ? 2 : 1;
  constexpr bool CTA = T1 <= CT_B;
  static_assert(T0 > 0 || T1 == 2, "second set: buffer offsets, warps");
  PROF_G(13 + 4 * (T0 == 0 ? 0 : T0 == CT_A ? 1 : 2));
  uint2 q[NS][T1];
  uint32_t dd[NS];
#pragma unroll
  for (int n = 0; n < NS; n++) {
    const int c = n < sets ? ch - n * 128 : ch;
#pragma unroll
    for (int u = 0; u < T1; u++) q[n][u] = __ldg((const uint2*)(P.ssm_k + (size_t)c * SEQ) + u * 32 + lane);
    dd[n] = (uint32_t)__bfloat16_as_ushort(P.ssm_d[c]) * 0x10001u;
  }
  if (CTA) {
#pragma unroll
    for (int tq = w; tq < 4 * T1 * sets; tq += 16) {
      uint4 o[2];
      const int n = T0 == 0 ? tq >> 3 : 0, tgp = (tq - 8 * n) * 4 + (lane & 3), c0 = (lane >> 2) * 2;
      kv_block<1, uint32_t>(o, P, tgp * 8, ch - w + c0 - n * 128);
#pragma unroll
      for (int c = 0; c < 2; c++) {
        sts4(sb + (c0 + c) * C_CH + n * 2048 + 256 + tgp * 16, o[c]);
        if (T0) g_kv[((size_t)tq * DM + ch - w + c0 + c) * 4 + (lane & 3)] = o[c];
      }
    }
    __syncwarp();
  } else {
    uint4 o[NL];
#pragma unroll
    for (int u = 0; u < NL; u++) o[u] = __ldcg(g_kv + ((size_t)(u * 8 + (lane >> 2)) * DM + ch) * 4 + (lane & 3));
#pragma unroll
    for (int u = 0; u < NL; u++) sts4(ub + 256 + (u * 32 + lane) * 16, o[u]);
  }
#pragma unroll
  for (int n = 0; n < NS; n++) {
    if (lane < 16) { sts4(ub + n * 2048 + lane * 16, make_uint4(0, 0, 0, 0)); sts1(zb + n * 4096 + lane * 4, 0); }
#pragma unroll
    for (int u = 0; u < T1; u++) {
      const uint2 k = q[n][u];
      const uint32_t pv = __shfl_sync(0xffffffffu, lane == 31 ? (u ? q[n][u ? u - 1 : 0].y : 0u) : k.y, (lane + 31) & 31);
      sts4(zb + n * 4096 + 64 + (u * 32 + lane) * 16, make_uint4(__byte_perm(k.x, pv, 0x7610), __byte_perm(k.x, k.x, 0x1032),
                                                                __byte_perm(k.y, k.x, 0x7610), __byte_perm(k.y, k.y, 0x1032)));
    }
  }
  if (CTA) __syncthreads(); else __syncwarp();
  PROF_G(14 + 4 * (T0 == 0 ? 0 : T0 == CT_A ? 1 : 2));
#pragma unroll 1
  for (int n = 0; n < sets; n++, ub += 2048, zb += 4096) {
    float acc[T1 - T0][4];
#pragma unroll
    for (int i = 0; i < T1 - T0; i++) acc[i][0] = acc[i][1] = acc[i][2] = acc[i][3] = 0.f;
#pragma unroll(T0 == 0 ? 4 : 1)
    for (int r = 0; r < 8; r++) {
      uint2 b[T1];
      uint32_t ba = ub + 256 - r * 32 + lane * 8, zp = zb + 64 + (16 * r + 2 * (lane >> 2) - 4 * (lane & 3)) * 4;
      asm volatile("" : "+r"(zp), "+r"(ba) :: "memory");
#pragma unroll
      for (int i = 0; i < T1; i++) b[i] = lds2_ro(ba + i * 256);
#pragma unroll
      for (int mu = 0; mu < T1; mu++) {
        const uint2 a01 = lds2_ro(zp + 512 * mu), a23 = lds2_ro(zp + 512 * mu - 8);
#pragma unroll
        for (int i = (mu > T0 ? mu : T0); i < T1; i++) mma16816(acc[i - T0], a01.x, a01.y, a23.x, a23.y, b[i - mu].x, b[i - mu].y);
      }
    }
    PROF_G(15 + 4 * (T0 == 0 ? 0 : T0 == CT_A ? 1 : 2));
#pragma unroll
    for (int i = 0; i < T1 - T0; i++)
#pragma unroll
      for (int e = 0; e < 2; e++) {
        const int col = (T0 + i) * 8 + 2 * (lane & 3) + e;
        ((uint32_t*)g_y)[((size_t)col * DM + ch - n * 128) * 8 + (lane >> 2)] =
            bf2_add(pack_bf16(acc[i][e], acc[i][2 + e]), bf2_mul(lds1(ub + 256 + col * 32 + (lane >> 2) * 4), n ? dd[NS - 1] : dd[0]));
      }
  }
  if (CTA) __syncthreads(); else __syncwarp();
  PROF_G(16 + 4 * (T0 == 0 ? 0 : T0 == CT_A ? 1 : 2));
  if (CTA ? threadIdx.x == 480 && (T0 == 0 || ch < 512) : lane == 0) flag_add(g_flags + FL_Y + T0 * 32);
  __syncwarp();
}

__global__ void __launch_bounds__(512, 1) tail_kernel(const __grid_constant__ Params P) {
  extern __shared__ uint8_t smem_raw[];
  const uint32_t sb = (uint32_t)__cvta_generic_to_shared(smem_raw);
  if (sb != SB0) __trap();
  PROF_BEGIN();
  if (threadIdx.x == 0) {
    for (int c = 0; c < 16; c++) mbar_init(sb + B_FULL + 8 * c, 1);
    for (int c = 0; c < 4; c++) mbar_init(sb + B_EMPTY + 8 * c, 3);
    for (int c = 0; c < 2; c++) mbar_init(sb + B_FT + 8 * c, 1);
    for (int c = 0; c < 8; c++) mbar_init(sb + B_RF + 8 * c, 2);
    for (int c = 0; c < 3; c++) { mbar_init(sb + B_WT + 8 * c, 1); mbar_expect(sb + B_WT + 8 * c, 65536); }
    sts1(sb + W_K1, 0);
    sts1(sb + Q_SET, (__ldcg(&g_epoch) & 1) * FL_TOTAL);
    fence_async_smem();
  }
  const int b = blockIdx.x, w = threadIdx.x >> 5;
  if ((b >> 2) == 6) {
    __syncthreads();
  } else {
    conv_job<0, CT_A>(sb, P, b * 16 + w, b < 32 ? 1 : 2);
    PROF_G(3);
#pragma unroll 1
    for (int g = b; g == b || (g >> 2) == 6; g -= 8) conv_job<CT_A, CT_B>(sb, P, g * 16 + w);
    PROF_G(4);
    constexpr int KV0 = 36 * CT_B, KV1 = KV0 + 192;
    int job = b < 32 ? KV0 + (b - 28) * 16 + w : -1;
#pragma unroll 1
    for (int k = 0; b >= 28; k++) {
      if (job >= 0) {
        kv_task(P, job);
        __syncwarp();
        if ((threadIdx.x & 31) == 0) flag_add(g_flags + FL_KV + (job < KV1 ? 0 : 32));
        if (job + 64 < KV1) { job += 64; continue; }
      }
      if (job < KV1) {
        warp_flag_wait(g_flags + FL_Y + CT_A * 32, 32);
        warp_flag_wait(g_flags + FL_KV, 192);
        spin_until(rd_clock() + (w >> 2) * 2000);
      }
      while ((job = next_job(sb)) < DM) conv_job<CT_B, CT_C>(sb, P, job);
      if (job < DM + 128) PROF_G(6);
      job -= DM - KV1;
      if (job >= 576) break;
    }
    if (b >= 28) {
      warp_flag_wait(g_flags + FL_KV + 32, 576 - KV1);
#pragma unroll 1
      for (job -= 576; job < DM; job = next_job(sb) - DM - (576 - KV1)) conv_job<CT_C, 16>(sb, P, job);
      PROF_G(5);
      PROF_END();
      return;
    }
    __syncwarp();
  }
  if (blockIdx.x >= 24) {
    PROF_G(24);
    tail_finisher(sb, P);
    PROF_END();
    asm volatile("griddepcontrol.wait;" ::: "memory");
  } else if (rd_warp() < 12) {
    asm volatile("setmaxnreg.inc.sync.aligned.u32 160;");
    tail_gemm(sb, P);
    PROF_END();
  } else {
    asm volatile("setmaxnreg.dec.sync.aligned.u32 32;");
    tail_service(sb);
    PROF_END();
  }
}

}

extern "C" void kernel_launch(void* const* d_in, const int* in_sizes, int n_in, void* d_out, int out_size) {
  typedef const __nv_bfloat16* bp;
  Params P;
  P.x0 = (bp)d_in[0]; P.ck = (bp)d_in[1]; P.cv = (bp)d_in[2]; P.shift = (bp)d_in[3]; P.ssm_k = (bp)d_in[4]; P.ssm_d = (bp)d_in[5];
  P.mem0 = (bp)d_in[7]; P.wq = (bp)d_in[8]; P.wk = (bp)d_in[9]; P.wv = (bp)d_in[10]; P.wo = (bp)d_in[11];
  P.out = (__nv_bfloat16*)d_out;
  typedef CUresult (*Encode)(CUtensorMap*, CUtensorMapDataType, cuuint32_t, void*, const cuuint64_t*, const cuuint64_t*, const cuuint32_t*, const cuuint32_t*,
                             CUtensorMapInterleave, CUtensorMapSwizzle, CUtensorMapL2promotion, CUtensorMapFloatOOBfill);
  static Encode encode = nullptr;
  if (!encode) {
    cudaDriverEntryPointQueryResult qr;
    cudaGetDriverEntryPoint("cuTensorMapEncodeTiled", (void**)&encode, cudaEnableDefault, &qr);
  }
  const cuuint64_t dims[2] = {DM, 4096}, pitch[1] = {DM * 2};
  const cuuint32_t box[2] = {64, 16}, es[2] = {1, 1};
  encode(&P.tm, CU_TENSOR_MAP_DATA_TYPE_BFLOAT16, 2, d_in[11], dims, pitch, box, es, CU_TENSOR_MAP_INTERLEAVE_NONE,
         CU_TENSOR_MAP_SWIZZLE_128B, CU_TENSOR_MAP_L2_PROMOTION_NONE, CU_TENSOR_MAP_FLOAT_OOB_FILL_NONE);
  void* xc = nullptr;
  cudaGetSymbolAddress(&xc, g_xchg);
  P.memx = (uint4*)(((uintptr_t)xc + 0x1FFFFF) & ~(uintptr_t)0x1FFFFF);
  P.d_x = mkdesc(Q_X, 128, 1024, 0); P.d_wl = mkdesc(Q_WL, 16, 1024, 1);
  P.d_ring = mkdesc(W_RING, 512, 128, 0); P.d_ws = mkdesc(W_WS, 16, 1024, 1);
  cudaFuncSetAttribute(head_kernel, cudaFuncAttributeMaxDynamicSharedMemorySize, SMEM_TOTAL);
  cudaFuncSetAttribute(tail_kernel, cudaFuncAttributeMaxDynamicSharedMemorySize, SMEM_TOTAL);
  head_kernel<<<96, 512, SMEM_TOTAL>>>(P);
  cudaLaunchConfig_t cfg = {};
  cfg.gridDim = dim3(36); cfg.blockDim = dim3(512); cfg.dynamicSmemBytes = SMEM_TOTAL; cfg.stream = 0;
  cudaLaunchAttribute attr[1];
  attr[0].id = cudaLaunchAttributeProgrammaticStreamSerialization;
  attr[0].val.programmaticStreamSerializationAllowed = 1;
  cfg.attrs = attr; cfg.numAttrs = 1;
  cudaLaunchKernelEx(&cfg, tail_kernel, P);
}
```

```cpp
#include <cuda.h>
#include <cuda_runtime.h>
#include <cuda_bf16.h>
#include <stdint.h>

namespace {

constexpr int SEQ = 2048, DM = 576, NSEG = 64;
#define LAG_V 5
#define RV_V 1950
#define R1_V 380
#define R0_V 590
#define V1_V 80
#define V2_V 200
#define Q1_V 150
#define Q2_V 290
#define SWAP_V 1
#define ST0_V 200
#define GX_V 1130
#define AD_V 0
#define RS_V 5
#define CALIB 0
#define RF_V 2350
#define RL_V 2000
#define PA1_V 500
#define PA0_V 700
#define ST_V 5
#define XA_V 1
#define XP_V 160
#define CTB_V 6
#define CTC_V 11
#define DP_V 2000
#define NFV_V 24
#define KPV_V 16
#define KP1_V 24
#define KP0_V 28
constexpr int LAG = LAG_V;
constexpr int NT = NSEG + LAG;
constexpr int OXRING = 8;
static_assert(LAG >= 3 && LAG < OXRING, "pipeline lag");
constexpr uint32_t D_RED = RV_V;
__host__ __device__ constexpr uint32_t rank_delay(int r) { return r == 2 ? 0 : r ? R1_V : R0_V; }
__host__ __device__ constexpr int tile_of(int r, int i) { return r == 2 ? i : SWAP_V ? (r ? 3 + i + (i >> 1) : 5 + i + (i > 0)) : 6 - 3 * r + i; }
__host__ __device__ constexpr uint32_t tile_delay(int r, int i) { return (i == 0 ? 0 : r == 2 ? (i == 1 ? V1_V : V2_V) : i == 1 ? Q1_V : Q2_V) * 9 / 16; }
constexpr uint32_t D_DUE = RF_V, D_LATE = RL_V;
constexpr uint32_t D_GX = GX_V * 9 / 16, D_ADAPT = AD_V * 9 / 16;
constexpr int KP_V = KPV_V, KP_1 = KP1_V, KP_0 = KP0_V;
constexpr int KP_MAX = KP_0 > KP_1 ? KP_0 : KP_1;
constexpr uint32_t SB0 = 1024;
constexpr float SM_SCALE = 0.08838834764831845f * 1.4426950408889634f;
constexpr uint32_t SENT = 0x80008000u;
constexpr uint32_t SPIN_LIMIT = 1u << 21;

constexpr int FL_XS = 0;
constexpr int FL_ACC = (NT + 2) * 32;
constexpr int FL_OX = FL_ACC + 128 * 32;
constexpr int FL_SEL = FL_OX + (NT + 1) * 32;
constexpr int FL_Y = FL_SEL + 96 * 4;
constexpr int FL_KV = FL_Y + 512;
constexpr int FL_TOTAL = FL_KV + 128;

__device__ __align__(1024) uint4 g_y[256 * DM];
__device__ __align__(1024) uint4 g_kv[256 * DM];
__device__ __align__(1024) float4 g_acc[2 * 256 * 36 * 32];
__device__ __align__(1024) uint4 g_xs[NT * 4608];
__device__ __align__(1024) uint4 g_ox[OXRING * 512 * 8 * 8];
__device__ __align__(1024) uint4 g_xchg[(256 + 256 + 45) * 512];
__host__ __device__ constexpr uint32_t part_of(int cta) { return (cta < 81 ? 12 + cta * 3 : 13 + cta * 3) * 8192; }
__device__ __align__(1024) uint32_t g_flagsets[2 * FL_TOTAL];
__device__ uint32_t g_epoch;
#define PROF_T(slot) do {} while (0)
#define PROF_END() do {} while (0)
#define PROF_W(cond, slot) do {} while (0)
#define PROF_V(cond, slot, val) do { (void)(val); } while (0)
#define PROF_G(slot) do {} while (0)
#define PROF_OR(slot, val) do {} while (0)
#define PROF_A(idx, val) do { (void)(val); } while (0)
#define PROF_BEGIN() do {} while (0)
#define PROF_MID() do {} while (0)

#define CHINT ""
#define HINT ", 100000"
__device__ __forceinline__ uint32_t pack_bf16(float lo, float hi) {
  uint32_t r; asm("cvt.rn.bf16x2.f32 %0, %1, %2;" : "=r"(r) : "f"(hi), "f"(lo)); return r;
}
__device__ __forceinline__ float bf_lo(uint32_t w) { return __uint_as_float(__byte_perm(w, 0, 0x1044)); }
__device__ __forceinline__ float bf_hi(uint32_t w) { return __uint_as_float(w & 0xFFFF0000u); }
__device__ __forceinline__ uint32_t mapa(uint32_t a, uint32_t r) {
  uint32_t o; asm("mapa.shared::cluster.u32 %0, %1, %2;" : "=r"(o) : "r"(a), "r"(r)); return o;
}
__device__ __forceinline__ void mbar_init(uint32_t bar, uint32_t cnt) {
  asm volatile("mbarrier.init.shared::cta.b64 [%0], %1;" :: "r"(bar), "r"(cnt) : "memory");
}
__device__ __forceinline__ void mbar_expect(uint32_t bar, uint32_t bytes) {
  asm volatile("mbarrier.arrive.expect_tx.shared::cta.b64 _, [%0], %1;" :: "r"(bar), "r"(bytes) : "memory");
}
__device__ __forceinline__ void mbar_arrive(uint32_t bar) {
  asm volatile("mbarrier.arrive.shared::cta.b64 _, [%0];" :: "r"(bar) : "memory");
}
__device__ __forceinline__ void mbar_arrive_if0(uint32_t sel, uint32_t bar) {
  asm volatile("{\n.reg .pred p;\nsetp.eq.u32 p, %1, 0;\n@p mbarrier.arrive.shared::cta.b64 _, [%0];\n}" :: "r"(bar), "r"(sel) : "memory");
}
__device__ __forceinline__ void mbar_expect_if0(uint32_t sel, uint32_t bar, uint32_t bytes) {
  asm volatile("{\n.reg .pred p;\nsetp.eq.u32 p, %1, 0;\n@p mbarrier.arrive.expect_tx.shared::cta.b64 _, [%0], %2;\n}" :: "r"(bar), "r"(sel), "r"(bytes) : "memory");
}
__device__ __forceinline__ void mbar_rarrive_if0(uint32_t sel, uint32_t bar) {
  asm volatile("{\n.reg .pred p;\nsetp.eq.u32 p, %1, 0;\n@p mbarrier.arrive.relaxed.cluster.shared::cluster.b64 _, [%0];\n}" :: "r"(bar), "r"(sel) : "memory");
}
__device__ __forceinline__ void mbar_wait_lim(uint32_t bar, uint32_t par) {
  asm volatile(
    "{\n.reg .pred p;\n.reg .u32 c;\nmov.u32 c, 0;\n"
    "W_%=:\n"
    "mbarrier.try_wait.parity.shared::cta.b64 p, [%0], %1;\n"
    "@p bra D_%=;\n"
    "add.u32 c, c, 1;\nsetp.lt.u32 p, c, %2;\n@p bra W_%=;\ntrap;\n"
    "D_%=:\n}\n" :: "r"(bar), "r"(par), "n"(SPIN_LIMIT) : "memory");
}
__device__ __forceinline__ void mbar_wait(uint32_t bar, uint32_t par) {
  asm volatile(
    "{\n.reg .pred p;\n"
    "W_%=:\n"
    "mbarrier.try_wait.parity.shared::cta.b64 p, [%0], %1" HINT ";\n"
    "@!p bra W_%=;\n}\n" :: "r"(bar), "r"(par) : "memory");
}
__device__ __forceinline__ void mbar_spin(uint32_t bar, uint32_t par) {
  asm volatile("{\n.reg .pred p;\nW_%=:\nmbarrier.try_wait.parity.shared::cta.b64 p, [%0], %1;\n@!p bra W_%=;\n}\n" :: "r"(bar), "r"(par) : "memory");
}
__device__ __forceinline__ uint32_t mbar_test(uint32_t bar, uint32_t par) {
  uint32_t r;
  asm volatile("{\n.reg .pred p;\nmbarrier.test_wait.parity.shared::cta.b64 p, [%1], %2;\nselp.u32 %0, 1, 0, p;\n}" : "=r"(r) : "r"(bar), "r"(par) : "memory");
  return __shfl_sync(0xffffffffu, r, 0);
}
__device__ __forceinline__ void mbar_wait_if(uint32_t& done, uint32_t test, uint32_t bar, uint32_t par, bool force) {
  asm volatile(
    "{\n.reg .pred p, q;\nsetp.ne.u32 p, %0, 0;\n@p bra.uni D_%=;\nsetp.ne.u32 q, %4, 0;\n"
    "mbarrier.test_wait.parity.shared::cta.b64 p, [%1], %3;\n"
    "or.pred p, p, q;\n@!p bra D_%=;\n"
    "W_%=:\n"
    "mbarrier.try_wait.parity.shared::cta.b64 p, [%2], %3, 100000;\n"
    "@!p bra W_%=;\nmov.u32 %0, 1;\nD_%=:\n}\n" : "+r"(done) : "r"(test), "r"(bar), "r"(par), "r"((uint32_t)force) : "memory");
}
template <int ID, int N> __device__ __forceinline__ void bar_sync() { asm volatile("bar.sync %0, %1;" :: "n"(ID), "n"(N) : "memory"); }
template <int ID, int N> __device__ __forceinline__ void bar_arrive() { asm volatile("bar.arrive %0, %1;" :: "n"(ID), "n"(N) : "memory"); }
__device__ __forceinline__ void bar_sync_r(int id, int n) { asm volatile("bar.sync %0, %1;" :: "r"(id), "r"(n) : "memory"); }
__device__ __forceinline__ void bar_arrive_r(int id, int n) { asm volatile("bar.arrive %0, %1;" :: "r"(id), "r"(n) : "memory"); }
__device__ __forceinline__ uint32_t pin(uint32_t x) { return __shfl_sync(0xffffffffu, x, threadIdx.x); }
__device__ __forceinline__ void cluster_sync() {
  asm volatile("barrier.cluster.arrive.aligned;\nbarrier.cluster.wait.aligned;" ::: "memory");
}
__device__ __forceinline__ void fence_async_smem() { asm volatile("fence.proxy.async.shared::cta;" ::: "memory"); }
__device__ __forceinline__ void fence_async_global() { asm volatile("fence.proxy.async.global;" ::: "memory"); }
__device__ __forceinline__ uint4 ld_poll(const uint4* p) {
  uint4 v;
  asm volatile("ld.relaxed.gpu.global.v4.u32 {%0,%1,%2,%3}, [%4];" : "=r"(v.x), "=r"(v.y), "=r"(v.z), "=r"(v.w) : "l"(p) : "memory");
  return v;
}
__device__ __forceinline__ uint32_t rd_clock() { uint64_t c; asm volatile("mov.u64 %0, %%clock64;" : "=l"(c) :: "memory"); return (uint32_t)c; }
__device__ __forceinline__ void spin_until(uint32_t when) {
  asm volatile("{\n.reg .pred p;\n.reg .b64 c;\n.reg .s32 lo;\nS_%=:\nmov.u64 c, %%clock64;\ncvt.u32.u64 lo, c;\nsub.s32 lo, lo, %0;\n"
               "setp.lt.s32 p, lo, 0;\n@p bra.uni S_%=;\n}" :: "r"(when) : "memory");
}
__device__ __forceinline__ uint32_t near_page(uint4* pair, uint32_t mark) {
  uint32_t best0 = ~0u, best1 = ~0u;
  const int lane = threadIdx.x & 31;
#pragma unroll 1
  for (int r = 0; r < 8; r++) {
    if (r >= 4 && !(r & 1) && __all_sync(0xffffffffu, max(best0, best1) - min(best0, best1) > 110u && min(best0, best1) < 420u)) break;
    uint32_t t0, t1, v;
    asm volatile("mov.u32 %0, %%clock;" : "=r"(t0) :: "memory");
    asm volatile("{\n.reg .pred p;\nsetp.eq.u32 p, %2, 0;\nmov.u32 %0, 0;\n@p atom.relaxed.gpu.global.exch.b32 %0, [%1], %3;\n}"
                 : "=&r"(v) : "l"(pair + (r & 1) * 256), "r"(lane), "r"(mark) : "memory");
    asm volatile("{\n.reg .pred p;\nsetp.ne.u32 p, %1, 0x9E3779B9;\nmov.u32 %0, %2;\n@p mov.u32 %0, %%clock;\n}" : "=&r"(t1) : "r"(v), "r"(t0 - 1) : "memory");
    if (r & 1) best1 = min(best1, t1 - t0); else best0 = min(best0, t1 - t0);
  }
  return best1 < best0;
}
__device__ __forceinline__ void st_gpu4(uint4* p, uint32_t a, uint32_t b, uint32_t c, uint32_t d) {
  asm volatile("st.relaxed.gpu.global.v4.u32 [%0], {%1,%2,%3,%4};" :: "l"(p), "r"(a), "r"(b), "r"(c), "r"(d) : "memory");
}
__device__ __forceinline__ void st_gpu1(uint32_t* p, uint32_t a) {
  asm volatile("st.relaxed.gpu.global.u32 [%0], %1;" :: "l"(p), "r"(a) : "memory");
}
__device__ __forceinline__ void st_gpu1_if(bool c, uint32_t* p, uint32_t a) {
  asm volatile("{\n.reg .pred p;\nsetp.ne.u32 p, %2, 0;\n@p st.relaxed.gpu.global.u32 [%0], %1;\n}" :: "l"(p), "r"(a), "r"((uint32_t)c) : "memory");
}
__device__ __forceinline__ void warp_flag_wait(const uint32_t* p, uint32_t target) {
  uint32_t v, n = 0;
  do {
    asm volatile("ld.relaxed.gpu.global.u32 %0, [%1];" : "=r"(v) : "l"(p) : "memory");
    if (++n > SPIN_LIMIT) __trap();
  } while (__any_sync(0xffffffffu, v < target));
}
__device__ __forceinline__ void flag_add(uint32_t* p) {
  asm volatile("red.release.gpu.global.add.u32 [%0], 1;" :: "l"(p) : "memory");
}
__device__ __forceinline__ void bulk_g2s(uint32_t dst, const void* src, uint32_t bytes, uint32_t bar) {
  asm volatile("cp.async.bulk.shared::cluster.global.mbarrier::complete_tx::bytes [%0], [%1], %2, [%3];"
               :: "r"(dst), "l"(src), "r"(bytes), "r"(bar) : "memory");
}
__device__ __forceinline__ void bulk_g2s_mc(uint32_t dst, const void* src, uint32_t bytes, uint32_t bar, uint16_t mask) {
  asm volatile("cp.async.bulk.shared::cluster.global.mbarrier::complete_tx::bytes.multicast::cluster [%0], [%1], %2, [%3], %4;"
               :: "r"(dst), "l"(src), "r"(bytes), "r"(bar), "h"(mask) : "memory");
}
__device__ __forceinline__ void tma_box(uint32_t dst, const CUtensorMap* tm, int col, int row, uint32_t bar) {
  asm volatile("cp.async.bulk.tensor.2d.shared::cluster.global.mbarrier::complete_tx::bytes [%0], [%1, {%2, %3}], [%4];"
               :: "r"(dst), "l"(tm), "r"(col), "r"(row), "r"(bar) : "memory");
}
__device__ __forceinline__ void bulk_s2s(uint32_t dst, uint32_t src, uint32_t bytes, uint32_t bar) {
  asm volatile("cp.async.bulk.shared::cluster.shared::cta.mbarrier::complete_tx::bytes [%0], [%1], %2, [%3];"
               :: "r"(dst), "r"(src), "r"(bytes), "r"(bar) : "memory");
}
__device__ __forceinline__ void bulk_s2g(void* dst, uint32_t src, uint32_t bytes) {
  asm volatile("cp.async.bulk.global.shared::cta.bulk_group [%0], [%1], %2;" :: "l"(dst), "r"(src), "r"(bytes) : "memory");
}
__device__ __forceinline__ void bulk_commit_wait() {
  asm volatile("cp.async.bulk.commit_group;\ncp.async.bulk.wait_group 0;" ::: "memory");
}
__device__ __forceinline__ bool elect_one() {
  uint32_t p; asm volatile("{\n.reg .pred p;\nelect.sync _|p, 0xffffffff;\nselp.u32 %0, 1, 0, p;\n}" : "=r"(p)); return p;
}
__device__ __forceinline__ void ldsm4(uint32_t& r0, uint32_t& r1, uint32_t& r2, uint32_t& r3, uint32_t a) {
  asm volatile("ldmatrix.sync.aligned.m8n8.x4.shared.b16 {%0,%1,%2,%3}, [%4];" : "=r"(r0), "=r"(r1), "=r"(r2), "=r"(r3) : "r"(a) : "memory");
}
__device__ __forceinline__ void ldsm4t(uint32_t& r0, uint32_t& r1, uint32_t& r2, uint32_t& r3, uint32_t a) {
  asm volatile("ldmatrix.sync.aligned.m8n8.x4.trans.shared.b16 {%0,%1,%2,%3}, [%4];" : "=r"(r0), "=r"(r1), "=r"(r2), "=r"(r3) : "r"(a) : "memory");
}
__device__ __forceinline__ void stsm4(uint32_t a, uint32_t r0, uint32_t r1, uint32_t r2, uint32_t r3) {
  asm volatile("stmatrix.sync.aligned.m8n8.x4.shared.b16 [%0], {%1,%2,%3,%4};" :: "r"(a), "r"(r0), "r"(r1), "r"(r2), "r"(r3) : "memory");
}
__device__ __forceinline__ void stsm2(uint32_t a, uint32_t r0, uint32_t r1) {
  asm volatile("stmatrix.sync.aligned.m8n8.x2.shared.b16 [%0], {%1,%2};" :: "r"(a), "r"(r0), "r"(r1) : "memory");
}
__device__ __forceinline__ void stsm4t(uint32_t a, uint32_t r0, uint32_t r1, uint32_t r2, uint32_t r3) {
  asm volatile("stmatrix.sync.aligned.m8n8.x4.trans.shared.b16 [%0], {%1,%2,%3,%4};" :: "r"(a), "r"(r0), "r"(r1), "r"(r2), "r"(r3) : "memory");
}
__device__ __forceinline__ float4 lds4f(uint32_t a) {
  float4 v; asm volatile("ld.shared.v4.f32 {%0,%1,%2,%3}, [%4];" : "=f"(v.x), "=f"(v.y), "=f"(v.z), "=f"(v.w) : "r"(a) : "memory"); return v;
}
__device__ __forceinline__ uint4 lds4(uint32_t a) {
  uint4 v; asm volatile("ld.shared.v4.u32 {%0,%1,%2,%3}, [%4];" : "=r"(v.x), "=r"(v.y), "=r"(v.z), "=r"(v.w) : "r"(a) : "memory"); return v;
}
__device__ __forceinline__ uint32_t lds1(uint32_t a) {
  uint32_t v; asm volatile("ld.shared.u32 %0, [%1];" : "=r"(v) : "r"(a) : "memory"); return v;
}
__device__ __forceinline__ void sts4(uint32_t a, uint4 v) {
  asm volatile("st.shared.v4.u32 [%0], {%1,%2,%3,%4};" :: "r"(a), "r"(v.x), "r"(v.y), "r"(v.z), "r"(v.w) : "memory");
}
__device__ __forceinline__ void sts1(uint32_t a, uint32_t v) { asm volatile("st.shared.u32 [%0], %1;" :: "r"(a), "r"(v) : "memory"); }
__device__ __forceinline__ void mma16816(float (&d)[4], uint32_t a0, uint32_t a1, uint32_t a2, uint32_t a3, uint32_t b0, uint32_t b1) {
  asm volatile("mma.sync.aligned.m16n8k16.row.col.f32.bf16.bf16.f32 {%0,%1,%2,%3}, {%4,%5,%6,%7}, {%8,%9}, {%0,%1,%2,%3};"
               : "+f"(d[0]), "+f"(d[1]), "+f"(d[2]), "+f"(d[3]) : "r"(a0), "r"(a1), "r"(a2), "r"(a3), "r"(b0), "r"(b1));
}
__device__ __forceinline__ void mma1688(float (&d)[4], uint32_t a0, uint32_t a1, uint32_t b0) {
  asm volatile("mma.sync.aligned.m16n8k8.row.col.f32.bf16.bf16.f32 {%0,%1,%2,%3}, {%4,%5}, {%6}, {%0,%1,%2,%3};"
               : "+f"(d[0]), "+f"(d[1]), "+f"(d[2]), "+f"(d[3]) : "r"(a0), "r"(a1), "r"(b0));
}
__device__ __forceinline__ float rcp(float x) { float r; asm("rcp.approx.ftz.f32 %0, %1;" : "=f"(r) : "f"(x)); return r; }
__device__ __forceinline__ float sqr(float x) { float r; asm("sqrt.approx.f32 %0, %1;" : "=f"(r) : "f"(x)); return r; }
__device__ __forceinline__ float ex2(float x) { float r; asm("ex2.approx.ftz.f32 %0, %1;" : "=f"(r) : "f"(x)); return r; }

__device__ __forceinline__ uint32_t bf2_op(uint32_t a, uint32_t b, uint32_t c) {
  uint32_t r; asm("fma.rn.bf16x2 %0, %1, %2, %3;" : "=r"(r) : "r"(a), "r"(b), "r"(c)); return r;
}
__device__ __forceinline__ uint32_t bf2_mul(uint32_t a, uint32_t b) {
  uint32_t r; asm("mul.rn.bf16x2 %0, %1, %2;" : "=r"(r) : "r"(a), "r"(b)); return r;
}
__device__ __forceinline__ uint32_t bf2_add(uint32_t a, uint32_t b) {
  uint32_t r; asm("add.rn.bf16x2 %0, %1, %2;" : "=r"(r) : "r"(a), "r"(b)); return r;
}

__host__ __device__ constexpr uint64_t mkdesc(uint32_t off, uint32_t lbo, uint32_t sbo, uint32_t sw) {
  return (uint64_t)((SB0 + off) >> 4) | ((uint64_t)(lbo >> 4) << 16) | ((uint64_t)(sbo >> 4) << 32) | ((uint64_t)sw << 62);
}
__device__ __forceinline__ void wg_fence() { asm volatile("wgmma.fence.sync.aligned;" ::: "memory"); }
__device__ __forceinline__ void wg_commit() { asm volatile("wgmma.commit_group.sync.aligned;" ::: "memory"); }
template <int N> __device__ __forceinline__ void wg_wait() { asm volatile("wgmma.wait_group.sync.aligned %0;" :: "n"(N) : "memory"); }
template <int N> __device__ __forceinline__ void reg_fence(float (&d)[N]) {
#pragma unroll
  for (int i = 0; i < N; i++) asm volatile("" : "+f"(d[i]) :: "memory");
}

#define F4(d, o) "+f"(d[o]), "+f"(d[o + 1]), "+f"(d[o + 2]), "+f"(d[o + 3])
template <int SC, int TB> __device__ __forceinline__ void wg_rs(float (&d)[8], const uint32_t* a, uint64_t db, int ob) {
  asm volatile("{\n.reg .pred p;\n.reg .b64 b;\nsetp.ne.b32 p, %13, 0;\nadd.s64 b, %12, %15;\n"
    "wgmma.mma_async.sync.aligned.m64n16k16.f32.bf16.bf16 {%0,%1,%2,%3,%4,%5,%6,%7}, {%8,%9,%10,%11}, b, p, 1, 1, %14;\n}\n"
    : F4(d, 0), F4(d, 4) : "r"(a[0]), "r"(a[1]), "r"(a[2]), "r"(a[3]), "l"(db), "n"(SC), "n"(TB), "l"((uint64_t)ob));
}
template <int SC, int TB> __device__ __forceinline__ void wg_rs(float (&d)[12], const uint32_t* a, uint64_t db, int ob) {
  asm volatile("{\n.reg .pred p;\n.reg .b64 b;\nsetp.ne.b32 p, %17, 0;\nadd.s64 b, %16, %19;\n"
    "wgmma.mma_async.sync.aligned.m64n24k16.f32.bf16.bf16 {%0,%1,%2,%3,%4,%5,%6,%7,%8,%9,%10,%11}, {%12,%13,%14,%15}, b, p, 1, 1, %18;\n}\n"
    : F4(d, 0), F4(d, 4), F4(d, 8) : "r"(a[0]), "r"(a[1]), "r"(a[2]), "r"(a[3]), "l"(db), "n"(SC), "n"(TB), "l"((uint64_t)ob));
}
template <int SC, int TB> __device__ __forceinline__ void wg_rs(float (&d)[16], const uint32_t* a, uint64_t db, int ob) {
  asm volatile("{\n.reg .pred p;\n.reg .b64 b;\nsetp.ne.b32 p, %21, 0;\nadd.s64 b, %20, %23;\n"
    "wgmma.mma_async.sync.aligned.m64n32k16.f32.bf16.bf16 {%0,%1,%2,%3,%4,%5,%6,%7,%8,%9,%10,%11,%12,%13,%14,%15}, {%16,%17,%18,%19}, b, p, 1, 1, %22;\n}\n"
    : F4(d, 0), F4(d, 4), F4(d, 8), F4(d, 12) : "r"(a[0]), "r"(a[1]), "r"(a[2]), "r"(a[3]), "l"(db), "n"(SC), "n"(TB), "l"((uint64_t)ob));
}
template <int SC, int TB> __device__ __forceinline__ void wg_rs(float (&d)[28], const uint32_t* a, uint64_t db, int ob) {
  asm volatile("{\n.reg .pred p;\n.reg .b64 b;\nsetp.ne.b32 p, %33, 0;\nadd.s64 b, %32, %35;\n"
    "wgmma.mma_async.sync.aligned.m64n56k16.f32.bf16.bf16 {%0,%1,%2,%3,%4,%5,%6,%7,%8,%9,%10,%11,%12,%13,%14,%15,%16,%17,%18,%19,%20,%21,%22,%23,%24,%25,%26,%27}, {%28,%29,%30,%31}, b, p, 1, 1, %34;\n}\n"
    : F4(d, 0), F4(d, 4), F4(d, 8), F4(d, 12), F4(d, 16), F4(d, 20), F4(d, 24) : "r"(a[0]), "r"(a[1]), "r"(a[2]), "r"(a[3]), "l"(db), "n"(SC), "n"(TB), "l"((uint64_t)ob));
}
template <int SC, int TB> __device__ __forceinline__ void wg_ss(float (&d)[8], uint64_t da, int oa, uint64_t db, int ob) {
  asm volatile("{\n.reg .pred p;\n.reg .b64 a, b;\nsetp.ne.b32 p, %10, 0;\nadd.s64 a, %8, %12;\nadd.s64 b, %9, %13;\n"
    "wgmma.mma_async.sync.aligned.m64n16k16.f32.bf16.bf16 {%0,%1,%2,%3,%4,%5,%6,%7}, a, b, p, 1, 1, 1, %11;\n}\n"
    : F4(d, 0), F4(d, 4) : "l"(da), "l"(db), "n"(SC), "n"(TB), "l"((uint64_t)oa), "l"((uint64_t)ob));
}
template <int SC, int TB> __device__ __forceinline__ void wg_ss(float (&d)[12], uint64_t da, int oa, uint64_t db, int ob) {
  asm volatile("{\n.reg .pred p;\n.reg .b64 a, b;\nsetp.ne.b32 p, %14, 0;\nadd.s64 a, %12, %16;\nadd.s64 b, %13, %17;\n"
    "wgmma.mma_async.sync.aligned.m64n24k16.f32.bf16.bf16 {%0,%1,%2,%3,%4,%5,%6,%7,%8,%9,%10,%11}, a, b, p, 1, 1, 1, %15;\n}\n"
    : F4(d, 0), F4(d, 4), F4(d, 8) : "l"(da), "l"(db), "n"(SC), "n"(TB), "l"((uint64_t)oa), "l"((uint64_t)ob));
}
template <int SC, int TB> __device__ __forceinline__ void wg_ss(float (&d)[16], uint64_t da, int oa, uint64_t db, int ob) {
  asm volatile("{\n.reg .pred p;\n.reg .b64 a, b;\nsetp.ne.b32 p, %18, 0;\nadd.s64 a, %16, %20;\nadd.s64 b, %17, %21;\n"
    "wgmma.mma_async.sync.aligned.m64n32k16.f32.bf16.bf16 {%0,%1,%2,%3,%4,%5,%6,%7,%8,%9,%10,%11,%12,%13,%14,%15}, a, b, p, 1, 1, 1, %19;\n}\n"
    : F4(d, 0), F4(d, 4), F4(d, 8), F4(d, 12) : "l"(da), "l"(db), "n"(SC), "n"(TB), "l"((uint64_t)oa), "l"((uint64_t)ob));
}
template <int SC, int TB> __device__ __forceinline__ void wg_ss(float (&d)[20], uint64_t da, int oa, uint64_t db, int ob) {
  asm volatile("{\n.reg .pred p;\n.reg .b64 a, b;\nsetp.ne.b32 p, %22, 0;\nadd.s64 a, %20, %24;\nadd.s64 b, %21, %25;\n"
    "wgmma.mma_async.sync.aligned.m64n40k16.f32.bf16.bf16 {%0,%1,%2,%3,%4,%5,%6,%7,%8,%9,%10,%11,%12,%13,%14,%15,%16,%17,%18,%19}, a, b, p, 1, 1, 1, %23;\n}\n"
    : F4(d, 0), F4(d, 4), F4(d, 8), F4(d, 12), F4(d, 16) : "l"(da), "l"(db), "n"(SC), "n"(TB), "l"((uint64_t)oa), "l"((uint64_t)ob));
}
template <int SC, int TB> __device__ __forceinline__ void wg_ss(float (&d)[28], uint64_t da, int oa, uint64_t db, int ob) {
  asm volatile("{\n.reg .pred p;\n.reg .b64 a, b;\nsetp.ne.b32 p, %30, 0;\nadd.s64 a, %28, %32;\nadd.s64 b, %29, %33;\n"
    "wgmma.mma_async.sync.aligned.m64n56k16.f32.bf16.bf16 {%0,%1,%2,%3,%4,%5,%6,%7,%8,%9,%10,%11,%12,%13,%14,%15,%16,%17,%18,%19,%20,%21,%22,%23,%24,%25,%26,%27}, a, b, p, 1, 1, 1, %31;\n}\n"
    : F4(d, 0), F4(d, 4), F4(d, 8), F4(d, 12), F4(d, 16), F4(d, 20), F4(d, 24) : "l"(da), "l"(db), "n"(SC), "n"(TB), "l"((uint64_t)oa), "l"((uint64_t)ob));
}

template <int SC> __device__ __forceinline__ void wg_sskk(float (&d)[16], uint64_t da, int oa, uint64_t db, int ob) {
  asm volatile("{\n.reg .pred p;\n.reg .b64 a, b;\nsetp.ne.b32 p, %18, 0;\nadd.s64 a, %16, %19;\nadd.s64 b, %17, %20;\n"
    "wgmma.mma_async.sync.aligned.m64n32k16.f32.bf16.bf16 {%0,%1,%2,%3,%4,%5,%6,%7,%8,%9,%10,%11,%12,%13,%14,%15}, a, b, p, 1, 1, 0, 0;\n}\n"
    : F4(d, 0), F4(d, 4), F4(d, 8), F4(d, 12) : "l"(da), "l"(db), "n"(SC), "l"((uint64_t)oa), "l"((uint64_t)ob));
}

template <int NK> __device__ __forceinline__ void load_afrags(uint32_t* a, uint32_t tile, int w, int lane) {
  int i = lane >> 3, r = lane & 7;
  uint32_t base = tile + ((i >> 1) * 8 + r) * 128 + (((2 * w + (i & 1)) ^ r) << 4);
#pragma unroll
  for (int kk = 0; kk < NK; kk++) ldsm4t(a[4 * kk], a[4 * kk + 1], a[4 * kk + 2], a[4 * kk + 3], base + kk * 2048);
}

constexpr uint32_t Q_WL = 0;
constexpr uint32_t Q_WO = 24576;
constexpr uint32_t Q_OX = Q_WO;
constexpr uint32_t Q_X = 73728;
constexpr uint32_t Q_CS = 10240;
constexpr uint32_t Q_STG = 165888;
constexpr uint32_t Q_OB = 190464;
constexpr uint32_t Q_SIN = 194560;
constexpr uint32_t Q_PX = 204800;
constexpr uint32_t Q_SOUT = Q_PX;
constexpr int Q_KR = 30;
constexpr uint32_t BARS = 228352;
constexpr uint32_t B_CP = BARS;
constexpr uint32_t B_OK = BARS + 408;
constexpr uint32_t B_G0 = BARS + 272;
constexpr uint32_t B_XF = BARS + 72;
constexpr uint32_t B_E = BARS + 224;
constexpr uint32_t B_SM = BARS + 160;
constexpr uint32_t B_O = BARS + 168;
constexpr uint32_t B_P = BARS + 176;
constexpr uint32_t B_OXREADY = BARS + 192;
constexpr uint32_t B_OXFREE = BARS + 200;
constexpr uint32_t B_REF = BARS + 208;
constexpr uint32_t B_AN = BARS + 264;
constexpr uint32_t B_PZ = BARS + 256;
constexpr uint32_t B_RES = BARS + 216;
constexpr uint32_t Q_REF = BARS + 288;
constexpr uint32_t Q_SEL = BARS + 304;
constexpr uint32_t Q_SET = BARS + 360;
constexpr uint32_t SM_BYTES = 4 * 1024, SX_BYTES = 2560, PX_BYTES = 2 * 14 * 128;
constexpr int W_KR = 29;
constexpr uint32_t W_RING = 0;
constexpr uint32_t W_WS = 196608;
constexpr uint32_t W_FT = 0;
constexpr uint32_t W_FO = 18688;
constexpr uint32_t W_Z = 30720;
constexpr uint32_t W_RS = 49152;
constexpr uint32_t W_ST = 28672;
constexpr int CT_A = 2, CT_B = CTB_V, CT_C = CTC_V;
static_assert(36 * CT_C <= 36 * CT_B + 192, "kv stages");
constexpr uint32_t C_U = 256 + 4096;
constexpr uint32_t C_CH = C_U + 64 + 8192 + 96;
constexpr uint32_t B_FULL = BARS;
constexpr uint32_t B_EMPTY = BARS + 128;
constexpr uint32_t B_FT = BARS + 160;
constexpr uint32_t B_RF = BARS + 176;
constexpr uint32_t B_WT = BARS + 248;
constexpr uint32_t W_K1 = BARS + 240;
constexpr uint32_t SMEM_TOTAL = BARS + 512;

struct Params {
  CUtensorMap tm;
  const __nv_bfloat16 *x0, *wq, *wk, *wv, *wo, *mem0, *ck, *cv, *shift, *ssm_k, *ssm_d;
  __nv_bfloat16* out;
  uint4* memx;
  uint64_t d_x, d_wl, d_ring, d_ws;
};

constexpr uint64_t D_QK = mkdesc(Q_STG, 768, 128, 0), D_WO = mkdesc(Q_WO, 16, 1024, 1), D_OB = mkdesc(Q_OB, 128, 2048, 0), D_PX = mkdesc(Q_PX, 128, 768, 0);
constexpr uint64_t D_V = mkdesc(Q_STG, 128, 768, 0);

#define g_flags (g_flagsets + lds1(sb + Q_SET))

__device__ __forceinline__ int rd_cid() { uint32_t v; asm volatile("mov.u32 %0, %%clusterid.x;" : "=r"(v)); return v; }
__device__ __forceinline__ int rd_rank() { uint32_t v; asm volatile("mov.u32 %0, %%cluster_ctarank;" : "=r"(v)); return v; }
__device__ __forceinline__ int rd_lane() { uint32_t v; asm volatile("mov.u32 %0, %%laneid;" : "=r"(v)); return v; }
__device__ __forceinline__ int rd_warp() { uint32_t v; asm volatile("mov.u32 %0, %%tid.x;" : "=r"(v)); return __shfl_sync(0xffffffffu, v >> 5, 0); }

template <int NA>
__device__ __forceinline__ void proj_step(float (&acc)[NA], const uint32_t* a, uint64_t db, uint64_t dwl, int k) {
  const int ob = (k >> 2) * (Q_CS / 16) + (k & 3) * 16;
  if (k == 0) wg_rs<0, 1>(acc, a, db, ob);
  else if (k % 6 != 5) wg_rs<1, 1>(acc, a + 4 * (k - k / 6), db, ob);
  else wg_ss<1, 1>(acc, dwl, 128 * (k / 6), db, ob);
}
__device__ __forceinline__ void stage_groups(uint32_t stl, const uint32_t (&pk)[14]) {
#pragma unroll
  for (int h = 0; h < 2; h++) {
    stsm4(stl + h * 768 + 256, pk[h], pk[2 + h], pk[4 + h], 0);
    stsm4(stl + h * 768 + 6144 + 128, pk[6 + h], pk[8 + h], pk[10 + h], pk[12 + h]);
  }
}
__device__ __forceinline__ void head_main(uint32_t sb, const Params& P) {
  const int lane = threadIdx.x & 31, warp = rd_warp(), w = warp & 3, wg = warp >> 2, rank = rd_rank();
  uint32_t a[4 * Q_KR];
  {
    const int tid = threadIdx.x & 127;
    const __nv_bfloat16* src = (rank == 2 ? P.wv + wg * 64 : (wg ? P.wk : P.wq) + rank * 64) + rd_cid() * 128 + (size_t)(tid >> 3) * 4096 + (tid & 7) * 8;
    const uint32_t so = (tid >> 3) * 128 + (((tid & 7) ^ ((tid >> 3) & 7)) << 4), st = sb + Q_X + wg * (Q_KR * 2048);
    uint4 v[36];
#pragma unroll
    for (int k = 0; k < 36; k++) v[k] = __ldg((const uint4*)(src + (size_t)k * 65536));
#pragma unroll
    for (int k = 0; k < 36; k++) sts4(so + (k % 6 == 5 ? sb + Q_WL + wg * 12288 + (k / 6) * 2048 : st + (k - k / 6) * 2048), v[k]);
    bar_sync_r(9 + wg, wg ? 128 : 224);
    PROF_G(7);
    load_afrags<Q_KR>(a, st, w, lane);
    fence_async_smem();
    bar_arrive<11, 384>();
  }
  cluster_sync();
  PROF_G(8);
  const uint64_t dwl = P.d_wl + wg * 768, dq = D_QK + wg * 384;
  const uint32_t stg = sb + Q_STG + wg * 12288 + 2 * w * 768;
  const uint32_t stm = pin(stg + (lane >> 4) * 6144 + ((lane >> 3) & 1) * 768 + (lane & 7) * 16), stl = pin(stg + lane * 16);
  const uint32_t rel = mapa(sb + B_E, 0), rev = mapa(sb + B_E, 2), sel = pin(threadIdx.x & 127), arm = pin(threadIdx.x - 128 > 8), xfa = pin(sb + B_XF + 8 * lane);
  const uint32_t sx = sb + (wg == rank ? Q_SIN + rank * 4096 : Q_SOUT + 2048), s0 = w ? sx + (2 * w - 1) * 512 : sb + Q_SOUT + wg * 1024, s1 = sx + 2 * w * 512;
  const uint32_t sd0 = pin(s0 + lane * 16), sd1 = pin(s1 + lane * 16), sr = sb + Q_SIN + rank * 4096;
  const int kp = rank == 2 ? KP_V : rank ? KP_1 : KP_0;
  const uint32_t selq = pin(sel | rank >> 1);
    const uint32_t pz = sb + (rank == 2 ? B_SM : B_PZ);
  uint32_t pk[14] = {};
#pragma unroll 1
  for (int t = 0;; t++) {
    const uint32_t par = t & 1;
    uint32_t paused = 0;
    if (t == 0) {
      mbar_wait(sb + B_XF, 0);
    } else {
      float m[12];
#pragma unroll
      for (int c = 0; c < 9; c++) {
        mbar_spin(sb + B_OK + 8 * c, par ^ 1);
        if (c == 0 || c == 3 || c == 8) PROF_W(warp == 0, c == 0 ? 0 : c == 3 ? 1 : 3);
        if (c == 8) mbar_rarrive_if0(selq, rev + 24);
        wg_fence();
#pragma unroll
        for (int k = 4 * c; k < 4 * c + 4; k++) proj_step(m, a, P.d_x, dwl, k);
        if (c == 0) { mbar_expect_if0(arm, xfa, 7168); mbar_rarrive_if0(sel | (rank ^ 2), rel); }
        if (c == XA_V) mbar_rarrive_if0(selq, rel);
        if (c == 3) mbar_rarrive_if0(sel, rev);
        if (c == ST_V && rank == 2) {
          if (t > 1) bar_sync<3, 384>();
          stage_groups(stl, pk);
        }
      }
      wg_commit();
      if (rank == 2 && t < NT) { mbar_wait(sb + B_XF, par); paused = mbar_test(pz, par ^ 1); }
      wg_wait<0>();
      reg_fence(m);
      PROF_W(warp == 0, 2);
      stsm4(stm, pack_bf16(m[0], m[1]), pack_bf16(m[2], m[3]), pack_bf16(m[4], m[5]), pack_bf16(m[6], m[7]));
      stsm2(stm + 128, pack_bf16(m[8], m[9]), pack_bf16(m[10], m[11]));
      if (rank == 2) {
        bar_arrive<1, 384>();
        if (t == NT) break;
        if (paused) mbar_wait(sb + B_RES, par ^ 1);
      } else {
        float s[20];
        bar_sync<1, 256>();
        fence_async_smem();
        wg_fence();
        wg_ss<0, 1>(s, dq, 0, dq, 768);
#pragma unroll
        for (int i = 1; i < 4; i++) wg_ss<1, 1>(s, dq, 96 * i, dq, 768 + 96 * i);
        wg_commit();
        if (t < NT) mbar_wait(sb + B_XF, par);
        wg_wait<0>();
        reg_fence(s);
        if (w < 3) {
          sts4(sd0, make_uint4(pack_bf16(s[0], s[1]), pack_bf16(s[4], s[5]), pack_bf16(s[8], s[9]), pack_bf16(s[12], s[13])));
          if (w != 1) sts1(sd0 + 512, pack_bf16(s[16], s[17]));
          if (w == 0) {
            fence_async_smem();
            __syncwarp();
            if (elect_one()) bulk_s2s(mapa(sr + wg * 1024, 2), s0, 1024, mapa(sb + B_SM, 2));
            __syncwarp();
            PROF_W(wg == 1, 4); PROF_W(wg == 0, 8);
          }
          if (w < 2) sts4(sd1, make_uint4(pack_bf16(s[2], s[3]), pack_bf16(s[6], s[7]), pack_bf16(s[10], s[11]), pack_bf16(s[14], s[15])));
          bar_arrive<8, 224>();
        }
        if (t == NT) break;
      }
    }
    float e[28];
#pragma unroll
    for (int k = 0; k < 36; k++) {
      if (k == 2 && t > 0) {
        mbar_rarrive_if0(sel, rel + 16);
        mbar_expect_if0(arm, xfa - (B_XF - B_CP), 2048);
        mbar_expect_if0(sel | wg, sb + B_G0, 9216);
      }
      if (k % 4 == 0 && k) mbar_wait(sb + B_XF + 2 * k, par);
      if (k == 0) PROF_W(warp == 0, 5);
      if (k % 2 == 0 && k && k <= KP_MAX) {
        mbar_wait_if(paused, pz, sb + B_RES, par ^ 1, k == kp);
      }
      if (k % 4 == 0 || (k % 2 == 0 && k <= KP_MAX)) wg_fence();
      proj_step(e, a, P.d_x + 192, dwl, k);
    }
    wg_commit();
    mbar_wait(sb + B_G0, par);
    wg_wait<0>();
    reg_fence(e);
    PROF_W(warp == 0, 10);
#pragma unroll
    for (int i = 0; i < 14; i++) pk[i] = pack_bf16(e[2 * i], e[2 * i + 1]);
    if (rank != 2) stage_groups(stl, pk);
    PROF_W(warp == 0, 12);
  }
  cluster_sync();
}

__device__ __forceinline__ uint32_t next_tick() {
  uint64_t g0, g1;
  asm volatile("mov.u64 %0, %%globaltimer;" : "=l"(g0) :: "memory");
#pragma unroll 1
  for (int n = 0; n < 8; n++) {
    asm volatile("mov.u64 %0, %%globaltimer;" : "=l"(g1) :: "memory");
    if (__any_sync(0xffffffffu, (uint32_t)g1 != (uint32_t)g0)) break;
  }
  return (uint32_t)g1;
}
__device__ __forceinline__ void wait_ns(uint32_t when) {
  uint32_t c;
  asm volatile("{\n.reg .pred p;\n.reg .b64 g;\n.reg .s32 lo;\nS_%=:\nmov.u64 g, %%globaltimer;\ncvt.u32.u64 lo, g;\nsub.s32 lo, %1, lo;\n"
               "setp.gt.s32 p, lo, 31;\n@p bra.uni S_%=;\nmov.u64 g, %%clock64;\ncvt.u32.u64 %0, g;\nshl.b32 lo, lo, 1;\nadd.s32 %0, %0, lo;\n}" : "=&r"(c) : "r"(when) : "memory");
  spin_until(c - 30);
}
template <bool TAG>
__device__ __forceinline__ uint32_t poll4(uint4 (&v)[4], const uint4* src, uint32_t tag) {
#pragma unroll
  for (int j = 0; j < 4; j++) v[j] = ld_poll(src + j * 32);
  uint32_t n = 0;
  while (__any_sync(0xffffffffu, TAG ? (((v[0].x ^ tag) | (v[1].x ^ tag) | (v[2].x ^ tag) | (v[3].x ^ tag)) & 1) != 0
                                     : (v[0].x == SENT || v[1].x == SENT || v[2].x == SENT || v[3].x == SENT))) {
#pragma unroll
    for (int j = 0; j < 4; j++) if (TAG ? ((v[j].x ^ tag) & 1) != 0 : v[j].x == SENT) v[j] = ld_poll(src + j * 32);
    if (++n > SPIN_LIMIT) __trap();
  }
  return n;
}

template <int STEP>
__device__ __forceinline__ void check_tiles(uint32_t sb, const Params& P, int w, int t) {
  const int lane = rd_lane();
  uint32_t chk = sb + Q_X + w * Q_CS + lane * 32 + (lane >> 2) * 4, bad = 0;
#pragma unroll 1
  for (uint32_t bar = sb + B_CP + 8 * w; bar <= sb + B_CP + 64; bar += 8 * STEP, chk += STEP * Q_CS) {
    uint32_t ok;
    asm volatile("{\n.reg .pred p, q;\n.reg .b32 a, b;\nsetp.eq.u32 q, %4, 0;\n"
                 "W_%=:\nmbarrier.try_wait.parity.shared::cta.b64 p, [%1], %2" CHINT ";\n@!p bra W_%=;\n"
                 "ld.shared.u32 a, [%3];\nld.shared.u32 b, [%3 + 1024];\nsetp.ne.u32 p, a, 0x80008000;\nsetp.ne.and.u32 p, b, 0x80008000, p;\n"
                 "vote.sync.all.pred p, p, 0xFFFFFFFF;\nand.pred q, q, p;\n@q mbarrier.arrive.shared::cta.b64 _, [%1 + %5];\nselp.u32 %0, 1, 0, p;\n}"
                 : "=r"(ok) : "r"(bar), "r"(~t & 1), "r"(chk), "r"(lane), "n"(B_OK - B_CP) : "memory");
    const int c = (bar - sb - B_CP) / 8;
    if (!ok) {
      uint4 v[4];
      poll4<false>(v, P.memx + c * 512 + (t & 1) * 128 + lds1(sb + Q_SEL + 4 * c) / 16 + lane, 0);
#pragma unroll
      for (int j = 0; j < 4; j++) sts4(sb + Q_X + c * Q_CS + j * 512 + lane * 16, v[j]);
      fence_async_smem();
      __syncwarp();
      mbar_arrive_if0(lane, bar + B_OK - B_CP);
      if (t > LAG + 4) sts1(sb + Q_REF + 4, lds1(sb + Q_REF + 4) + 1);
      PROF_OR(7, 1 << c);
      PROF_A(c, 1);
      bad |= c < 6;
    }
    if (STEP == 3) mbar_arrive_if0(lane | (c / 3 != 1 + bad), sb + B_E + 24);
  }
}
__device__ __forceinline__ void load_scores(float (&s)[10], uint32_t sa) {
  const uint4 a = lds4(sa), b = lds4(sa + 4096);
  const uint32_t a4 = lds1(sa + 512), b4 = lds1(sa + 4608);
  s[0] = bf_lo(a.x) + bf_lo(b.x); s[1] = bf_hi(a.x) + bf_hi(b.x); s[2] = bf_lo(a.y) + bf_lo(b.y); s[3] = bf_hi(a.y) + bf_hi(b.y);
  s[4] = bf_lo(a.z) + bf_lo(b.z); s[5] = bf_hi(a.z) + bf_hi(b.z); s[6] = bf_lo(a.w) + bf_lo(b.w); s[7] = bf_hi(a.w) + bf_hi(b.w);
  s[8] = bf_lo(a4) + bf_lo(b4); s[9] = bf_hi(a4) + bf_hi(b4);
}
__device__ __forceinline__ void softmax_num(float (&s)[10]) {
  float mx = fmaxf(fmaxf(fmaxf(s[0], s[1]), fmaxf(s[2], s[3])), fmaxf(fmaxf(s[4], s[5]), fmaxf(s[6], s[7])));
  mx = fmaxf(mx, fmaxf(s[8], s[9]));
  const float m1 = __shfl_xor_sync(0xffffffffu, mx, 1), m2 = __shfl_xor_sync(0xffffffffu, mx, 2), m3 = __shfl_xor_sync(0xffffffffu, mx, 3);
  mx = fmaxf(fmaxf(mx, m1), fmaxf(m2, m3));
  mx *= -SM_SCALE;
#pragma unroll
  for (int i = 0; i < 10; i++) s[i] = ex2(fmaf(s[i], SM_SCALE, mx));
}

template <int NF>
__device__ __forceinline__ void wo_tiles(uint32_t sb, const uint32_t (&f)[76], char* d0, uint32_t pg, uint32_t rs, int t) {
  float d[2][8];
  auto mma = [&](int i, int k0, int k1) {
#pragma unroll
    for (int k = k0; k < k1; k++) {
      if (8 * i + k >= NF && k == 0) wg_ss<0, 0>(d[i & 1], D_WO, 1024 * i, D_OB, 0);
      else if (8 * i + k >= NF || (i == 2 && ((k & 1) || k == 6))) wg_ss<1, 0>(d[i & 1], D_WO, 1024 * i + 128 * k, D_OB, 16 * k);
      else if (k == 0) wg_rs<0, 0>(d[i & 1], f + 32 * i, D_OB, 0);
      else wg_rs<1, 0>(d[i & 1], f + (i < 2 ? 32 * i + 4 * k : 64 + 2 * k), D_OB, 16 * k);
    }
    wg_commit();
  };
  auto put = [&](float (&q)[8]) {
    reg_fence(q);
    st_gpu4((uint4*)d0, (pack_bf16(q[0], q[1]) & ~1u) | ((t - 1) >> 1 & 1), pack_bf16(q[4], q[5]), pack_bf16(q[2], q[3]), pack_bf16(q[6], q[7]));
    __syncwarp();
  };
  wg_fence();
  mma(0, 0, 8);
  mma(1, 0, 8);
  wg_wait<1>();
  put(d[0]);
  PROF_W(threadIdx.x < 288, 14);
  wg_fence();
  mma(2, 0, RS_V);
  d0 += pg & 0xFFFF;
  wg_wait<1>();
  put(d[1]);
  PROF_W(threadIdx.x < 288, 15);
  mma(2, RS_V, 8);
  d0 += pg >> 16;
  wg_wait<1>();
  mbar_arrive_if0(rs, sb + B_RES);
  PROF_W(threadIdx.x < 288, 17);
  wg_wait<0>();
  put(d[0]);
  PROF_W(threadIdx.x < 288, 16);
}
__device__ __forceinline__ void probe_pages(uint32_t sb, const Params& P, int own) {
  const int lane = threadIdx.x & 31;
  const uint32_t first = own ? part_of(blockIdx.x) : 0;
  const uint32_t sel = __shfl_sync(0xffffffffu, near_page(P.memx + first / 16 + (own ? 0 : (blockIdx.x & 63) * 2), own ? 1 : SENT), 0);
  if (lane < (own ? 3 : 10))
    sts1(sb + Q_SEL + 4 * (own ? 9 + lane : lane == 9 ? 12 : lane), ((sel ^ __popc(((first + lane * 8192) ^ first) & 0xB2000)) & 1) * 4096);
}
__device__ __forceinline__ void head_aux(uint32_t sb, const Params& P) {
  const int tid = threadIdx.x & 127, w = rd_warp() & 3, rank = rd_rank(), head = __shfl_sync(0xffffffffu, rd_cid(), 0);
  uint32_t m0[20];
  {
    uint4 a[12], b[12];
#pragma unroll
    for (int j = 0; j < 12; j++) {
      const int u = j;
      const int r = (u & 3) * 32 + (tid >> 2);
      const uint4* src = (const uint4*)(P.wo + (size_t)(head * 128 + (r & 64) + (r & 7) * 8 + ((r >> 3) & 7)) * DM + tile_of(rank, u >> 2) * 64) + (tid & 3) * 2;
      a[j] = __ldg(src); b[j] = __ldg(src + 1);
    }
#pragma unroll
    for (int j = 0; j < 12; j++) {
      const int u = j;
      const int r = (u & 3) * 32 + (tid >> 2);
      const uint32_t dst = sb + Q_WO + (u >> 2) * 16384 + r * 128 + ((((tid & 3) * 2) ^ (r & 7) ^ ((head >> 2) & 1)) << 4);
      sts4(dst, make_uint4(__byte_perm(a[j].x, a[j].y, 0x5410), __byte_perm(a[j].z, a[j].w, 0x5410), __byte_perm(b[j].x, b[j].y, 0x5410), __byte_perm(b[j].z, b[j].w, 0x5410)));
      sts4(dst ^ 16, make_uint4(__byte_perm(a[j].x, a[j].y, 0x7632), __byte_perm(a[j].z, a[j].w, 0x7632), __byte_perm(b[j].x, b[j].y, 0x7632), __byte_perm(b[j].z, b[j].w, 0x7632)));
    }
  }
#pragma unroll
  for (int j = 0; j < 20; j++) {
    const int k = min(tid + (j >> 2) * 128, DM - 1);
    m0[j] = bf2_add(__bfloat16_as_ushort(P.mem0[2 * (j & 3) * DM + k]) | (uint32_t)__bfloat16_as_ushort(P.mem0[(2 * (j & 3) + 1) * DM + k]) << 16, 0);
  }
#pragma unroll
  for (int i = 0; i < 6; i++) sts4(sb + Q_PX + (i * 128 + tid) * 16, make_uint4(0, 0, 0, 0));
  bar_sync<11, 384>();
#pragma unroll
  for (int j = 0; j < 5; j++) {
    const int k = min(tid + j * 128, DM - 1);
    sts4(sb + Q_X + (k >> 6) * Q_CS + (k & 63) * 16, make_uint4(m0[4 * j], m0[4 * j + 1], m0[4 * j + 2], m0[4 * j + 3]));
    sts4(sb + Q_X + (k >> 6) * Q_CS + (k & 63) * 16 + 1024, make_uint4(m0[4 * j], m0[4 * j + 1], m0[4 * j + 2], m0[4 * j + 3]));
  }
#pragma unroll
  for (int i = 0; i < 2; i++) sts4(sb + Q_STG + (i * 16 + (tid >> 3)) * 768 + 640 + (tid & 7) * 16, make_uint4(0, 0, 0, 0));
  fence_async_smem();
  PROF_G(2);
  const uint32_t wa = pin(sb + Q_WO + ((tid >> 4 & 1) * 8 + (tid & 7)) * 128 + (((2 * w + ((tid >> 3) & 1)) ^ (tid & 7)) << 4));
  char* pd = nullptr;
  uint32_t pg = 0;
  auto find_pieces = [&]() {
    const int lane = tid & 31, dcta = (w * 8 + (lane >> 2)) * 3 + rank;
    uint4 f;
    uint32_t n = 0;
    do {
      f = ld_poll((const uint4*)(g_flags + FL_SEL) + dcta);
      if (++n > SPIN_LIMIT) __trap();
    } while (__any_sync(0xffffffffu, !f.x || !f.y || !f.z));
    pd = (char*)P.memx + part_of(dcta) + (head * 4 + (lane & 3) + (f.x - 1) * 256) * 16;
    pg = (8192 + (f.y - f.x) * 4096) | (8192 + (f.z - f.y) * 4096) << 16;
  };
  uint32_t f[76];
  if (rank != 2) {
#pragma unroll
    for (int k = 0; k < 19; k++) ldsm4t(f[4 * k], f[4 * k + 1], f[4 * k + 2], f[4 * k + 3], wa + (k < 16 ? k : 2 * k - 16) * 2048);
    const uint32_t rs = pin(tid);
    cluster_sync();
#pragma unroll 1
    for (int t = 1;; t++) {
      if (t > 1) check_tiles<4>(sb, P, w, t);
      if (w == 0) {
        bar_sync<8, 224>();
        fence_async_smem();
        if (elect_one()) {
          bulk_s2s(mapa(sb + Q_SIN + rank * 4096, rank ^ 1), sb + Q_SOUT + 2048, SX_BYTES, mapa(sb + B_SM, rank ^ 1));
          mbar_arrive(sb + B_SM);
        }
        __syncwarp();
      }
      if (t == NT) break;
      if (t == 1) find_pieces();
      pd = (char*)((uintptr_t)pd ^ 2048);
      if (w == 1) {
        mbar_wait(sb + B_AN, (t - 1) & 1);
        spin_until(rd_clock() + (rank ? PA1_V : PA0_V));
        mbar_arrive_if0(rs - 32, sb + B_PZ);
      }
      mbar_spin(sb + B_O, (t - 1) & 1);
      PROF_W(w == 0, 13);
      wo_tiles<24>(sb, f, pd, pg, rs, t);
      mbar_expect_if0(rs, sb + B_O, 4096);
    }
  } else {
#pragma unroll
    for (int k = 0; k < 8; k++) ldsm4t(f[4 * k], f[4 * k + 1], f[4 * k + 2], f[4 * k + 3], wa + k * 2048);
    cluster_sync();
    find_pieces();
    const int l = w & 1, tile = w >> 1;
    const uint32_t ob = pin(sb + Q_OB + (l ^ ((head >> 1) & 1)) * 2048 + tile * 1024 + (tid >> 2 & 7) * 128 + (tid & 3) * 16);
    const uint32_t ob0 = sb + Q_OB + ((head >> 1) & 1) * 2048;
    const uint32_t sa = pin(sb + Q_SIN + l * 1024 + (tid & 31) * 16);
#pragma unroll 1
    for (int t = 1; t <= NT; t++) {
      const uint32_t par = (t - 1) & 1;
      {
        uint32_t vf[4][10], p[5];
        float s[10], o[4][4];
        const int lane = rd_lane();
        const uint32_t vb = sb + Q_STG + tile * 12288 + l * 6144 + (lane & 7) * 16;
        const uint32_t ax = vb + ((lane >> 3) & 1) * 768 + (lane >> 4) * 128;
        pd = (char*)((uintptr_t)pd ^ 2048);
        bar_sync<1, 384>();
#pragma unroll
        for (int i = 0; i < 4; i++) ldsm4(vf[i][4], vf[i][5], vf[i][6], vf[i][7], ax + i * 1536 + 256);
        ldsm4(vf[0][8], vf[0][9], vf[1][8], vf[1][9], vb + (lane >> 3) * 768 + 512);
        ldsm4(vf[2][8], vf[2][9], vf[3][8], vf[3][9], vb + (lane >> 3) * 768 + 512 + 3072);
#pragma unroll
        for (int i = 0; i < 4; i++) ldsm4(vf[i][0], vf[i][1], vf[i][2], vf[i][3], ax + i * 1536);
        mbar_spin(sb + B_SM, par);
        PROF_W(w == 0, 20);
        if (t < NT) {
          load_scores(s, sa);
          __syncwarp();
          softmax_num(s);
#pragma unroll
          for (int j = 0; j < 5; j++) p[j] = pack_bf16(s[2 * j], s[2 * j + 1]);
          __syncwarp();
          PROF_W(w == 0, 9);
          float z[4] = {0.f, 0.f, 0.f, 0.f};
          const uint32_t ONE = 0x3F803F80u;
          mma16816(z, ONE, ONE, ONE, ONE, p[0], p[1]);
#pragma unroll
          for (int i = 0; i < 4; i++) { o[i][0] = o[i][1] = o[i][2] = o[i][3] = 0.f; mma16816(o[i], vf[i][0], vf[i][1], vf[i][2], vf[i][3], p[0], p[1]); }
#pragma unroll
          for (int k = 8; k < (NFV_V < 12 ? NFV_V : 12); k++) ldsm4t(f[4 * k], f[4 * k + 1], f[4 * k + 2], f[4 * k + 3], wa + k * 2048);
          mma16816(z, ONE, ONE, ONE, ONE, p[2], p[3]);
#pragma unroll
          for (int i = 0; i < 4; i++) mma16816(o[i], vf[i][4], vf[i][5], vf[i][6], vf[i][7], p[2], p[3]);
#pragma unroll
          for (int k = 12; k < (NFV_V < 16 ? NFV_V : 16); k++) ldsm4t(f[4 * k], f[4 * k + 1], f[4 * k + 2], f[4 * k + 3], wa + k * 2048);
          mma1688(z, ONE, ONE, p[4]);
#pragma unroll
          for (int i = 0; i < 4; i++) mma1688(o[i], vf[i][8], vf[i][9], p[4]);
#pragma unroll
          for (int k = 16; k < 19 && 2 * k - 16 < NFV_V; k++) ldsm4t(f[4 * k], f[4 * k + 1], f[4 * k + 2], f[4 * k + 3], wa + (2 * k - 16) * 2048);
          const float r0 = rcp(z[0]), r1 = rcp(z[1]);
          const uint4 u0 = make_uint4(pack_bf16(o[0][0] * r0, o[0][2] * r0), pack_bf16(o[1][0] * r0, o[1][2] * r0),
                                      pack_bf16(o[2][0] * r0, o[2][2] * r0), pack_bf16(o[3][0] * r0, o[3][2] * r0));
          const uint4 u1 = make_uint4(pack_bf16(o[0][1] * r1, o[0][3] * r1), pack_bf16(o[1][1] * r1, o[1][3] * r1),
                                      pack_bf16(o[2][1] * r1, o[2][3] * r1), pack_bf16(o[3][1] * r1, o[3][3] * r1));
          PROF_W(w == 0, 8);
          sts4(ob, u0);
          sts4(ob + 64, u1);
          bar_sync<5, 160>();
          fence_async_smem();
          PROF_W(w == 0, 13);
          wo_tiles<NFV_V>(sb, f, pd, pg, ob ^ ob0, t);
        }
      }
      const int lane = rd_lane();
      mbar_expect_if0(lane | w, sb + B_SM, SM_BYTES);
      if (t < NT) bar_sync<12, 160>();
      {
        float o[3][16];
        const uint32_t ox = sb + Q_OX + 2 * w * 512 + lane * 16;
        const uint64_t dp = D_PX + (t & 1) * 384;
        fence_async_smem();
        mbar_wait(sb + B_P + 8 * (t & 1), ((t - 1) >> 1) & 1);
        PROF_W(w == 0, 7);
#pragma unroll
        for (int j = 0; j < 7; j++) {
          if (j >= 3) {
            const int i = j - 3;
            if (i == 0) mbar_wait(sb + B_OXFREE, par ^ 1);
            if (i < 2) wg_wait<2>(); else if (i == 2) wg_wait<0>();
            if (i == 2 && t < NT) bar_arrive<3, 384>();
            reg_fence(o[i % 3]);
#pragma unroll
            for (int h = 0; h < 2; h++)
              stsm4(ox + i * 4096 + h * 512, pack_bf16(o[i % 3][2 * h], o[i % 3][2 * h + 1]), pack_bf16(o[i % 3][4 + 2 * h], o[i % 3][5 + 2 * h]),
                    pack_bf16(o[i % 3][8 + 2 * h], o[i % 3][9 + 2 * h]), pack_bf16(o[i % 3][12 + 2 * h], o[i % 3][13 + 2 * h]));
          }
          if (j < 4) {
            if (j % 3 == 0) wg_fence();
            wg_sskk<0>(o[j % 3], D_V, (j >> 1) * 384 + (j & 1) * 768, dp, (j >> 1) * 192);
            wg_sskk<1>(o[j % 3], D_V, (j >> 1) * 384 + (j & 1) * 768 + 16, dp, (j >> 1) * 192 + 16);
            wg_sskk<1>(o[j % 3], D_V, (j >> 1) * 384 + (j & 1) * 768 + 32, dp, (j >> 1) * 192 + 32);
            wg_commit();
          }
        }
        mbar_expect_if0(lane | w, sb + B_P + 8 * (t & 1), PX_BYTES);
      }
      fence_async_smem();
      __syncwarp();
      mbar_arrive_if0(lane, sb + B_OXREADY);
      PROF_W(w == 0, 23);
    }
  }
  cluster_sync();
}

__device__ __forceinline__ void softmax_x(uint32_t sb, int w, int rank, int t) {
  float s[10];
  const int lane = rd_lane();
  mbar_wait(sb + B_SM, (t - 1) & 1);
  PROF_W(w == 3, 20);
  load_scores(s, sb + Q_SIN + w * 512 + lane * 16);
  const int last = 8 + 8 * w + (lane >> 2) - 2 * (lane & 3);
#pragma unroll
  for (int i = 2; i < 10; i++) s[i] = (8 * (i >> 1) + (i & 1) <= last) ? s[i] : -INFINITY;
  softmax_num(s);
  float sum = ((s[0] + s[1]) + (s[2] + s[3])) + ((s[4] + s[5]) + (s[6] + s[7])) + (s[8] + s[9]);
  sum += __shfl_xor_sync(0xffffffffu, sum, 1);
  sum += __shfl_xor_sync(0xffffffffu, sum, 2);
  const float r = rcp(sum);
  const uint32_t po = sb + Q_SOUT + 6144 + w * 768;
#pragma unroll
  for (int j = 0; j < 5; j++) sts1(po + lane * 4 + j * 128, pack_bf16(s[2 * j] * r, s[2 * j + 1] * r));
  fence_async_smem();
  __syncwarp();
  if (elect_one()) bulk_s2s(mapa(sb + Q_PX + ((t & 1) * 2 + rank) * 3072 + w * 768, 2), po, 128 * (w + 2), mapa(sb + B_P + 8 * (t & 1), 2));
  __syncwarp();
  PROF_W(w == 3, 22);
}

__device__ __forceinline__ void head_service(uint32_t sb, const Params& P) {
  const int lane = threadIdx.x & 31, rank = rd_rank(), w = rd_warp() & 3, i3 = w - 1;
  const int head = rd_cid(), c = tile_of(rank, i3);
  uint32_t dof = c * 8192 + (lane & 4) * 1024 + (lane & 8) * 128 + head * 32 + (lane & 16) + (lane & 3) * 4;
  uint32_t sof = part_of(blockIdx.x) + i3 * 8192, gof = 0, dly = tile_delay(rank, i3), g0 = 0, c0 = 0, ref = 0;
  asm volatile("barrier.cluster.arrive.aligned;" ::: "memory");
  if (w) {
#pragma unroll 1
    for (int j = 0; j < 16; j++) st_gpu4((uint4*)((char*)P.memx + sof) + j * 32 + lane, 1, 1, 1, 1);
    st_gpu1((uint32_t*)((char*)P.memx + dof), SENT);
    st_gpu1((uint32_t*)((char*)P.memx + dof + 2048), SENT);
    if (w == 2 && lane < 4) st_gpu4(P.memx + (blockIdx.x & 63) * 2 + (lane & 2) * 128 + (lane & 1), SENT, SENT, SENT, SENT);
    bar_sync<9, 224>();
    if (w < 3) probe_pages(sb, P, w == 1);
    if (w == 2 && rank != 2) bar_arrive<13, 64>();
    bar_sync<12, 96>();
    if (w == 1) PROF_G(0);
    sof += __shfl_sync(0xffffffffu, lds1(sb + Q_SEL + 36 + 4 * i3), 0);
    asm volatile("st.release.gpu.global.u32 [%0], %1;" :: "l"(g_flags + FL_SEL + blockIdx.x * 4 + i3), "r"(((sof >> 12) & 1) + 1) : "memory");
    if (w == 1) PROF_G(1);
    gof = c * 8192 + __shfl_sync(0xffffffffu, lds1(sb + Q_SEL + 4 * c), 0);
  }
  asm volatile("barrier.cluster.wait.aligned;" ::: "memory");
#pragma unroll 1
  for (int t = 0; t <= NT; t++) {
    if (w == 0 && rank == 0 && t < NT) {
      const uint32_t* fl = g_flags + FL_XS + t * 32;
      warp_flag_wait(fl + (lane & 1 ? (t >= LAG ? 16 : 0) : (t <= NSEG ? 0 : 16)), 4);
      fence_async_global();
      const char* src = (const char*)g_xs + (size_t)t * 73728;
      if (t > 0) mbar_wait(sb + B_E, (t - 1) & 1);
      PROF_T(24);
      uint32_t at = rd_clock();
#pragma unroll 1
      for (int k = 0; k < 9; k++) {
        if (elect_one()) bulk_g2s_mc(sb + Q_X + 3072 + k * Q_CS, src + 1024 + k * 8192, 7168, sb + B_XF + 8 * k, 7);
        __syncwarp();
        at += t ? XP_V : 0;
        spin_until(at);
      }
      if (t == 0) PROF_G(31);
    }
    if (t > 0) {
    if (rank == 2 && w) { if (t > 1) check_tiles<3>(sb, P, w - 1, t); else mbar_arrive_if0(lane, sb + B_E + 24); }
    if (w == (rank == 2) && t < NT) {
      if (t == 1 && rank != 2) bar_sync<13, 64>();
      const uint32_t* tms = (const uint32_t*)(P.memx + 9 * 512 + lds1(sb + Q_SEL + 48) / 16 + (head >> 4) * 32 + lane) + rank;
      const uint32_t due = ref + D_GX + (D_DUE - rank_delay(rank)) * 9 / 16;
      if (rank == 2) {
        const uint32_t g1 = next_tick(), c1 = rd_clock();
        const uint32_t rate = t > 1 ? __float2uint_rn(65536.f * (g1 - g0) * rcp(c1 - c0)) : 36400;
        g0 = g1; c0 = c1;
        uint4* pub = P.memx + 9 * 512 + (lane & 1) * 256 + (lane & 2) * 16 + head;
        const uint32_t lead = D_RED * rate >> 16, late = D_LATE * rate >> 16, r1 = rank_delay(1) * rate >> 10, r0 = rank_delay(0) * rate >> 10;
        mbar_wait(sb + B_E, (t - 1) & 1);
        PROF_T(4);
        mbar_spin(sb + B_E + 24, (t - 1) & 1);
        uint32_t now = g0 + ((rd_clock() - c0) * rate >> 16);
        now = (now + (t < 3 ? lead + ST0_V : (int)(now + 90 - due) > 0 ? late : lead)) << 6;
        st_gpu4(pub, ((now + r0) & ~255u) | t, ((now + r1) & ~255u) | t, (now & ~255u) | t, 0);
        PROF_T(22);
        PROF_V(true, 1, now >> 6);
      } else {
        mbar_wait(sb + B_CP + 64, (t - 1) & 1);
      }
      if (t > 1) wait_ns(due); else ref = next_tick();
      uint32_t d, n = 0;
      do {
        asm volatile("ld.relaxed.gpu.global.u32 %0, [%1];" : "=r"(d) : "l"(tms) : "memory");
        if (++n > SPIN_LIMIT) __trap();
      } while (__any_sync(0xffffffffu, (d ^ t) & 255));
      ref += __reduce_max_sync(0xffffffffu, (int)(d - (ref << 6))) >> 6;
      sts1(sb + Q_REF, ref);
      __syncwarp();
      mbar_arrive_if0(lane, sb + B_REF);
      PROF_A(13, n);
      PROF_T(19);
    }
    if (w == 2 && rank == 2 && t < NT) {
      mbar_wait(sb + B_SM, (t - 1) & 1);
      mbar_rarrive_if0(lane >> 1, mapa(sb + B_AN, lane & 1));
      bar_sync<5, 160>();
      fence_async_smem();
      if (elect_one()) {
        bulk_s2s(mapa(sb + Q_OB, 1), sb + Q_OB, 4096, mapa(sb + B_O, 1));
        bulk_s2s(mapa(sb + Q_OB, 0), sb + Q_OB, 4096, mapa(sb + B_O, 0));
      }
      __syncwarp();
    }
    if (rank != 2) {
      softmax_x(sb, w, rank, t);
      if (w == 0 && t < NT) bar_arrive<7, 64>();
      mbar_expect_if0(lane | (w - 1), sb + B_SM, SX_BYTES);
    }
    }
    if (w == 0 && rank == 0 && t < NT) {
      if (t > 0) mbar_wait(sb + B_E + 16, (t - 1) & 1);
      if (elect_one()) {
#pragma unroll 1
        for (int k = 0; k < 9; k++) bulk_g2s_mc(sb + Q_X + 2048 + k * Q_CS, (const char*)g_xs + (size_t)t * 73728 + k * 8192, 1024, sb + B_G0, 7);
      }
      __syncwarp();
    }
    if (t == 0) continue;
    if (w == 3) PROF_MID();
    if (w && t < NT) {
      mbar_wait(sb + B_REF, (t - 1) & 1);
      uint32_t when = lds1(sb + Q_REF) + dly;
      sof ^= 2048; dof ^= 2048;
      uint4* src = (uint4*)((char*)P.memx + sof) + lane;
      uint32_t* dst = (uint32_t*)((char*)P.memx + (dof ^ 2048));
      const bool inj = t == LAG && (lane & 8);
      if (t == LAG) {
        const __nv_bfloat16* m0 = P.mem0 + (lane & 3) * 2 * DM + c * 64 + head * 2 + (lane >> 4);
        st_gpu1_if(inj, dst, bf2_add(__bfloat16_as_ushort(m0[0]) | (uint32_t)__bfloat16_as_ushort(m0[DM]) << 16, 0));
      }
      asm volatile("" : "+l"(dst), "+l"(src));
      uint4 v[4];
      wait_ns(when);
      PROF_W(i3 == 0, 18);
      const uint32_t nr = poll4<true>(v, src, (t - 1) >> 1);
      PROF_T(26 + i3);
      const uint32_t z = bf2_add(bf2_add(v[0].z, v[1].z), bf2_add(v[2].z, v[3].z)), u = bf2_add(bf2_add(v[0].w, v[1].w), bf2_add(v[2].w, v[3].w));
      const uint32_t x = bf2_add(bf2_add(v[0].x, v[1].x), bf2_add(v[2].x, v[3].x)), y = bf2_add(bf2_add(v[0].y, v[1].y), bf2_add(v[2].y, v[3].y));
      const uint32_t x2 = bf2_add(bf2_add(x, 0), __shfl_xor_sync(0xffffffffu, z, 16)), y2 = bf2_add(y, __shfl_xor_sync(0xffffffffu, u, 16));
      const uint32_t x3 = bf2_add(x2, __shfl_xor_sync(0xffffffffu, y2, 8));
      st_gpu1_if(!inj, dst, bf2_add(x3, __shfl_xor_sync(0xffffffffu, x3, 4)));
      if (w == 3 && rank == 2) bar_arrive<12, 160>();
      PROF_T(29 + i3);
      PROF_A(10 + i3, nr);
      when += D_GX + min(lds1(sb + Q_REF + 4), 8u) * D_ADAPT;
      if (nr && t > LAG + 3 && dly < tile_delay(rank, i3) + 8 * D_ADAPT) dly += D_ADAPT;
      fence_async_global();
      if (w == 3 && rank != 2) bar_sync<7, 64>();
      wait_ns(when);
      if (elect_one()) bulk_g2s_mc(sb + Q_X + c * Q_CS, (const char*)P.memx + gof + (~t & 1) * 2048, 2048, sb + B_CP + 8 * c, 7);
      __syncwarp();
      if (i3 == 0) PROF_T(21);
      st_gpu1((uint32_t*)((char*)P.memx + dof), SENT);
    }
    if (w == 0 && rank == 2) {
      if (t < NT) mbar_wait(sb + B_XF, t & 1); else warp_flag_wait(g_flags + FL_XS + NT * 32 + 16, 4);
      mbar_wait(sb + B_OXREADY, (t - 1) & 1);
      if (elect_one()) {
        uint4* od = g_ox + (size_t)(t & (OXRING - 1)) * 32768 + head * 512;
        if (t <= NSEG) bulk_s2g(od, sb + Q_OX, 8192);
        if (t > LAG) bulk_s2g(od + 16384, sb + Q_OX + 8192, 8192);
        bulk_commit_wait();
        mbar_arrive(sb + B_OXFREE);
        flag_add(g_flags + FL_OX + t * 32 + head);
      }
      __syncwarp();
      PROF_T(25);
    }
  }
  cluster_sync();
}

__global__ void __cluster_dims__(3, 1, 1) __launch_bounds__(512, 1) head_kernel(const __grid_constant__ Params P) {
  extern __shared__ uint8_t smem_raw[];
  const uint32_t sb = (uint32_t)__cvta_generic_to_shared(smem_raw);
  if ((sb & 0xFFFFFFu) != SB0) __trap();
  asm volatile("griddepcontrol.launch_dependents;");
  if (threadIdx.x < 96) {
    const int i = blockIdx.x * 24 + threadIdx.x % 24, m = threadIdx.x / 24;
    const __nv_bfloat16* p = m == 3 ? P.ssm_k + (size_t)(i >> 2) * SEQ + (i & 3) * 64 : (m == 0 ? P.ck : m == 1 ? P.cv : P.x0) + (size_t)i * 64;
    asm volatile("prefetch.global.L2 [%0];" :: "l"(p));
  } else if (threadIdx.x == 96 && blockIdx.x < 45) {
    asm volatile("prefetch.global.L2 [%0];" :: "l"(blockIdx.x < 36 ? P.shift + blockIdx.x * 64 : P.ssm_d + (blockIdx.x - 36) * 64));
  } else if (threadIdx.x == 97 && blockIdx.x < 72) {
    asm volatile("prefetch.global.L2 [%0];" :: "l"(P.mem0 + blockIdx.x * 64));
  }
  PROF_BEGIN();
  if (threadIdx.x == 416) sts1(sb + Q_SET, (__ldcg(&g_epoch) & 1) * FL_TOTAL);
  const int rank = rd_rank(), wg = rd_warp() >> 2;
  if (threadIdx.x == 448) {
    for (int c = 0; c < 9; c++) { mbar_init(sb + B_CP + 8 * c, 1); mbar_arrive(sb + B_CP + 8 * c); mbar_init(sb + B_OK + 8 * c, 1); mbar_arrive(sb + B_OK + 8 * c); mbar_init(sb + B_XF + 8 * c, 1); mbar_expect(sb + B_XF + 8 * c, 7168); }
    mbar_init(sb + B_E, 6); mbar_init(sb + B_G0, 1); mbar_expect(sb + B_G0, 9216); mbar_init(sb + B_E + 16, 6); mbar_init(sb + B_E + 24, 7);
    mbar_init(sb + B_SM, rank == 2 ? 1 : 2); mbar_init(sb + B_O, 1); mbar_init(sb + B_P, 1); mbar_init(sb + B_P + 8, 1);
    mbar_init(sb + B_REF, 1); mbar_init(sb + B_RES, 1); mbar_init(sb + B_PZ, 1); mbar_init(sb + B_AN, 1); mbar_init(sb + B_OXREADY, 4); mbar_init(sb + B_OXFREE, 1);
    mbar_expect(sb + B_SM, rank == 2 ? SM_BYTES : SX_BYTES); mbar_expect(sb + B_P, PX_BYTES); mbar_expect(sb + B_P + 8, PX_BYTES);
    mbar_expect(sb + B_O, 4096);
    sts1(sb + Q_REF + 4, 0);
    asm volatile("fence.mbarrier_init.release.cluster;" ::: "memory");
  }
  __syncthreads();
  PROF_G(6);
  if (wg < 2) {
    asm volatile("setmaxnreg.inc.sync.aligned.u32 176;");
    head_main(sb, P);
    PROF_END();
  } else if (wg == 2) {
    asm volatile("setmaxnreg.dec.sync.aligned.u32 120;");
    head_aux(sb, P);
    PROF_END();
  } else {
    asm volatile("setmaxnreg.dec.sync.aligned.u32 40;");
    head_service(sb, P);
    PROF_END();
  }
}

__device__ __forceinline__ void tail_gemm(uint32_t sb, const Params& P) {
  const int lane = threadIdx.x & 31, warp = rd_warp(), w = warp & 3, wg = warp >> 2, tid = threadIdx.x & 127;
  uint32_t a[4 * W_KR];
  fence_async_smem();
  if (elect_one()) {
#pragma unroll 1
    for (int k = w; k < 32; k += 4)
      tma_box(k < W_KR ? sb + wg * 65536 + k * 2048 : sb + W_WS + wg * 6144 + (k - W_KR) * 2048, &P.tm, (blockIdx.x % 3) * 192 + wg * 64, (blockIdx.x / 3) * 512 + k * 16, sb + B_WT + 8 * wg);
  }
  __syncwarp();
  mbar_wait(sb + B_WT + 8 * wg, 0);
  load_afrags<W_KR>(a, sb + wg * 65536, w, lane);
  fence_async_smem();
  bar_sync<1, 416>();
  PROF_G(26);
  if (wg == 2) bar_arrive<2, 256>();
  const uint64_t dw = P.d_ws + wg * 384;
  float4* dst0 = g_acc + ((blockIdx.x % 3) * 12 + warp) * 32 + lane;
#pragma unroll 1
  for (int t = 1; t <= NT; t++) {
#pragma unroll 1
    for (int l = t > NSEG; l <= (t > LAG); l++) {
      const int seg = t - 1 - l * LAG, grp = (seg & 1) * 2 + l;
      const uint64_t db = P.d_ring + grp * 2048;
      float acc[16];
      bar_sync_r(2 + wg, 256);
#pragma unroll
      for (int c = 0; c < 4; c++) {
        if (wg == 0) mbar_wait(sb + B_FULL + 32 * grp + 8 * c, (seg >> 1) & 1);
        if (c == 0) PROF_T(6 * l + wg);
        wg_fence();
#pragma unroll
        for (int i = 0; i < 8; i++) {
          if (c == 0 && i == 0) wg_rs<0, 1>(acc, a, db, 0);
          else if (8 * c + i < W_KR) wg_rs<1, 1>(acc, a + 32 * c + 4 * i, db, 512 * c + 64 * i);
          else wg_ss<1, 1>(acc, dw, 128 * (8 * c + i - W_KR), db, 512 * c + 64 * i);
        }
      }
      wg_commit();
      bar_arrive_r(wg == 2 ? 2 : 3 + wg, 256);
      wg_wait<0>();
      reg_fence(acc);
      mbar_arrive_if0(tid, sb + B_EMPTY + 8 * grp);
      float4* dst = dst0 + (size_t)(l * 256 + seg * 4) * 1152;
#pragma unroll
      for (int j = 0; j < 4; j++)
        asm volatile("red.relaxed.gpu.global.add.v4.f32 [%0], {%1,%2,%3,%4};" :: "l"(dst + j * 1152),
                     "f"(acc[4 * j]), "f"(acc[4 * j + 1]), "f"(acc[4 * j + 2]), "f"(acc[4 * j + 3]) : "memory");
      bar_sync_r(5 + wg, 160);
    }
  }
}
__device__ __forceinline__ void tail_service(uint32_t sb) {
  const int lane = threadIdx.x & 31, warp = rd_warp();
  if (warp == 12) bar_sync<1, 416>();
#pragma unroll 1
  for (int t = 1; t <= NT; t++) {
    if (warp == 12) {
      const int h0 = (blockIdx.x / 3) * 4;
      warp_flag_wait(g_flags + FL_OX + t * 32 + h0 + (lane & 3), 1);
      fence_async_global();
#pragma unroll 1
      for (int l = t > NSEG; l <= (t > LAG); l++) {
        const int seg = t - 1 - l * LAG, grp = (seg & 1) * 2 + l;
        const uint4* src = g_ox + (size_t)(t % OXRING) * 32768 + l * 16384 + h0 * 512;
        const uint32_t bar = sb + B_FULL + 32 * grp;
        mbar_wait_lim(sb + B_EMPTY + 8 * grp, ((seg >> 1) & 1) ^ 1);
        mbar_expect_if0(lane > 3, bar + 8 * lane, 8192);
        if (elect_one()) {
#pragma unroll
          for (int j = 0; j < 4; j++) bulk_g2s(sb + W_RING + (grp * 4 + j) * 8192, src + j * 512, 8192, bar + 8 * j);
        }
        __syncwarp();
      }
      PROF_T(12);
      PROF_MID();
    } else {
#pragma unroll 1
      for (int l = t > NSEG; l <= (t > LAG); l++) {
        bar_sync_r(warp - 8, 160);
        if (lane == 0) flag_add(g_flags + FL_ACC + (l * 64 + t - 1 - l * LAG) * 32);
        __syncwarp();
        PROF_T(6 * l + warp - 10);
      }
    }
  }
}

__device__ __forceinline__ void wait_k1(uint32_t sb, int n) {
  uint32_t c = 0;
  while ((int)lds1(sb + W_K1) < n) {
    __nanosleep(64);
    if (++c > SPIN_LIMIT) __trap();
  }
}
__device__ __forceinline__ void tail_finisher(uint32_t sb, const Params& P) {
  const int lane = threadIdx.x & 31, warp = rd_warp(), kind = warp < 12 ? warp / 6 : warp & 1, f = warp - 6 * kind, tg = blockIdx.x & 3;
  if (warp >= 14) {
    const uint32_t set = lds1(sb + Q_SET), ft = sb + W_FO + kind * 576;
    if (tg == 0) for (int i = kind * 32 + lane; i < FL_TOTAL; i += 64) g_flagsets[FL_TOTAL - set + i] = 0;
#pragma unroll 1
    for (int t = 0; t < NSEG; t++) {
      warp_flag_wait(g_flags + FL_ACC + (64 + t) * 32, 72);
      PROF_T(17);
      if (t == 0 && tg == 0 && threadIdx.x == 448) g_epoch = set ? 0 : 1;
      const float4* ac = g_acc + ((size_t)(256 + t * 4 + tg) * 36 + kind * 18) * 32 + lane;
      float4 v[18];
#pragma unroll
      for (int i = 0; i < 18; i++) v[i] = __ldcg(ac + i * 32);
#pragma unroll
      for (int i = 0; i < 9; i++) {
        const uint4 r = lds4(sb + W_RS + (8 + (t & 7)) * 9216 + (kind * 9 + i) * 512 + lane * 16);
        stsm4t(ft + (lane & 7) * 1168 + (lane >> 3) * 16 + 64 * i, bf2_add(r.x, pack_bf16(v[2 * i].x, v[2 * i].y)), bf2_add(r.y, pack_bf16(v[2 * i].z, v[2 * i].w)),
               bf2_add(r.z, pack_bf16(v[2 * i + 1].x, v[2 * i + 1].y)), bf2_add(r.w, pack_bf16(v[2 * i + 1].z, v[2 * i + 1].w)));
      }
      fence_async_smem();
      __syncwarp();
      mbar_arrive_if0(lane, sb + B_RF + 8 * (t & 7));
      wait_k1(sb, min(t + LAG + 1, NSEG));
      if (lane < 8) {
        bulk_s2g(P.out + (size_t)((t * 4 + tg) * 8 + lane) * DM + kind * 288, ft + lane * 1168, 576);
        bulk_commit_wait();
      }
      __syncwarp();
      PROF_T(18);
    }
    return;
  }
  if (warp >= 12) {
    for (int i = kind * 32 + lane; i < 1152; i += 64) sts4(sb + W_Z + i * 16, make_uint4(0, 0, 0, 0));
    fence_async_smem();
    bar_sync<12, 64>();
#pragma unroll 1
    for (int t = -1; t <= NSEG; t++) {
      if (kind == 0 && t + 1 < NSEG) {
        const uint32_t bar = sb + B_FT + 8 * ((t + 1) & 1);
        mbar_expect_if0(lane, bar, 9216);
        __syncwarp();
        if (lane < 8) bulk_g2s(sb + W_FT + ((t + 1) & 1) * 9344 + lane * 1168, P.x0 + (size_t)(((t + 1) * 4 + tg) * 8 + lane) * DM, 1152, bar);
      }
      if (t < 0) continue;
      if (t < NSEG) bar_sync_r(9 + 2 * kind, 224);
      if (lane == 0) {
        flag_add(g_flags + FL_XS + (t + kind * LAG) * 32 + kind * 16);
        if (kind) { sts1(sb + W_K1, t + 1); PROF_T(14); }
        if (kind ? t < NSEG : t < LAG) bulk_s2g(g_acc + (size_t)(kind * 256 + t * 4 + tg) * 1152, sb + W_Z, 18432);
        if (kind && t + LAG < NSEG) bulk_s2g(g_acc + (size_t)((t + LAG) * 4 + tg) * 1152, sb + W_Z, 18432);
        bulk_commit_wait();
      }
      __syncwarp();
      if (kind) PROF_MID();
    }
    return;
  }
  const uint32_t BF_1 = 0x3F803F80u;
  const uint32_t* ys = (const uint32_t*)(g_y + ((tg >> 1) * DM + f * 96 + (lane >> 2)) * 2 + (tg & 1)) + (lane & 3);
  const uint32_t rs = sb + W_RS + f * 1536 + lane * 16;
  uint32_t y[12] = {};
#pragma unroll 1
  for (int t = 0; t < NSEG; t++) {
    uint32_t x[12];
    if (kind == 0) {
      wait_k1(sb, t - 6);
      mbar_wait(sb + B_FT + 8 * (t & 1), (t >> 1) & 1);
#pragma unroll
      for (int i = 0; i < 3; i++)
        ldsm4t(x[4 * i], x[4 * i + 1], x[4 * i + 2], x[4 * i + 3], sb + W_FT + (t & 1) * 9344 + (lane & 7) * 1168 + f * 192 + (lane >> 3) * 16 + 64 * i);
    } else {
      warp_flag_wait(g_flags + FL_ACC + t * 32, 72);
      PROF_T(13);
#pragma unroll
      for (int i = 0; i < 6; i++) {
        const float4 v = __ldcg(g_acc + ((size_t)(t * 4 + tg) * 36 + f * 6 + i) * 32 + lane);
        x[2 * i] = pack_bf16(v.x, v.y); x[2 * i + 1] = pack_bf16(v.z, v.w);
      }
#pragma unroll
      for (int i = 0; i < 3; i++) {
        const uint4 r = lds4(rs + (t & 7) * 9216 + i * 512);
        x[4 * i] = bf2_add(x[4 * i], r.x); x[4 * i + 1] = bf2_add(x[4 * i + 1], r.y); x[4 * i + 2] = bf2_add(x[4 * i + 2], r.z); x[4 * i + 3] = bf2_add(x[4 * i + 3], r.w);
      }
      mbar_wait(sb + B_RF + 8 * (t & 7), ((t >> 3) & 1) ^ 1);
      PROF_T(15);
    }
    {
      if (t == 0) PROF_G(27);
#pragma unroll 1
      for (int pass = 0; pass < 2; pass++) {
        float g[2][4] = {};
#pragma unroll
        for (int i = 0; i < 12; i++) {
          uint32_t u;
          asm volatile("movmatrix.sync.aligned.m8n8.trans.b16 %0, %1;" : "=r"(u) : "r"(x[i]));
          mma1688(g[i & 1], u, BF_1, u);
        }
        const uint32_t st = sb + W_ST + kind * 1024 + pass * 512 + (lane & 3) * 16;
        if ((lane >> 3) == (lane & 3))
          asm volatile("st.shared.v2.f32 [%0], {%1,%2};" :: "r"(st + f * 64 + (lane & 4) * 2), "f"(lane & 4 ? g[0][3] + g[1][3] : g[0][2] + g[1][2]),
                       "f"(lane & 4 ? g[0][1] + g[1][1] : g[0][0] + g[1][0]) : "memory");
        bar_sync_r(8 + 2 * kind, 192);
        float s0 = 0.f, s1 = 0.f, q0 = 0.f, q1 = 0.f;
        if (kind && pass == 0) PROF_T(19);
        if (kind && pass == 1) PROF_T(21);
#pragma unroll
        for (int i = 0; i < 6; i++) {
          const float4 e = lds4f(st + i * 64);
          s0 += e.x; q0 += e.y; s1 += e.z; q1 += e.w;
        }
        s0 *= 1.f / 576.f; s1 *= 1.f / 576.f;
        const float v0 = fmaf(q0, 1.f / 576.f, -s0 * s0), v1 = fmaf(q1, 1.f / 576.f, -s1 * s1);
        const uint32_t nmean = pack_bf16(-s0, -s1), vb = pack_bf16(fmaxf(v0, 0.f), fmaxf(v1, 0.f));
        const uint32_t ve = pack_bf16(bf_lo(vb) + 1e-5f, bf_hi(vb) + 1e-5f), sd = pack_bf16(sqr(bf_lo(ve)), sqr(bf_hi(ve)));
        const float r0 = rcp(bf_lo(sd)), r1 = rcp(bf_hi(sd));
        const uint32_t rh = pack_bf16(r0, r1), rl = pack_bf16(r0 - bf_lo(rh), r1 - bf_hi(rh));
        if (pass == 0 && (t == 0 || t == 4 * CT_A || t == 4 * CT_B || t == 4 * CT_C)) {
          if (t == 0) PROF_G(25);
          warp_flag_wait(g_flags + FL_Y + t * 8, t < 4 * CT_B ? 32 : DM);
          if (t == 0) PROF_G(26);
#pragma unroll
          for (int i = 0; i < 12; i++) y[i] = __ldcg(ys + t * (DM * 16) + i * 64);
        }
        uint32_t* xd = (uint32_t*)(g_xs + (size_t)(t + kind * LAG) * 4608 + (kind * 4 + tg) * 64 + (f * 3 >> 1) * 512 + (f & 1) * 32) + lane;
#pragma unroll
        for (int i = 0; i < 12; i++) {
          const uint32_t d = bf2_add(x[i], nmean), q = bf2_op(d, rh, bf2_mul(d, rl));
          if (pass == 0) x[i] = bf2_add(x[i], bf2_mul(q, y[i]));
          else xd[i < 4 ? i * 32 : i < 8 ? i * 32 + (f & 1) * 1792 : i * 32 + 1792] = q;
        }
        if (pass == 0) {
#pragma unroll
          for (int i = 0; i < 3; i++) sts4(rs + (kind * 8 + (t & 7)) * 9216 + i * 512, make_uint4(x[4 * i], x[4 * i + 1], x[4 * i + 2], x[4 * i + 3]));
        }
        if (kind && pass == 0) PROF_T(20);
        if (kind && pass == 1) PROF_T(22);
      }
      if (kind) PROF_T(16);
      if (t < 3) PROF_G(28 + t);
      bar_sync_r(9 + 2 * kind, 224);
#pragma unroll
      for (int i = 0; i < 12; i++) y[i] = __ldcg(ys + ((t + 1) & 63) * (DM * 16) + i * 64);
    }
  }
}

template <int NP, typename V>
__device__ __forceinline__ void kv_block(uint4 (&o)[2 * NP], const Params& P, int r0, int c0) {
  V kk[11], vv[8];
  uint4 sw[NP];
#pragma unroll
  for (int i = 0; i < NP; i++) sw[i] = __ldg((const uint4*)(P.shift + (c0 + 2 * i) * 4));
#pragma unroll
  for (int i = 0; i < 11; i++) kk[i] = r0 + i >= 3 ? __ldg((const V*)(P.ck + (size_t)(r0 + i - 3) * DM + c0)) : V{};
#pragma unroll
  for (int i = 0; i < 8; i++) vv[i] = __ldg((const V*)(P.cv + (size_t)(r0 + i) * DM + c0));
#pragma unroll
  for (int cp = 0; cp < NP; cp++) {
    const uint32_t wt[4] = {__byte_perm(sw[cp].y, sw[cp].w, 0x7632), __byte_perm(sw[cp].y, sw[cp].w, 0x5410),
                            __byte_perm(sw[cp].x, sw[cp].z, 0x7632), __byte_perm(sw[cp].x, sw[cp].z, 0x5410)};
    uint32_t e[8];
#pragma unroll
    for (int i = 0; i < 8; i++) {
      uint32_t a = bf2_mul(((const uint32_t*)&kk[i])[cp], wt[0]);
#pragma unroll
      for (int j = 1; j < 4; j++) a = bf2_add(a, bf2_mul(((const uint32_t*)&kk[i + j])[cp], wt[j]));
      e[i] = bf2_mul(a, ((const uint32_t*)&vv[i])[cp]);
    }
    o[2 * cp] = make_uint4(__byte_perm(e[0], e[1], 0x5410), __byte_perm(e[2], e[3], 0x5410), __byte_perm(e[4], e[5], 0x5410), __byte_perm(e[6], e[7], 0x5410));
    o[2 * cp + 1] = make_uint4(__byte_perm(e[0], e[1], 0x7632), __byte_perm(e[2], e[3], 0x7632), __byte_perm(e[4], e[5], 0x7632), __byte_perm(e[6], e[7], 0x7632));
  }
}
__device__ __forceinline__ void kv_task(const Params& P, int id) {
  const int lane = threadIdx.x & 31, tq = id / 9, c0 = (id % 9) * 64 + (lane >> 2) * 8;
  uint4 o[8];
  kv_block<4, uint4>(o, P, tq * 32 + (lane & 3) * 8, c0);
#pragma unroll
  for (int c = 0; c < 8; c++) g_kv[((size_t)tq * DM + c0 + c) * 4 + (lane & 3)] = o[c];
}
__device__ __forceinline__ int next_job(uint32_t sb) {
  int j = 0;
  if ((threadIdx.x & 31) == 0) j = atomicAdd(g_flags + FL_KV + 96, 1);
  return __shfl_sync(0xffffffffu, j, 0);
}
__device__ __forceinline__ uint2 lds2_ro(uint32_t a) { uint2 v; asm("ld.shared.v2.u32 {%0,%1}, [%2];" : "=r"(v.x), "=r"(v.y) : "r"(a)); return v; }

template <int T0, int T1>
__device__ __forceinline__ void conv_job(uint32_t sb, const Params& P, int ch, int sets = 1) {
  const int lane = threadIdx.x & 31, w = threadIdx.x >> 5;
  uint32_t ub = sb + w * C_CH, zb = ub + C_U;
  constexpr int NL = (T1 + 1) / 2, NS = T0 == 0 ? 2 : 1;
  constexpr bool CTA = T1 <= CT_B;
  static_assert(T0 > 0 || T1 == 2, "second set: buffer offsets, warps");
  PROF_G(13 + 4 * (T0 == 0 ? 0 : T0 == CT_A ? 1 : 2));
  uint2 q[NS][T1];
  uint32_t dd[NS];
#pragma unroll
  for (int n = 0; n < NS; n++) {
    const int c = n < sets ? ch - n * 128 : ch;
#pragma unroll
    for (int u = 0; u < T1; u++) q[n][u] = __ldg((const uint2*)(P.ssm_k + (size_t)c * SEQ) + u * 32 + lane);
    dd[n] = (uint32_t)__bfloat16_as_ushort(P.ssm_d[c]) * 0x10001u;
  }
  if (CTA) {
#pragma unroll
    for (int tq = w; tq < 4 * T1 * sets; tq += 16) {
      uint4 o[2];
      const int n = T0 == 0 ? tq >> 3 : 0, tgp = (tq - 8 * n) * 4 + (lane & 3), c0 = (lane >> 2) * 2;
      kv_block<1, uint32_t>(o, P, tgp * 8, ch - w + c0 - n * 128);
#pragma unroll
      for (int c = 0; c < 2; c++) {
        sts4(sb + (c0 + c) * C_CH + n * 2048 + 256 + tgp * 16, o[c]);
        if (T0) g_kv[((size_t)tq * DM + ch - w + c0 + c) * 4 + (lane & 3)] = o[c];
      }
    }
    __syncwarp();
  } else {
    uint4 o[NL];
#pragma unroll
    for (int u = 0; u < NL; u++) o[u] = __ldcg(g_kv + ((size_t)(u * 8 + (lane >> 2)) * DM + ch) * 4 + (lane & 3));
#pragma unroll
    for (int u = 0; u < NL; u++) sts4(ub + 256 + (u * 32 + lane) * 16, o[u]);
  }
#pragma unroll
  for (int n = 0; n < NS; n++) {
    if (lane < 16) { sts4(ub + n * 2048 + lane * 16, make_uint4(0, 0, 0, 0)); sts1(zb + n * 4096 + lane * 4, 0); }
#pragma unroll
    for (int u = 0; u < T1; u++) {
      const uint2 k = q[n][u];
      const uint32_t pv = __shfl_sync(0xffffffffu, lane == 31 ? (u ? q[n][u ? u - 1 : 0].y : 0u) : k.y, (lane + 31) & 31);
      sts4(zb + n * 4096 + 64 + (u * 32 + lane) * 16, make_uint4(__byte_perm(k.x, pv, 0x7610), __byte_perm(k.x, k.x, 0x1032),
                                                                __byte_perm(k.y, k.x, 0x7610), __byte_perm(k.y, k.y, 0x1032)));
    }
  }
  if (CTA) __syncthreads(); else __syncwarp();
  PROF_G(14 + 4 * (T0 == 0 ? 0 : T0 == CT_A ? 1 : 2));
#pragma unroll 1
  for (int n = 0; n < sets; n++, ub += 2048, zb += 4096) {
    float acc[T1 - T0][4];
#pragma unroll
    for (int i = 0; i < T1 - T0; i++) acc[i][0] = acc[i][1] = acc[i][2] = acc[i][3] = 0.f;
#pragma unroll(T0 == 0 ? 4 : 1)
    for (int r = 0; r < 8; r++) {
      uint2 b[T1];
      uint32_t ba = ub + 256 - r * 32 + lane * 8, zp = zb + 64 + (16 * r + 2 * (lane >> 2) - 4 * (lane & 3)) * 4;
      asm volatile("" : "+r"(zp), "+r"(ba) :: "memory");
#pragma unroll
      for (int i = 0; i < T1; i++) b[i] = lds2_ro(ba + i * 256);
#pragma unroll
      for (int mu = 0; mu < T1; mu++) {
        const uint2 a01 = lds2_ro(zp + 512 * mu), a23 = lds2_ro(zp + 512 * mu - 8);
#pragma unroll
        for (int i = (mu > T0 ? mu : T0); i < T1; i++) mma16816(acc[i - T0], a01.x, a01.y, a23.x, a23.y, b[i - mu].x, b[i - mu].y);
      }
    }
    PROF_G(15 + 4 * (T0 == 0 ? 0 : T0 == CT_A ? 1 : 2));
#pragma unroll
    for (int i = 0; i < T1 - T0; i++)
#pragma unroll
      for (int e = 0; e < 2; e++) {
        const int col = (T0 + i) * 8 + 2 * (lane & 3) + e;
        ((uint32_t*)g_y)[((size_t)col * DM + ch - n * 128) * 8 + (lane >> 2)] =
            bf2_add(pack_bf16(acc[i][e], acc[i][2 + e]), bf2_mul(lds1(ub + 256 + col * 32 + (lane >> 2) * 4), n ? dd[NS - 1] : dd[0]));
      }
  }
  if (CTA) __syncthreads(); else __syncwarp();
  PROF_G(16 + 4 * (T0 == 0 ? 0 : T0 == CT_A ? 1 : 2));
  if (CTA ? threadIdx.x == 480 && (T0 == 0 || ch < 512) : lane == 0) flag_add(g_flags + FL_Y + T0 * 32);
  __syncwarp();
}

__global__ void __launch_bounds__(512, 1) tail_kernel(const __grid_constant__ Params P) {
  extern __shared__ uint8_t smem_raw[];
  const uint32_t sb = (uint32_t)__cvta_generic_to_shared(smem_raw);
  if (sb != SB0) __trap();
  PROF_BEGIN();
  if (threadIdx.x == 0) {
    for (int c = 0; c < 16; c++) mbar_init(sb + B_FULL + 8 * c, 1);
    for (int c = 0; c < 4; c++) mbar_init(sb + B_EMPTY + 8 * c, 3);
    for (int c = 0; c < 2; c++) mbar_init(sb + B_FT + 8 * c, 1);
    for (int c = 0; c < 8; c++) mbar_init(sb + B_RF + 8 * c, 2);
    for (int c = 0; c < 3; c++) { mbar_init(sb + B_WT + 8 * c, 1); mbar_expect(sb + B_WT + 8 * c, 65536); }
    sts1(sb + W_K1, 0);
    sts1(sb + Q_SET, (__ldcg(&g_epoch) & 1) * FL_TOTAL);
    fence_async_smem();
  }
  const int b = blockIdx.x, w = threadIdx.x >> 5;
  if ((b >> 2) == 6) {
    __syncthreads();
  } else {
    conv_job<0, CT_A>(sb, P, b * 16 + w, b < 32 ? 1 : 2);
    PROF_G(3);
#pragma unroll 1
    for (int g = b; g == b || (g >> 2) == 6; g -= 8) conv_job<CT_A, CT_B>(sb, P, g * 16 + w);
    PROF_G(4);
    if (b >= 28) {
      constexpr int KV0 = 36 * CT_B, KV1 = KV0 + 192, NK = 576 - KV1;
      const int lane = threadIdx.x & 31;
      auto draw = [&]() {
        const int j = next_job(sb), ch = j < DM ? j : j - DM - NK;
        if (ch >= 0 && ch < DM && lane < (j < DM ? 2 * CT_C : 32)) asm volatile("prefetch.global.L2 [%0];" :: "l"(P.ssm_k + (size_t)ch * SEQ + lane * 64));
        return j;
      };
      int job = draw();
#pragma unroll 1
      for (int k = KV0 + (b - 28) * 16 + w; b < 32 && k < KV1; k += 64) {
        kv_task(P, k);
        __syncwarp();
        if (lane == 0) flag_add(g_flags + FL_KV);
      }
      warp_flag_wait(g_flags + FL_Y + CT_A * 32, 32);
      warp_flag_wait(g_flags + FL_KV, 192);
      spin_until(rd_clock() + (w >> 2) * DP_V);
#pragma unroll 1
      while (job < DM) { const int nx = draw(); conv_job<CT_B, CT_C>(sb, P, job); job = nx; }
      PROF_G(6);
#pragma unroll 1
      while (job < DM + NK) {
        const int nx = draw();
        kv_task(P, job - DM + KV1);
        __syncwarp();
        if (lane == 0) flag_add(g_flags + FL_KV + 32);
        job = nx;
      }
      warp_flag_wait(g_flags + FL_KV + 32, NK);
#pragma unroll 1
      while (job < 2 * DM + NK) { const int nx = draw(); conv_job<CT_C, 16>(sb, P, job - DM - NK); job = nx; }
      PROF_G(5);
      PROF_END();
      return;
    }
    __syncwarp();
  }
  if (blockIdx.x >= 24) {
    PROF_G(24);
    tail_finisher(sb, P);
    PROF_END();
    asm volatile("griddepcontrol.wait;" ::: "memory");
  } else if (rd_warp() < 12) {
    asm volatile("setmaxnreg.inc.sync.aligned.u32 160;");
    tail_gemm(sb, P);
    PROF_END();
  } else {
    asm volatile("setmaxnreg.dec.sync.aligned.u32 32;");
    tail_service(sb);
    PROF_END();
  }
}

}

extern "C" void kernel_launch(void* const* d_in, const int* in_sizes, int n_in, void* d_out, int out_size) {
  typedef const __nv_bfloat16* bp;
  Params P;
  P.x0 = (bp)d_in[0]; P.ck = (bp)d_in[1]; P.cv = (bp)d_in[2]; P.shift = (bp)d_in[3]; P.ssm_k = (bp)d_in[4]; P.ssm_d = (bp)d_in[5];
  P.mem0 = (bp)d_in[7]; P.wq = (bp)d_in[8]; P.wk = (bp)d_in[9]; P.wv = (bp)d_in[10]; P.wo = (bp)d_in[11];
  P.out = (__nv_bfloat16*)d_out;
  typedef CUresult (*Encode)(CUtensorMap*, CUtensorMapDataType, cuuint32_t, void*, const cuuint64_t*, const cuuint64_t*, const cuuint32_t*, const cuuint32_t*,
                             CUtensorMapInterleave, CUtensorMapSwizzle, CUtensorMapL2promotion, CUtensorMapFloatOOBfill);
  static Encode encode = nullptr;
  if (!encode) {
    cudaDriverEntryPointQueryResult qr;
    cudaGetDriverEntryPoint("cuTensorMapEncodeTiled", (void**)&encode, cudaEnableDefault, &qr);
  }
  const cuuint64_t dims[2] = {DM, 4096}, pitch[1] = {DM * 2};
  const cuuint32_t box[2] = {64, 16}, es[2] = {1, 1};
  encode(&P.tm, CU_TENSOR_MAP_DATA_TYPE_BFLOAT16, 2, d_in[11], dims, pitch, box, es, CU_TENSOR_MAP_INTERLEAVE_NONE,
         CU_TENSOR_MAP_SWIZZLE_128B, CU_TENSOR_MAP_L2_PROMOTION_NONE, CU_TENSOR_MAP_FLOAT_OOB_FILL_NONE);
  void* xc = nullptr;
  cudaGetSymbolAddress(&xc, g_xchg);
  P.memx = (uint4*)(((uintptr_t)xc + 0x1FFFFF) & ~(uintptr_t)0x1FFFFF);
  P.d_x = mkdesc(Q_X, 128, 1024, 0); P.d_wl = mkdesc(Q_WL, 16, 1024, 1);
  P.d_ring = mkdesc(W_RING, 512, 128, 0); P.d_ws = mkdesc(W_WS, 16, 1024, 1);
  cudaFuncSetAttribute(head_kernel, cudaFuncAttributeMaxDynamicSharedMemorySize, SMEM_TOTAL);
  cudaFuncSetAttribute(tail_kernel, cudaFuncAttributeMaxDynamicSharedMemorySize, SMEM_TOTAL);
  head_kernel<<<96, 512, SMEM_TOTAL>>>(P);
  cudaLaunchConfig_t cfg = {};
  cfg.gridDim = dim3(36); cfg.blockDim = dim3(512); cfg.dynamicSmemBytes = SMEM_TOTAL; cfg.stream = 0;
  cudaLaunchAttribute attr[1];
  attr[0].id = cudaLaunchAttributeProgrammaticStreamSerialization;
  attr[0].val.programmaticStreamSerializationAllowed = 1;
  cfg.attrs = attr; cfg.numAttrs = 1;
  cudaLaunchKernelEx(&cfg, tail_kernel, P);
}
```

```cpp
#include <cuda.h>
#include <cuda_runtime.h>
#include <cuda_bf16.h>
#include <stdint.h>

namespace {

constexpr int SEQ = 2048, DM = 576, NSEG = 64;
#define LAG_V 5
#define RV_V 1950
#define R1_V 380
#define R0_V 590
#define V1_V 80
#define V2_V 200
#define Q1_V 150
#define Q2_V 290
#define SWAP_V 1
#define ST0_V 200
#define GX_V 1130
#define AD_V 0
#define RS_V 5
#define CALIB 0
#define RF_V 2350
#define RL_V 2000
#define PA1_V 500
#define PA0_V 700
#define XA_V 1
#define XP_V 160
#define CTB_V 6
#define CTC_V 11
#define DP_V 2000
#define NFV_V 24
#define ST_V 5
#define GT_V 5
#define VG_V 1
#define MG_V 3
#define SP_V 0
#define KPV_V 16
#define KP1_V 24
#define KP0_V 28
constexpr int LAG = LAG_V;
constexpr int NT = NSEG + LAG;
constexpr int OXRING = 8;
static_assert(LAG >= 3 && LAG < OXRING, "pipeline lag");
constexpr uint32_t D_RED = RV_V;
__host__ __device__ constexpr uint32_t rank_delay(int r) { return r == 2 ? 0 : r ? R1_V : R0_V; }
__host__ __device__ constexpr int tile_of(int r, int i) { return r == 2 ? i : SWAP_V ? (r ? 3 + i + (i >> 1) : 5 + i + (i > 0)) : 6 - 3 * r + i; }
__host__ __device__ constexpr uint32_t tile_delay(int r, int i) { return (i == 0 ? 0 : r == 2 ? (i == 1 ? V1_V : V2_V) : i == 1 ? Q1_V : Q2_V) * 9 / 16; }
constexpr uint32_t D_DUE = RF_V, D_LATE = RL_V;
constexpr uint32_t D_GX = GX_V * 9 / 16, D_ADAPT = AD_V * 9 / 16;
constexpr int KP_V = KPV_V, KP_1 = KP1_V, KP_0 = KP0_V;
constexpr int KP_MAX = KP_0 > KP_1 ? KP_0 : KP_1;
constexpr uint32_t SB0 = 1024;
constexpr float SM_SCALE = 0.08838834764831845f * 1.4426950408889634f;
constexpr uint32_t SENT = 0x80008000u;
constexpr uint32_t SPIN_LIMIT = 1u << 21;

constexpr int FL_XS = 0;
constexpr int FL_ACC = (NT + 2) * 32;
constexpr int FL_OX = FL_ACC + 128 * 32;
constexpr int FL_SEL = FL_OX + (NT + 1) * 32;
constexpr int FL_Y = FL_SEL + 96 * 4;
constexpr int FL_KV = FL_Y + 512;
constexpr int FL_TOTAL = FL_KV + 128;

__device__ __align__(1024) uint4 g_y[256 * DM];
__device__ __align__(1024) uint4 g_kv[256 * DM];
__device__ __align__(1024) float4 g_acc[2 * 256 * 36 * 32];
__device__ __align__(1024) uint4 g_xs[NT * 4608];
__device__ __align__(1024) uint4 g_ox[OXRING * 512 * 8 * 8];
__device__ __align__(1024) uint4 g_xchg[(256 + 256 + 45) * 512];
__host__ __device__ constexpr uint32_t part_of(int cta) { return (cta < 81 ? 12 + cta * 3 : 13 + cta * 3) * 8192; }
__device__ __align__(1024) uint32_t g_flagsets[2 * FL_TOTAL];
__device__ uint32_t g_epoch;
#define PROF_T(slot) do {} while (0)
#define PROF_END() do {} while (0)
#define PROF_W(cond, slot) do {} while (0)
#define PROF_V(cond, slot, val) do { (void)(val); } while (0)
#define PROF_G(slot) do {} while (0)
#define PROF_OR(slot, val) do {} while (0)
#define PROF_A(idx, val) do { (void)(val); } while (0)
#define PROF_BEGIN() do {} while (0)
#define PROF_MID() do {} while (0)

#define CHINT ""
#define HINT ", 100000"
__device__ __forceinline__ uint32_t pack_bf16(float lo, float hi) {
  uint32_t r; asm("cvt.rn.bf16x2.f32 %0, %1, %2;" : "=r"(r) : "f"(hi), "f"(lo)); return r;
}
__device__ __forceinline__ float bf_lo(uint32_t w) { return __uint_as_float(__byte_perm(w, 0, 0x1044)); }
__device__ __forceinline__ float bf_hi(uint32_t w) { return __uint_as_float(w & 0xFFFF0000u); }
__device__ __forceinline__ uint32_t mapa(uint32_t a, uint32_t r) {
  uint32_t o; asm("mapa.shared::cluster.u32 %0, %1, %2;" : "=r"(o) : "r"(a), "r"(r)); return o;
}
__device__ __forceinline__ void mbar_init(uint32_t bar, uint32_t cnt) {
  asm volatile("mbarrier.init.shared::cta.b64 [%0], %1;" :: "r"(bar), "r"(cnt) : "memory");
}
__device__ __forceinline__ void mbar_expect(uint32_t bar, uint32_t bytes) {
  asm volatile("mbarrier.arrive.expect_tx.shared::cta.b64 _, [%0], %1;" :: "r"(bar), "r"(bytes) : "memory");
}
__device__ __forceinline__ void mbar_arrive(uint32_t bar) {
  asm volatile("mbarrier.arrive.shared::cta.b64 _, [%0];" :: "r"(bar) : "memory");
}
__device__ __forceinline__ void mbar_arrive_if0(uint32_t sel, uint32_t bar) {
  asm volatile("{\n.reg .pred p;\nsetp.eq.u32 p, %1, 0;\n@p mbarrier.arrive.shared::cta.b64 _, [%0];\n}" :: "r"(bar), "r"(sel) : "memory");
}
__device__ __forceinline__ void mbar_expect_if0(uint32_t sel, uint32_t bar, uint32_t bytes) {
  asm volatile("{\n.reg .pred p;\nsetp.eq.u32 p, %1, 0;\n@p mbarrier.arrive.expect_tx.shared::cta.b64 _, [%0], %2;\n}" :: "r"(bar), "r"(sel), "r"(bytes) : "memory");
}
__device__ __forceinline__ void mbar_rarrive_if0(uint32_t sel, uint32_t bar) {
  asm volatile("{\n.reg .pred p;\nsetp.eq.u32 p, %1, 0;\n@p mbarrier.arrive.relaxed.cluster.shared::cluster.b64 _, [%0];\n}" :: "r"(bar), "r"(sel) : "memory");
}
__device__ __forceinline__ void mbar_wait_lim(uint32_t bar, uint32_t par) {
  asm volatile(
    "{\n.reg .pred p;\n.reg .u32 c;\nmov.u32 c, 0;\n"
    "W_%=:\n"
    "mbarrier.try_wait.parity.shared::cta.b64 p, [%0], %1;\n"
    "@p bra D_%=;\n"
    "add.u32 c, c, 1;\nsetp.lt.u32 p, c, %2;\n@p bra W_%=;\ntrap;\n"
    "D_%=:\n}\n" :: "r"(bar), "r"(par), "n"(SPIN_LIMIT) : "memory");
}
__device__ __forceinline__ void mbar_wait(uint32_t bar, uint32_t par) {
  asm volatile(
    "{\n.reg .pred p;\n"
    "W_%=:\n"
    "mbarrier.try_wait.parity.shared::cta.b64 p, [%0], %1" HINT ";\n"
    "@!p bra W_%=;\n}\n" :: "r"(bar), "r"(par) : "memory");
}
__device__ __forceinline__ void mbar_spin(uint32_t bar, uint32_t par) {
  asm volatile("{\n.reg .pred p;\nW_%=:\nmbarrier.try_wait.parity.shared::cta.b64 p, [%0], %1;\n@!p bra W_%=;\n}\n" :: "r"(bar), "r"(par) : "memory");
}
__device__ __forceinline__ uint32_t mbar_test(uint32_t bar, uint32_t par) {
  uint32_t r;
  asm volatile("{\n.reg .pred p;\nmbarrier.test_wait.parity.shared::cta.b64 p, [%1], %2;\nselp.u32 %0, 1, 0, p;\n}" : "=r"(r) : "r"(bar), "r"(par) : "memory");
  return __shfl_sync(0xffffffffu, r, 0);
}
__device__ __forceinline__ void mbar_wait_if(uint32_t& done, uint32_t test, uint32_t bar, uint32_t par, bool force) {
  asm volatile(
    "{\n.reg .pred p, q;\nsetp.ne.u32 p, %0, 0;\n@p bra.uni D_%=;\nsetp.ne.u32 q, %4, 0;\n"
    "mbarrier.test_wait.parity.shared::cta.b64 p, [%1], %3;\n"
    "or.pred p, p, q;\n@!p bra D_%=;\n"
    "W_%=:\n"
    "mbarrier.try_wait.parity.shared::cta.b64 p, [%2], %3, 100000;\n"
    "@!p bra W_%=;\nmov.u32 %0, 1;\nD_%=:\n}\n" : "+r"(done) : "r"(test), "r"(bar), "r"(par), "r"((uint32_t)force) : "memory");
}
template <int ID, int N> __device__ __forceinline__ void bar_sync() { asm volatile("bar.sync %0, %1;" :: "n"(ID), "n"(N) : "memory"); }
template <int ID, int N> __device__ __forceinline__ void bar_arrive() { asm volatile("bar.arrive %0, %1;" :: "n"(ID), "n"(N) : "memory"); }
__device__ __forceinline__ void bar_sync_r(int id, int n) { asm volatile("bar.sync %0, %1;" :: "r"(id), "r"(n) : "memory"); }
__device__ __forceinline__ void bar_arrive_r(int id, int n) { asm volatile("bar.arrive %0, %1;" :: "r"(id), "r"(n) : "memory"); }
__device__ __forceinline__ uint32_t pin(uint32_t x) { return __shfl_sync(0xffffffffu, x, threadIdx.x); }
__device__ __forceinline__ void cluster_sync() {
  asm volatile("barrier.cluster.arrive.aligned;\nbarrier.cluster.wait.aligned;" ::: "memory");
}
__device__ __forceinline__ void fence_async_smem() { asm volatile("fence.proxy.async.shared::cta;" ::: "memory"); }
__device__ __forceinline__ void fence_async_global() { asm volatile("fence.proxy.async.global;" ::: "memory"); }
__device__ __forceinline__ uint4 ld_poll(const uint4* p) {
  uint4 v;
  asm volatile("ld.relaxed.gpu.global.v4.u32 {%0,%1,%2,%3}, [%4];" : "=r"(v.x), "=r"(v.y), "=r"(v.z), "=r"(v.w) : "l"(p) : "memory");
  return v;
}
__device__ __forceinline__ uint32_t rd_clock() { uint64_t c; asm volatile("mov.u64 %0, %%clock64;" : "=l"(c) :: "memory"); return (uint32_t)c; }
__device__ __forceinline__ void spin_until(uint32_t when) {
  asm volatile("{\n.reg .pred p;\n.reg .b64 c;\n.reg .s32 lo;\nS_%=:\nmov.u64 c, %%clock64;\ncvt.u32.u64 lo, c;\nsub.s32 lo, lo, %0;\n"
               "setp.lt.s32 p, lo, 0;\n@p bra.uni S_%=;\n}" :: "r"(when) : "memory");
}
__device__ __forceinline__ uint32_t near_page(uint4* pair, uint32_t mark) {
  uint32_t best0 = ~0u, best1 = ~0u;
  const int lane = threadIdx.x & 31;
#pragma unroll 1
  for (int r = 0; r < 8; r++) {
    if (r >= 4 && !(r & 1) && __all_sync(0xffffffffu, max(best0, best1) - min(best0, best1) > 110u && min(best0, best1) < 420u)) break;
    uint32_t t0, t1, v;
    asm volatile("mov.u32 %0, %%clock;" : "=r"(t0) :: "memory");
    asm volatile("{\n.reg .pred p;\nsetp.eq.u32 p, %2, 0;\nmov.u32 %0, 0;\n@p atom.relaxed.gpu.global.exch.b32 %0, [%1], %3;\n}"
                 : "=&r"(v) : "l"(pair + (r & 1) * 256), "r"(lane), "r"(mark) : "memory");
    asm volatile("{\n.reg .pred p;\nsetp.ne.u32 p, %1, 0x9E3779B9;\nmov.u32 %0, %2;\n@p mov.u32 %0, %%clock;\n}" : "=&r"(t1) : "r"(v), "r"(t0 - 1) : "memory");
    if (r & 1) best1 = min(best1, t1 - t0); else best0 = min(best0, t1 - t0);
  }
  return best1 < best0;
}
__device__ __forceinline__ void st_gpu4(uint4* p, uint32_t a, uint32_t b, uint32_t c, uint32_t d) {
  asm volatile("st.relaxed.gpu.global.v4.u32 [%0], {%1,%2,%3,%4};" :: "l"(p), "r"(a), "r"(b), "r"(c), "r"(d) : "memory");
}
__device__ __forceinline__ void st_gpu1(uint32_t* p, uint32_t a) {
  asm volatile("st.relaxed.gpu.global.u32 [%0], %1;" :: "l"(p), "r"(a) : "memory");
}
__device__ __forceinline__ void st_gpu1_if(bool c, uint32_t* p, uint32_t a) {
  asm volatile("{\n.reg .pred p;\nsetp.ne.u32 p, %2, 0;\n@p st.relaxed.gpu.global.u32 [%0], %1;\n}" :: "l"(p), "r"(a), "r"((uint32_t)c) : "memory");
}
__device__ __forceinline__ void warp_flag_wait(const uint32_t* p, uint32_t target) {
  uint32_t v, n = 0;
  do {
    asm volatile("ld.relaxed.gpu.global.u32 %0, [%1];" : "=r"(v) : "l"(p) : "memory");
    if (++n > SPIN_LIMIT) __trap();
  } while (__any_sync(0xffffffffu, v < target));
}
__device__ __forceinline__ void flag_add(uint32_t* p) {
  asm volatile("red.release.gpu.global.add.u32 [%0], 1;" :: "l"(p) : "memory");
}
__device__ __forceinline__ void bulk_g2s(uint32_t dst, const void* src, uint32_t bytes, uint32_t bar) {
  asm volatile("cp.async.bulk.shared::cluster.global.mbarrier::complete_tx::bytes [%0], [%1], %2, [%3];"
               :: "r"(dst), "l"(src), "r"(bytes), "r"(bar) : "memory");
}
__device__ __forceinline__ void bulk_g2s_mc(uint32_t dst, const void* src, uint32_t bytes, uint32_t bar, uint16_t mask) {
  asm volatile("cp.async.bulk.shared::cluster.global.mbarrier::complete_tx::bytes.multicast::cluster [%0], [%1], %2, [%3], %4;"
               :: "r"(dst), "l"(src), "r"(bytes), "r"(bar), "h"(mask) : "memory");
}
__device__ __forceinline__ void tma_box(uint32_t dst, const CUtensorMap* tm, int col, int row, uint32_t bar) {
  asm volatile("cp.async.bulk.tensor.2d.shared::cluster.global.mbarrier::complete_tx::bytes [%0], [%1, {%2, %3}], [%4];"
               :: "r"(dst), "l"(tm), "r"(col), "r"(row), "r"(bar) : "memory");
}
__device__ __forceinline__ void bulk_s2s(uint32_t dst, uint32_t src, uint32_t bytes, uint32_t bar) {
  asm volatile("cp.async.bulk.shared::cluster.shared::cta.mbarrier::complete_tx::bytes [%0], [%1], %2, [%3];"
               :: "r"(dst), "r"(src), "r"(bytes), "r"(bar) : "memory");
}
__device__ __forceinline__ void bulk_s2g(void* dst, uint32_t src, uint32_t bytes) {
  asm volatile("cp.async.bulk.global.shared::cta.bulk_group [%0], [%1], %2;" :: "l"(dst), "r"(src), "r"(bytes) : "memory");
}
__device__ __forceinline__ void bulk_commit_wait() {
  asm volatile("cp.async.bulk.commit_group;\ncp.async.bulk.wait_group 0;" ::: "memory");
}
__device__ __forceinline__ bool elect_one() {
  uint32_t p; asm volatile("{\n.reg .pred p;\nelect.sync _|p, 0xffffffff;\nselp.u32 %0, 1, 0, p;\n}" : "=r"(p)); return p;
}
__device__ __forceinline__ void ldsm4(uint32_t& r0, uint32_t& r1, uint32_t& r2, uint32_t& r3, uint32_t a) {
  asm volatile("ldmatrix.sync.aligned.m8n8.x4.shared.b16 {%0,%1,%2,%3}, [%4];" : "=r"(r0), "=r"(r1), "=r"(r2), "=r"(r3) : "r"(a) : "memory");
}
__device__ __forceinline__ void ldsm4t(uint32_t& r0, uint32_t& r1, uint32_t& r2, uint32_t& r3, uint32_t a) {
  asm volatile("ldmatrix.sync.aligned.m8n8.x4.trans.shared.b16 {%0,%1,%2,%3}, [%4];" : "=r"(r0), "=r"(r1), "=r"(r2), "=r"(r3) : "r"(a) : "memory");
}
__device__ __forceinline__ void stsm4(uint32_t a, uint32_t r0, uint32_t r1, uint32_t r2, uint32_t r3) {
  asm volatile("stmatrix.sync.aligned.m8n8.x4.shared.b16 [%0], {%1,%2,%3,%4};" :: "r"(a), "r"(r0), "r"(r1), "r"(r2), "r"(r3) : "memory");
}
__device__ __forceinline__ void stsm2(uint32_t a, uint32_t r0, uint32_t r1) {
  asm volatile("stmatrix.sync.aligned.m8n8.x2.shared.b16 [%0], {%1,%2};" :: "r"(a), "r"(r0), "r"(r1) : "memory");
}
__device__ __forceinline__ void stsm4t(uint32_t a, uint32_t r0, uint32_t r1, uint32_t r2, uint32_t r3) {
  asm volatile("stmatrix.sync.aligned.m8n8.x4.trans.shared.b16 [%0], {%1,%2,%3,%4};" :: "r"(a), "r"(r0), "r"(r1), "r"(r2), "r"(r3) : "memory");
}
__device__ __forceinline__ float4 lds4f(uint32_t a) {
  float4 v; asm volatile("ld.shared.v4.f32 {%0,%1,%2,%3}, [%4];" : "=f"(v.x), "=f"(v.y), "=f"(v.z), "=f"(v.w) : "r"(a) : "memory"); return v;
}
__device__ __forceinline__ uint4 lds4(uint32_t a) {
  uint4 v; asm volatile("ld.shared.v4.u32 {%0,%1,%2,%3}, [%4];" : "=r"(v.x), "=r"(v.y), "=r"(v.z), "=r"(v.w) : "r"(a) : "memory"); return v;
}
__device__ __forceinline__ uint32_t lds1(uint32_t a) {
  uint32_t v; asm volatile("ld.shared.u32 %0, [%1];" : "=r"(v) : "r"(a) : "memory"); return v;
}
__device__ __forceinline__ void sts4(uint32_t a, uint4 v) {
  asm volatile("st.shared.v4.u32 [%0], {%1,%2,%3,%4};" :: "r"(a), "r"(v.x), "r"(v.y), "r"(v.z), "r"(v.w) : "memory");
}
__device__ __forceinline__ void sts1(uint32_t a, uint32_t v) { asm volatile("st.shared.u32 [%0], %1;" :: "r"(a), "r"(v) : "memory"); }
__device__ __forceinline__ void mma16816(float (&d)[4], uint32_t a0, uint32_t a1, uint32_t a2, uint32_t a3, uint32_t b0, uint32_t b1) {
  asm volatile("mma.sync.aligned.m16n8k16.row.col.f32.bf16.bf16.f32 {%0,%1,%2,%3}, {%4,%5,%6,%7}, {%8,%9}, {%0,%1,%2,%3};"
               : "+f"(d[0]), "+f"(d[1]), "+f"(d[2]), "+f"(d[3]) : "r"(a0), "r"(a1), "r"(a2), "r"(a3), "r"(b0), "r"(b1));
}
__device__ __forceinline__ void mma1688(float (&d)[4], uint32_t a0, uint32_t a1, uint32_t b0) {
  asm volatile("mma.sync.aligned.m16n8k8.row.col.f32.bf16.bf16.f32 {%0,%1,%2,%3}, {%4,%5}, {%6}, {%0,%1,%2,%3};"
               : "+f"(d[0]), "+f"(d[1]), "+f"(d[2]), "+f"(d[3]) : "r"(a0), "r"(a1), "r"(b0));
}
__device__ __forceinline__ float rcp(float x) { float r; asm("rcp.approx.ftz.f32 %0, %1;" : "=f"(r) : "f"(x)); return r; }
__device__ __forceinline__ float sqr(float x) { float r; asm("sqrt.approx.f32 %0, %1;" : "=f"(r) : "f"(x)); return r; }
__device__ __forceinline__ float ex2(float x) { float r; asm("ex2.approx.ftz.f32 %0, %1;" : "=f"(r) : "f"(x)); return r; }

__device__ __forceinline__ uint32_t bf2_op(uint32_t a, uint32_t b, uint32_t c) {
  uint32_t r; asm("fma.rn.bf16x2 %0, %1, %2, %3;" : "=r"(r) : "r"(a), "r"(b), "r"(c)); return r;
}
__device__ __forceinline__ uint32_t bf2_mul(uint32_t a, uint32_t b) {
  uint32_t r; asm("mul.rn.bf16x2 %0, %1, %2;" : "=r"(r) : "r"(a), "r"(b)); return r;
}
__device__ __forceinline__ uint32_t bf2_add(uint32_t a, uint32_t b) {
  uint32_t r; asm("add.rn.bf16x2 %0, %1, %2;" : "=r"(r) : "r"(a), "r"(b)); return r;
}

__host__ __device__ constexpr uint64_t mkdesc(uint32_t off, uint32_t lbo, uint32_t sbo, uint32_t sw) {
  return (uint64_t)((SB0 + off) >> 4) | ((uint64_t)(lbo >> 4) << 16) | ((uint64_t)(sbo >> 4) << 32) | ((uint64_t)sw << 62);
}
__device__ __forceinline__ void wg_fence() { asm volatile("wgmma.fence.sync.aligned;" ::: "memory"); }
__device__ __forceinline__ void wg_commit() { asm volatile("wgmma.commit_group.sync.aligned;" ::: "memory"); }
template <int N> __device__ __forceinline__ void wg_wait() { asm volatile("wgmma.wait_group.sync.aligned %0;" :: "n"(N) : "memory"); }
template <int N> __device__ __forceinline__ void reg_fence(float (&d)[N]) {
#pragma unroll
  for (int i = 0; i < N; i++) asm volatile("" : "+f"(d[i]) :: "memory");
}

#define F4(d, o) "+f"(d[o]), "+f"(d[o + 1]), "+f"(d[o + 2]), "+f"(d[o + 3])
template <int SC, int TB> __device__ __forceinline__ void wg_rs(float (&d)[8], const uint32_t* a, uint64_t db, int ob) {
  asm volatile("{\n.reg .pred p;\n.reg .b64 b;\nsetp.ne.b32 p, %13, 0;\nadd.s64 b, %12, %15;\n"
    "wgmma.mma_async.sync.aligned.m64n16k16.f32.bf16.bf16 {%0,%1,%2,%3,%4,%5,%6,%7}, {%8,%9,%10,%11}, b, p, 1, 1, %14;\n}\n"
    : F4(d, 0), F4(d, 4) : "r"(a[0]), "r"(a[1]), "r"(a[2]), "r"(a[3]), "l"(db), "n"(SC), "n"(TB), "l"((uint64_t)ob));
}
template <int SC, int TB> __device__ __forceinline__ void wg_rs(float (&d)[12], const uint32_t* a, uint64_t db, int ob) {
  asm volatile("{\n.reg .pred p;\n.reg .b64 b;\nsetp.ne.b32 p, %17, 0;\nadd.s64 b, %16, %19;\n"
    "wgmma.mma_async.sync.aligned.m64n24k16.f32.bf16.bf16 {%0,%1,%2,%3,%4,%5,%6,%7,%8,%9,%10,%11}, {%12,%13,%14,%15}, b, p, 1, 1, %18;\n}\n"
    : F4(d, 0), F4(d, 4), F4(d, 8) : "r"(a[0]), "r"(a[1]), "r"(a[2]), "r"(a[3]), "l"(db), "n"(SC), "n"(TB), "l"((uint64_t)ob));
}
template <int SC, int TB> __device__ __forceinline__ void wg_rs(float (&d)[16], const uint32_t* a, uint64_t db, int ob) {
  asm volatile("{\n.reg .pred p;\n.reg .b64 b;\nsetp.ne.b32 p, %21, 0;\nadd.s64 b, %20, %23;\n"
    "wgmma.mma_async.sync.aligned.m64n32k16.f32.bf16.bf16 {%0,%1,%2,%3,%4,%5,%6,%7,%8,%9,%10,%11,%12,%13,%14,%15}, {%16,%17,%18,%19}, b, p, 1, 1, %22;\n}\n"
    : F4(d, 0), F4(d, 4), F4(d, 8), F4(d, 12) : "r"(a[0]), "r"(a[1]), "r"(a[2]), "r"(a[3]), "l"(db), "n"(SC), "n"(TB), "l"((uint64_t)ob));
}
template <int SC, int TB> __device__ __forceinline__ void wg_rs(float (&d)[28], const uint32_t* a, uint64_t db, int ob) {
  asm volatile("{\n.reg .pred p;\n.reg .b64 b;\nsetp.ne.b32 p, %33, 0;\nadd.s64 b, %32, %35;\n"
    "wgmma.mma_async.sync.aligned.m64n56k16.f32.bf16.bf16 {%0,%1,%2,%3,%4,%5,%6,%7,%8,%9,%10,%11,%12,%13,%14,%15,%16,%17,%18,%19,%20,%21,%22,%23,%24,%25,%26,%27}, {%28,%29,%30,%31}, b, p, 1, 1, %34;\n}\n"
    : F4(d, 0), F4(d, 4), F4(d, 8), F4(d, 12), F4(d, 16), F4(d, 20), F4(d, 24) : "r"(a[0]), "r"(a[1]), "r"(a[2]), "r"(a[3]), "l"(db), "n"(SC), "n"(TB), "l"((uint64_t)ob));
}
template <int SC, int TB> __device__ __forceinline__ void wg_ss(float (&d)[8], uint64_t da, int oa, uint64_t db, int ob) {
  asm volatile("{\n.reg .pred p;\n.reg .b64 a, b;\nsetp.ne.b32 p, %10, 0;\nadd.s64 a, %8, %12;\nadd.s64 b, %9, %13;\n"
    "wgmma.mma_async.sync.aligned.m64n16k16.f32.bf16.bf16 {%0,%1,%2,%3,%4,%5,%6,%7}, a, b, p, 1, 1, 1, %11;\n}\n"
    : F4(d, 0), F4(d, 4) : "l"(da), "l"(db), "n"(SC), "n"(TB), "l"((uint64_t)oa), "l"((uint64_t)ob));
}
template <int SC, int TB> __device__ __forceinline__ void wg_ss(float (&d)[12], uint64_t da, int oa, uint64_t db, int ob) {
  asm volatile("{\n.reg .pred p;\n.reg .b64 a, b;\nsetp.ne.b32 p, %14, 0;\nadd.s64 a, %12, %16;\nadd.s64 b, %13, %17;\n"
    "wgmma.mma_async.sync.aligned.m64n24k16.f32.bf16.bf16 {%0,%1,%2,%3,%4,%5,%6,%7,%8,%9,%10,%11}, a, b, p, 1, 1, 1, %15;\n}\n"
    : F4(d, 0), F4(d, 4), F4(d, 8) : "l"(da), "l"(db), "n"(SC), "n"(TB), "l"((uint64_t)oa), "l"((uint64_t)ob));
}
template <int SC, int TB> __device__ __forceinline__ void wg_ss(float (&d)[16], uint64_t da, int oa, uint64_t db, int ob) {
  asm volatile("{\n.reg .pred p;\n.reg .b64 a, b;\nsetp.ne.b32 p, %18, 0;\nadd.s64 a, %16, %20;\nadd.s64 b, %17, %21;\n"
    "wgmma.mma_async.sync.aligned.m64n32k16.f32.bf16.bf16 {%0,%1,%2,%3,%4,%5,%6,%7,%8,%9,%10,%11,%12,%13,%14,%15}, a, b, p, 1, 1, 1, %19;\n}\n"
    : F4(d, 0), F4(d, 4), F4(d, 8), F4(d, 12) : "l"(da), "l"(db), "n"(SC), "n"(TB), "l"((uint64_t)oa), "l"((uint64_t)ob));
}
template <int SC, int TB> __device__ __forceinline__ void wg_ss(float (&d)[20], uint64_t da, int oa, uint64_t db, int ob) {
  asm volatile("{\n.reg .pred p;\n.reg .b64 a, b;\nsetp.ne.b32 p, %22, 0;\nadd.s64 a, %20, %24;\nadd.s64 b, %21, %25;\n"
    "wgmma.mma_async.sync.aligned.m64n40k16.f32.bf16.bf16 {%0,%1,%2,%3,%4,%5,%6,%7,%8,%9,%10,%11,%12,%13,%14,%15,%16,%17,%18,%19}, a, b, p, 1, 1, 1, %23;\n}\n"
    : F4(d, 0), F4(d, 4), F4(d, 8), F4(d, 12), F4(d, 16) : "l"(da), "l"(db), "n"(SC), "n"(TB), "l"((uint64_t)oa), "l"((uint64_t)ob));
}
template <int SC, int TB> __device__ __forceinline__ void wg_ss(float (&d)[28], uint64_t da, int oa, uint64_t db, int ob) {
  asm volatile("{\n.reg .pred p;\n.reg .b64 a, b;\nsetp.ne.b32 p, %30, 0;\nadd.s64 a, %28, %32;\nadd.s64 b, %29, %33;\n"
    "wgmma.mma_async.sync.aligned.m64n56k16.f32.bf16.bf16 {%0,%1,%2,%3,%4,%5,%6,%7,%8,%9,%10,%11,%12,%13,%14,%15,%16,%17,%18,%19,%20,%21,%22,%23,%24,%25,%26,%27}, a, b, p, 1, 1, 1, %31;\n}\n"
    : F4(d, 0), F4(d, 4), F4(d, 8), F4(d, 12), F4(d, 16), F4(d, 20), F4(d, 24) : "l"(da), "l"(db), "n"(SC), "n"(TB), "l"((uint64_t)oa), "l"((uint64_t)ob));
}

template <int SC> __device__ __forceinline__ void wg_sskk(float (&d)[16], uint64_t da, int oa, uint64_t db, int ob) {
  asm volatile("{\n.reg .pred p;\n.reg .b64 a, b;\nsetp.ne.b32 p, %18, 0;\nadd.s64 a, %16, %19;\nadd.s64 b, %17, %20;\n"
    "wgmma.mma_async.sync.aligned.m64n32k16.f32.bf16.bf16 {%0,%1,%2,%3,%4,%5,%6,%7,%8,%9,%10,%11,%12,%13,%14,%15}, a, b, p, 1, 1, 0, 0;\n}\n"
    : F4(d, 0), F4(d, 4), F4(d, 8), F4(d, 12) : "l"(da), "l"(db), "n"(SC), "l"((uint64_t)oa), "l"((uint64_t)ob));
}

template <int NK> __device__ __forceinline__ void load_afrags(uint32_t* a, uint32_t tile, int w, int lane) {
  int i = lane >> 3, r = lane & 7;
  uint32_t base = tile + ((i >> 1) * 8 + r) * 128 + (((2 * w + (i & 1)) ^ r) << 4);
#pragma unroll
  for (int kk = 0; kk < NK; kk++) ldsm4t(a[4 * kk], a[4 * kk + 1], a[4 * kk + 2], a[4 * kk + 3], base + kk * 2048);
}

constexpr uint32_t Q_WL = 0;
constexpr uint32_t Q_WO = 24576;
constexpr uint32_t Q_OX = Q_WO;
constexpr uint32_t Q_X = 73728;
constexpr uint32_t Q_CS = 10240;
constexpr uint32_t Q_STG = 165888;
constexpr uint32_t Q_OB = 190464;
constexpr uint32_t Q_SIN = 194560;
constexpr uint32_t Q_PX = 204800;
constexpr uint32_t Q_SOUT = Q_PX;
constexpr int Q_KR = 30;
constexpr uint32_t BARS = 228352;
constexpr uint32_t B_CP = BARS;
constexpr uint32_t B_OK = BARS + 408;
constexpr uint32_t B_G0 = BARS + 272;
constexpr uint32_t B_XF = BARS + 72;
constexpr uint32_t B_E = BARS + 224;
constexpr uint32_t B_SM = BARS + 160;
constexpr uint32_t B_O = BARS + 168;
constexpr uint32_t B_P = BARS + 176;
constexpr uint32_t B_OXREADY = BARS + 192;
constexpr uint32_t B_OXFREE = BARS + 200;
constexpr uint32_t B_REF = BARS + 208;
constexpr uint32_t B_AN = BARS + 264;
constexpr uint32_t B_PZ = BARS + 256;
constexpr uint32_t B_RES = BARS + 216;
constexpr uint32_t Q_REF = BARS + 288;
constexpr uint32_t Q_SEL = BARS + 304;
constexpr uint32_t Q_SET = BARS + 360;
constexpr uint32_t SM_BYTES = 4 * 1024, SX_BYTES = 2560, PX_BYTES = 2 * 14 * 128;
constexpr int W_KR = 29;
constexpr uint32_t W_RING = 0;
constexpr uint32_t W_WS = 196608;
constexpr uint32_t W_FT = 0;
constexpr uint32_t W_FO = 18688;
constexpr uint32_t W_Z = 30720;
constexpr uint32_t W_RS = 49152;
constexpr uint32_t W_ST = 28672;
constexpr int CT_A = 2, CT_B = CTB_V, CT_C = CTC_V;
static_assert(36 * CT_C <= 36 * CT_B + 192, "kv stages");
constexpr uint32_t C_U = 256 + 4096;
constexpr uint32_t C_CH = C_U + 64 + 8192 + 96;
constexpr uint32_t B_FULL = BARS;
constexpr uint32_t B_EMPTY = BARS + 128;
constexpr uint32_t B_FT = BARS + 160;
constexpr uint32_t B_RF = BARS + 176;
constexpr uint32_t B_WT = BARS + 248;
constexpr uint32_t W_K1 = BARS + 240;
constexpr uint32_t SMEM_TOTAL = BARS + 512;

struct Params {
  CUtensorMap tm;
  const __nv_bfloat16 *x0, *wq, *wk, *wv, *wo, *mem0, *ck, *cv, *shift, *ssm_k, *ssm_d;
  __nv_bfloat16* out;
  uint4* memx;
  uint64_t d_x, d_wl, d_ring, d_ws;
};

constexpr uint64_t D_QK = mkdesc(Q_STG, 768, 128, 0), D_WO = mkdesc(Q_WO, 16, 1024, 1), D_OB = mkdesc(Q_OB, 128, 2048, 0), D_PX = mkdesc(Q_PX, 128, 768, 0);
constexpr uint64_t D_V = mkdesc(Q_STG, 128, 768, 0);

#define g_flags (g_flagsets + lds1(sb + Q_SET))

__device__ __forceinline__ int rd_cid() { uint32_t v; asm volatile("mov.u32 %0, %%clusterid.x;" : "=r"(v)); return v; }
__device__ __forceinline__ int rd_rank() { uint32_t v; asm volatile("mov.u32 %0, %%cluster_ctarank;" : "=r"(v)); return v; }
__device__ __forceinline__ int rd_lane() { uint32_t v; asm volatile("mov.u32 %0, %%laneid;" : "=r"(v)); return v; }
__device__ __forceinline__ int rd_warp() { uint32_t v; asm volatile("mov.u32 %0, %%tid.x;" : "=r"(v)); return __shfl_sync(0xffffffffu, v >> 5, 0); }

template <int NA>
__device__ __forceinline__ void proj_step(float (&acc)[NA], const uint32_t* a, uint64_t db, uint64_t dwl, int k) {
  const int ob = (k >> 2) * (Q_CS / 16) + (k & 3) * 16;
  if (k == 0) wg_rs<0, 1>(acc, a, db, ob);
  else if (k % 6 != 5) wg_rs<1, 1>(acc, a + 4 * (k - k / 6), db, ob);
  else wg_ss<1, 1>(acc, dwl, 128 * (k / 6), db, ob);
}
__device__ __forceinline__ void stage_groups(uint32_t stl, const uint32_t (&pk)[14]) {
#pragma unroll
  for (int h = 0; h < 2; h++) {
    stsm4(stl + h * 768 + 256, pk[h], pk[2 + h], pk[4 + h], 0);
    stsm4(stl + h * 768 + 6144 + 128, pk[6 + h], pk[8 + h], pk[10 + h], pk[12 + h]);
  }
}
__device__ __forceinline__ void head_main(uint32_t sb, const Params& P) {
  const int lane = threadIdx.x & 31, warp = rd_warp(), w = warp & 3, wg = warp >> 2, rank = rd_rank();
  uint32_t a[4 * Q_KR];
  {
    const int tid = threadIdx.x & 127;
    const __nv_bfloat16* src = (rank == 2 ? P.wv + wg * 64 : (wg ? P.wk : P.wq) + rank * 64) + rd_cid() * 128 + (size_t)(tid >> 3) * 4096 + (tid & 7) * 8;
    const uint32_t so = (tid >> 3) * 128 + (((tid & 7) ^ ((tid >> 3) & 7)) << 4), st = sb + Q_X + wg * (Q_KR * 2048);
    uint4 v[36];
#pragma unroll
    for (int k = 0; k < 36; k++) v[k] = __ldg((const uint4*)(src + (size_t)k * 65536));
#pragma unroll
    for (int k = 0; k < 36; k++) sts4(so + (k % 6 == 5 ? sb + Q_WL + wg * 12288 + (k / 6) * 2048 : st + (k - k / 6) * 2048), v[k]);
    bar_sync_r(9 + wg, wg ? 128 : 224);
    PROF_G(7);
    load_afrags<Q_KR>(a, st, w, lane);
    fence_async_smem();
    bar_arrive<11, 384>();
  }
  cluster_sync();
  PROF_G(8);
  const uint64_t dwl = P.d_wl + wg * 768, dq = D_QK + wg * 384;
  const uint32_t stg = sb + Q_STG + wg * 12288 + 2 * w * 768;
  const uint32_t stm = pin(stg + (lane >> 4) * 6144 + ((lane >> 3) & 1) * 768 + (lane & 7) * 16), stl = pin(stg + lane * 16);
  const uint32_t rel = mapa(sb + B_E, 0), rev = mapa(sb + B_E, 2), sel = pin(threadIdx.x & 127), arm = pin(threadIdx.x - 128 > 8), xfa = pin(sb + B_XF + 8 * lane);
  const uint32_t sx = sb + (wg == rank ? Q_SIN + rank * 4096 : Q_SOUT + 2048), s0 = w ? sx + (2 * w - 1) * 512 : sb + Q_SOUT + wg * 1024, s1 = sx + 2 * w * 512;
  const uint32_t sd0 = pin(s0 + lane * 16), sd1 = pin(s1 + lane * 16), sr = sb + Q_SIN + rank * 4096;
  const int kp = rank == 2 ? KP_V : rank ? KP_1 : KP_0;
  const uint32_t selq = pin(sel | rank >> 1);
    const uint32_t pz = sb + (rank == 2 ? B_SM : B_PZ);
  uint32_t pk[14] = {};
#pragma unroll 1
  for (int t = 0;; t++) {
    const uint32_t par = t & 1;
    uint32_t paused = 0;
    if (t == 0) {
      mbar_wait(sb + B_XF, 0);
    } else {
      float m[12];
#pragma unroll
      for (int c = 0; c < 9; c++) {
        mbar_spin(sb + B_OK + 8 * c, par ^ 1);
        if (c == 0 || c == 3 || c == 8) PROF_W(warp == 0, c == 0 ? 0 : c == 3 ? 1 : 3);
        if (c == 8) mbar_rarrive_if0(selq, rev + 24);
        wg_fence();
#pragma unroll
        for (int k = 4 * c; k < 4 * c + 4; k++) proj_step(m, a, P.d_x, dwl, k);
        if (c == 0) { mbar_expect_if0(arm, xfa, 7168); mbar_rarrive_if0(sel | (rank ^ 2), rel); }
        if (c == XA_V) mbar_rarrive_if0(selq, rel);
        if (c == MG_V) mbar_rarrive_if0(sel, rev);
        if (c == ST_V && rank == 2) {
          if (t > 1) bar_sync<3, 384>();
          stage_groups(stl, pk);
        }
      }
      wg_commit();
      if (rank == 2 && t < NT) { mbar_wait(sb + B_XF, par); paused = mbar_test(pz, par ^ 1); }
      wg_wait<0>();
      reg_fence(m);
      PROF_W(warp == 0, 2);
      stsm4(stm, pack_bf16(m[0], m[1]), pack_bf16(m[2], m[3]), pack_bf16(m[4], m[5]), pack_bf16(m[6], m[7]));
      stsm2(stm + 128, pack_bf16(m[8], m[9]), pack_bf16(m[10], m[11]));
      if (rank == 2) {
        bar_arrive<1, 384>();
        mbar_rarrive_if0(sel, rel + 16);
        if (t == NT) break;
        if (paused) mbar_wait(sb + B_RES, par ^ 1);
      } else {
        float s[20];
        bar_sync<1, 256>();
        fence_async_smem();
        wg_fence();
        wg_ss<0, 1>(s, dq, 0, dq, 768);
#pragma unroll
        for (int i = 1; i < 4; i++) wg_ss<1, 1>(s, dq, 96 * i, dq, 768 + 96 * i);
        wg_commit();
        mbar_rarrive_if0(sel ^ 96, rel + 16);
        if (t < NT) mbar_wait(sb + B_XF, par);
        wg_wait<0>();
        reg_fence(s);
        if (w < 3) {
          sts4(sd0, make_uint4(pack_bf16(s[0], s[1]), pack_bf16(s[4], s[5]), pack_bf16(s[8], s[9]), pack_bf16(s[12], s[13])));
          if (w != 1) sts1(sd0 + 512, pack_bf16(s[16], s[17]));
          if (w == 0) {
            fence_async_smem();
            __syncwarp();
            if (elect_one()) bulk_s2s(mapa(sr + wg * 1024, 2), s0, 1024, mapa(sb + B_SM, 2));
            __syncwarp();
            PROF_W(wg == 1, 4); PROF_W(wg == 0, 8);
          }
          if (w < 2) sts4(sd1, make_uint4(pack_bf16(s[2], s[3]), pack_bf16(s[6], s[7]), pack_bf16(s[10], s[11]), pack_bf16(s[14], s[15])));
          bar_arrive<8, 224>();
        }
        if (t == NT) break;
      }
    }
    float e[28];
#pragma unroll
    for (int k = 0; k < 36; k++) {
      if (k == 2 && t > 0) {
        mbar_expect_if0(arm, xfa - (B_XF - B_CP), 2048);
        mbar_expect_if0(sel | wg, sb + B_G0, 9216);
      }
      if (k % 4 == 0 && k) mbar_wait(sb + B_XF + 2 * k, par);
      if (k == 0) PROF_W(warp == 0, 5);
      if (k % 2 == 0 && k && k <= KP_MAX) {
        mbar_wait_if(paused, pz, sb + B_RES, par ^ 1, k == kp);
      }
      if (k % 4 == 0 || (k % 2 == 0 && k <= KP_MAX)) wg_fence();
      proj_step(e, a, P.d_x + 192, dwl, k);
    }
    wg_commit();
    mbar_wait(sb + B_G0, par);
    wg_wait<0>();
    reg_fence(e);
    PROF_W(warp == 0, 10);
#pragma unroll
    for (int i = 0; i < 14; i++) pk[i] = pack_bf16(e[2 * i], e[2 * i + 1]);
    if (rank != 2) stage_groups(stl, pk);
    PROF_W(warp == 0, 12);
  }
  cluster_sync();
}

__device__ __forceinline__ uint32_t next_tick() {
  uint64_t g0, g1;
  asm volatile("mov.u64 %0, %%globaltimer;" : "=l"(g0) :: "memory");
#pragma unroll 1
  for (int n = 0; n < 8; n++) {
    asm volatile("mov.u64 %0, %%globaltimer;" : "=l"(g1) :: "memory");
    if (__any_sync(0xffffffffu, (uint32_t)g1 != (uint32_t)g0)) break;
  }
  return (uint32_t)g1;
}
__device__ __forceinline__ void wait_ns(uint32_t when) {
  uint32_t c;
  asm volatile("{\n.reg .pred p;\n.reg .b64 g;\n.reg .s32 lo;\nS_%=:\nmov.u64 g, %%globaltimer;\ncvt.u32.u64 lo, g;\nsub.s32 lo, %1, lo;\n"
               "setp.gt.s32 p, lo, 31;\n@p bra.uni S_%=;\nmov.u64 g, %%clock64;\ncvt.u32.u64 %0, g;\nshl.b32 lo, lo, 1;\nadd.s32 %0, %0, lo;\n}" : "=&r"(c) : "r"(when) : "memory");
  spin_until(c - 30);
}
template <bool TAG>
__device__ __forceinline__ uint32_t poll4(uint4 (&v)[4], const uint4* src, uint32_t tag) {
#pragma unroll
  for (int j = 0; j < 4; j++) v[j] = ld_poll(src + j * 32);
  uint32_t n = 0;
  while (__any_sync(0xffffffffu, TAG ? (((v[0].x ^ tag) | (v[1].x ^ tag) | (v[2].x ^ tag) | (v[3].x ^ tag)) & 1) != 0
                                     : (v[0].x == SENT || v[1].x == SENT || v[2].x == SENT || v[3].x == SENT))) {
#pragma unroll
    for (int j = 0; j < 4; j++) if (TAG ? ((v[j].x ^ tag) & 1) != 0 : v[j].x == SENT) v[j] = ld_poll(src + j * 32);
    if (++n > SPIN_LIMIT) __trap();
  }
  return n;
}

__device__ __forceinline__ void read_reference(uint32_t sb, const Params& P, uint32_t& ref, int rank, int t) {
  const int lane = rd_lane();
  const uint32_t* tms = (const uint32_t*)(P.memx + 9 * 512 + lds1(sb + Q_SEL + 48) / 16 + (rd_cid() >> 4) * 32 + lane) + rank;
  if (t > 1) wait_ns(ref + D_GX + (D_DUE - rank_delay(rank)) * 9 / 16); else ref = next_tick();
  uint32_t d, n = 0;
  do {
    asm volatile("ld.relaxed.gpu.global.u32 %0, [%1];" : "=r"(d) : "l"(tms) : "memory");
    if (++n > SPIN_LIMIT) __trap();
  } while (__any_sync(0xffffffffu, (d ^ t) & 255));
  ref += __reduce_max_sync(0xffffffffu, (int)(d - (ref << 6))) >> 6;
  sts1(sb + Q_REF, ref);
  __syncwarp();
  mbar_arrive_if0(lane, sb + B_REF);
  PROF_A(13, n);
  PROF_T(19);
  PROF_V(true, 11, ref - (D_RED + rank_delay(rank)) * 9 / 16);
}
template <int STEP>
__device__ __forceinline__ void check_tiles(uint32_t sb, const Params& P, int w, int t) {
  const int lane = rd_lane();
  uint32_t chk = sb + Q_X + w * Q_CS + lane * 32 + (lane >> 2) * 4, bad = 0;
#pragma unroll 1
  for (uint32_t bar = sb + B_CP + 8 * w; bar <= sb + B_CP + 64; bar += 8 * STEP, chk += STEP * Q_CS) {
    uint32_t ok;
    asm volatile("{\n.reg .pred p, q;\n.reg .b32 a, b;\nsetp.eq.u32 q, %4, 0;\n"
                 "W_%=:\nmbarrier.try_wait.parity.shared::cta.b64 p, [%1], %2" CHINT ";\n@!p bra W_%=;\n"
                 "ld.shared.u32 a, [%3];\nld.shared.u32 b, [%3 + 1024];\nsetp.ne.u32 p, a, 0x80008000;\nsetp.ne.and.u32 p, b, 0x80008000, p;\n"
                 "vote.sync.all.pred p, p, 0xFFFFFFFF;\nand.pred q, q, p;\n@q mbarrier.arrive.shared::cta.b64 _, [%1 + %5];\nselp.u32 %0, 1, 0, p;\n}"
                 : "=r"(ok) : "r"(bar), "r"(~t & 1), "r"(chk), "r"(lane), "n"(B_OK - B_CP) : "memory");
    const int c = (bar - sb - B_CP) / 8;
    if (!ok) {
      uint4 v[4];
      poll4<false>(v, P.memx + c * 512 + (t & 1) * 128 + lds1(sb + Q_SEL + 4 * c) / 16 + lane, 0);
#pragma unroll
      for (int j = 0; j < 4; j++) sts4(sb + Q_X + c * Q_CS + j * 512 + lane * 16, v[j]);
      fence_async_smem();
      __syncwarp();
      mbar_arrive_if0(lane, bar + B_OK - B_CP);
      if (t > LAG + 4) sts1(sb + Q_REF + 4, lds1(sb + Q_REF + 4) + 1);
      PROF_OR(7, 1 << c);
      PROF_A(c, 1);
      bad |= c < 3 * VG_V + 3;
    }
    if (STEP == 3) mbar_arrive_if0(lane | (c / 3 != (bad ? 2 : VG_V)), sb + B_E + 24);
  }
}
__device__ __forceinline__ void load_scores(float (&s)[10], uint32_t sa) {
  const uint4 a = lds4(sa), b = lds4(sa + 4096);
  const uint32_t a4 = lds1(sa + 512), b4 = lds1(sa + 4608);
  const uint32_t e[5] = {bf2_add(a.x, b.x), bf2_add(a.y, b.y), bf2_add(a.z, b.z), bf2_add(a.w, b.w), bf2_add(a4, b4)};
#pragma unroll
  for (int i = 0; i < 5; i++) { s[2 * i] = bf_lo(e[i]); s[2 * i + 1] = bf_hi(e[i]); }
}
__device__ __forceinline__ void softmax_num(float (&s)[10]) {
  float mx = fmaxf(fmaxf(fmaxf(s[0], s[1]), fmaxf(s[2], s[3])), fmaxf(fmaxf(s[4], s[5]), fmaxf(s[6], s[7])));
  mx = fmaxf(mx, fmaxf(s[8], s[9]));
  const float m1 = __shfl_xor_sync(0xffffffffu, mx, 1), m2 = __shfl_xor_sync(0xffffffffu, mx, 2), m3 = __shfl_xor_sync(0xffffffffu, mx, 3);
  mx = fmaxf(fmaxf(mx, m1), fmaxf(m2, m3));
  mx *= -SM_SCALE;
#pragma unroll
  for (int i = 0; i < 10; i++) s[i] = ex2(fmaf(s[i], SM_SCALE, mx));
}

template <int NF>
__device__ __forceinline__ void wo_tiles(uint32_t sb, const uint32_t (&f)[76], char* d0, uint32_t pg, uint32_t rs, int t) {
  float d[2][8];
  auto mma = [&](int i, int k0, int k1) {
#pragma unroll
    for (int k = k0; k < k1; k++) {
      if (8 * i + k >= NF && k == 0) wg_ss<0, 0>(d[i & 1], D_WO, 1024 * i, D_OB, 0);
      else if (8 * i + k >= NF || (i == 2 && ((k & 1) || k == 6))) wg_ss<1, 0>(d[i & 1], D_WO, 1024 * i + 128 * k, D_OB, 16 * k);
      else if (k == 0) wg_rs<0, 0>(d[i & 1], f + 32 * i, D_OB, 0);
      else wg_rs<1, 0>(d[i & 1], f + (i < 2 ? 32 * i + 4 * k : 64 + 2 * k), D_OB, 16 * k);
    }
    wg_commit();
  };
  auto put = [&](float (&q)[8]) {
    reg_fence(q);
    st_gpu4((uint4*)d0, (pack_bf16(q[0], q[1]) & ~1u) | ((t - 1) >> 1 & 1), pack_bf16(q[4], q[5]), pack_bf16(q[2], q[3]), pack_bf16(q[6], q[7]));
    __syncwarp();
  };
  wg_fence();
  mma(0, 0, 8);
  mma(1, 0, 8);
  wg_wait<1>();
  put(d[0]);
  PROF_W(threadIdx.x < 288, 14);
  wg_fence();
  mma(2, 0, RS_V);
  d0 += pg & 0xFFFF;
  wg_wait<1>();
  put(d[1]);
  PROF_W(threadIdx.x < 288, 15);
  mma(2, RS_V, 8);
  d0 += pg >> 16;
  wg_wait<1>();
  mbar_arrive_if0(rs, sb + B_RES);
  PROF_W(threadIdx.x < 288, 17);
  wg_wait<0>();
  put(d[0]);
  PROF_W(threadIdx.x < 288, 16);
}
__device__ __forceinline__ void probe_pages(uint32_t sb, const Params& P, int own) {
  const int lane = threadIdx.x & 31;
  const uint32_t first = own ? part_of(blockIdx.x) : 0;
  const uint32_t sel = __shfl_sync(0xffffffffu, near_page(P.memx + first / 16 + (own ? 0 : (blockIdx.x & 63) * 2), own ? 1 : SENT), 0);
  if (lane < (own ? 3 : 10))
    sts1(sb + Q_SEL + 4 * (own ? 9 + lane : lane == 9 ? 12 : lane), ((sel ^ __popc(((first + lane * 8192) ^ first) & 0xB2000)) & 1) * 4096);
}
__device__ __forceinline__ void head_aux(uint32_t sb, const Params& P) {
  const int tid = threadIdx.x & 127, w = rd_warp() & 3, rank = rd_rank(), head = __shfl_sync(0xffffffffu, rd_cid(), 0);
  uint32_t m0[20];
  {
    uint4 a[12], b[12];
#pragma unroll
    for (int j = 0; j < 12; j++) {
      const int u = j;
      const int r = (u & 3) * 32 + (tid >> 2);
      const uint4* src = (const uint4*)(P.wo + (size_t)(head * 128 + (r & 64) + (r & 7) * 8 + ((r >> 3) & 7)) * DM + tile_of(rank, u >> 2) * 64) + (tid & 3) * 2;
      a[j] = __ldg(src); b[j] = __ldg(src + 1);
    }
#pragma unroll
    for (int j = 0; j < 12; j++) {
      const int u = j;
      const int r = (u & 3) * 32 + (tid >> 2);
      const uint32_t dst = sb + Q_WO + (u >> 2) * 16384 + r * 128 + ((((tid & 3) * 2) ^ (r & 7) ^ ((head >> 2) & 1)) << 4);
      sts4(dst, make_uint4(__byte_perm(a[j].x, a[j].y, 0x5410), __byte_perm(a[j].z, a[j].w, 0x5410), __byte_perm(b[j].x, b[j].y, 0x5410), __byte_perm(b[j].z, b[j].w, 0x5410)));
      sts4(dst ^ 16, make_uint4(__byte_perm(a[j].x, a[j].y, 0x7632), __byte_perm(a[j].z, a[j].w, 0x7632), __byte_perm(b[j].x, b[j].y, 0x7632), __byte_perm(b[j].z, b[j].w, 0x7632)));
    }
  }
#pragma unroll
  for (int j = 0; j < 20; j++) {
    const int k = min(tid + (j >> 2) * 128, DM - 1);
    m0[j] = bf2_add(__bfloat16_as_ushort(P.mem0[2 * (j & 3) * DM + k]) | (uint32_t)__bfloat16_as_ushort(P.mem0[(2 * (j & 3) + 1) * DM + k]) << 16, 0);
  }
#pragma unroll
  for (int i = 0; i < 6; i++) sts4(sb + Q_PX + (i * 128 + tid) * 16, make_uint4(0, 0, 0, 0));
  bar_sync<11, 384>();
#pragma unroll
  for (int j = 0; j < 5; j++) {
    const int k = min(tid + j * 128, DM - 1);
    sts4(sb + Q_X + (k >> 6) * Q_CS + (k & 63) * 16, make_uint4(m0[4 * j], m0[4 * j + 1], m0[4 * j + 2], m0[4 * j + 3]));
    sts4(sb + Q_X + (k >> 6) * Q_CS + (k & 63) * 16 + 1024, make_uint4(m0[4 * j], m0[4 * j + 1], m0[4 * j + 2], m0[4 * j + 3]));
  }
#pragma unroll
  for (int i = 0; i < 2; i++) sts4(sb + Q_STG + (i * 16 + (tid >> 3)) * 768 + 640 + (tid & 7) * 16, make_uint4(0, 0, 0, 0));
  fence_async_smem();
  PROF_G(2);
  const uint32_t wa = pin(sb + Q_WO + ((tid >> 4 & 1) * 8 + (tid & 7)) * 128 + (((2 * w + ((tid >> 3) & 1)) ^ (tid & 7)) << 4));
  char* pd = nullptr;
  uint32_t pg = 0;
  auto find_pieces = [&]() {
    const int lane = tid & 31, dcta = (w * 8 + (lane >> 2)) * 3 + rank;
    uint4 f;
    uint32_t n = 0;
    do {
      f = ld_poll((const uint4*)(g_flags + FL_SEL) + dcta);
      if (++n > SPIN_LIMIT) __trap();
    } while (__any_sync(0xffffffffu, !f.x || !f.y || !f.z));
    pd = (char*)P.memx + part_of(dcta) + (head * 4 + (lane & 3) + (f.x - 1) * 256) * 16;
    pg = (8192 + (f.y - f.x) * 4096) | (8192 + (f.z - f.y) * 4096) << 16;
  };
  auto load_group0 = [&](int t) {
    mbar_wait(sb + B_XF, t & 1);
    if (t > 0) mbar_wait(sb + B_E + 16, (t - 1) & 1);
    fence_async_global();
    if (elect_one()) {
#pragma unroll
      for (int k = 0; k < 9; k++) bulk_g2s_mc(sb + Q_X + 2048 + k * Q_CS, (const char*)g_xs + (size_t)t * 73728 + k * 8192, 1024, sb + B_G0, 7);
    }
    __syncwarp();
  };
  uint32_t f[76];
  if (rank != 2) {
#pragma unroll
    for (int k = 0; k < 19; k++) ldsm4t(f[4 * k], f[4 * k + 1], f[4 * k + 2], f[4 * k + 3], wa + (k < 16 ? k : 2 * k - 16) * 2048);
    const uint32_t rs = pin(tid);
    cluster_sync();
    if (w == 3 && rank == 0) load_group0(0);
#pragma unroll 1
    for (int t = 1;; t++) {
      if (t > 1) check_tiles<4>(sb, P, w, t);
      if (w == 0) {
        bar_sync<8, 224>();
        fence_async_smem();
        if (elect_one()) {
          bulk_s2s(mapa(sb + Q_SIN + rank * 4096, rank ^ 1), sb + Q_SOUT + 2048, SX_BYTES, mapa(sb + B_SM, rank ^ 1));
          mbar_arrive(sb + B_SM);
        }
        __syncwarp();
      }
      if (t == NT) break;
      if (t == 1) find_pieces();
      pd = (char*)((uintptr_t)pd ^ 2048);
      if (w == 3 && rank == 0) load_group0(t);
      if (w == 2) { uint32_t ref = lds1(sb + Q_REF); read_reference(sb, P, ref, rank, t); }
      if (w == 1) {
        mbar_wait(sb + B_AN, (t - 1) & 1);
        spin_until(rd_clock() + (rank ? PA1_V : PA0_V));
        mbar_arrive_if0(rs - 32, sb + B_PZ);
      }
      mbar_spin(sb + B_O, (t - 1) & 1);
      PROF_W(w == 0, 13);
      wo_tiles<24>(sb, f, pd, pg, rs, t);
      mbar_expect_if0(rs, sb + B_O, 4096);
    }
  } else {
#pragma unroll
    for (int k = 0; k < 8; k++) ldsm4t(f[4 * k], f[4 * k + 1], f[4 * k + 2], f[4 * k + 3], wa + k * 2048);
    cluster_sync();
    find_pieces();
    const int l = w & 1, tile = w >> 1;
    const uint32_t ob = pin(sb + Q_OB + (l ^ ((head >> 1) & 1)) * 2048 + tile * 1024 + (tid >> 2 & 7) * 128 + (tid & 3) * 16);
    const uint32_t ob0 = sb + Q_OB + ((head >> 1) & 1) * 2048;
    const uint32_t sa = pin(sb + Q_SIN + l * 1024 + (tid & 31) * 16);
#pragma unroll 1
    for (int t = 1; t <= NT; t++) {
      const uint32_t par = (t - 1) & 1;
      {
        uint32_t vf[4][10], p[5];
        float s[10], o[4][4];
        const int lane = rd_lane();
        const uint32_t vb = sb + Q_STG + tile * 12288 + l * 6144 + (lane & 7) * 16;
        const uint32_t ax = vb + ((lane >> 3) & 1) * 768 + (lane >> 4) * 128;
        pd = (char*)((uintptr_t)pd ^ 2048);
        bar_sync<1, 384>();
#pragma unroll
        for (int i = 0; i < 4; i++) ldsm4(vf[i][4], vf[i][5], vf[i][6], vf[i][7], ax + i * 1536 + 256);
        ldsm4(vf[0][8], vf[0][9], vf[1][8], vf[1][9], vb + (lane >> 3) * 768 + 512);
        ldsm4(vf[2][8], vf[2][9], vf[3][8], vf[3][9], vb + (lane >> 3) * 768 + 512 + 3072);
#pragma unroll
        for (int i = 0; i < 4; i++) ldsm4(vf[i][0], vf[i][1], vf[i][2], vf[i][3], ax + i * 1536);
        mbar_spin(sb + B_SM, par);
        PROF_W(w == 0, 20);
        if (t < NT) {
          load_scores(s, sa);
          __syncwarp();
          softmax_num(s);
#pragma unroll
          for (int j = 0; j < 5; j++) p[j] = pack_bf16(s[2 * j], s[2 * j + 1]);
          __syncwarp();
          PROF_W(w == 0, 9);
          float z[4] = {0.f, 0.f, 0.f, 0.f};
          const uint32_t ONE = 0x3F803F80u;
          mma16816(z, ONE, ONE, ONE, ONE, p[0], p[1]);
#pragma unroll
          for (int i = 0; i < 4; i++) { o[i][0] = o[i][1] = o[i][2] = o[i][3] = 0.f; mma16816(o[i], vf[i][0], vf[i][1], vf[i][2], vf[i][3], p[0], p[1]); }
#pragma unroll
          for (int k = 8; k < (NFV_V < 12 ? NFV_V : 12); k++) ldsm4t(f[4 * k], f[4 * k + 1], f[4 * k + 2], f[4 * k + 3], wa + k * 2048);
          mma16816(z, ONE, ONE, ONE, ONE, p[2], p[3]);
#pragma unroll
          for (int i = 0; i < 4; i++) mma16816(o[i], vf[i][4], vf[i][5], vf[i][6], vf[i][7], p[2], p[3]);
#pragma unroll
          for (int k = 12; k < (NFV_V < 16 ? NFV_V : 16); k++) ldsm4t(f[4 * k], f[4 * k + 1], f[4 * k + 2], f[4 * k + 3], wa + k * 2048);
          mma1688(z, ONE, ONE, p[4]);
#pragma unroll
          for (int i = 0; i < 4; i++) mma1688(o[i], vf[i][8], vf[i][9], p[4]);
#pragma unroll
          for (int k = 16; k < 19 && 2 * k - 16 < NFV_V; k++) ldsm4t(f[4 * k], f[4 * k + 1], f[4 * k + 2], f[4 * k + 3], wa + (2 * k - 16) * 2048);
          const float r0 = rcp(z[0]), r1 = rcp(z[1]);
          const uint4 u0 = make_uint4(pack_bf16(o[0][0] * r0, o[0][2] * r0), pack_bf16(o[1][0] * r0, o[1][2] * r0),
                                      pack_bf16(o[2][0] * r0, o[2][2] * r0), pack_bf16(o[3][0] * r0, o[3][2] * r0));
          const uint4 u1 = make_uint4(pack_bf16(o[0][1] * r1, o[0][3] * r1), pack_bf16(o[1][1] * r1, o[1][3] * r1),
                                      pack_bf16(o[2][1] * r1, o[2][3] * r1), pack_bf16(o[3][1] * r1, o[3][3] * r1));
          PROF_W(w == 0, 8);
          sts4(ob, u0);
          sts4(ob + 64, u1);
          bar_sync<5, 160>();
          fence_async_smem();
          PROF_W(w == 0, 13);
          wo_tiles<NFV_V>(sb, f, pd, pg, ob ^ ob0, t);
        }
      }
      const int lane = rd_lane();
      mbar_expect_if0(lane | w, sb + B_SM, SM_BYTES);
      if (t < NT) bar_sync<12, 160>(); else fence_async_smem();
      {
        float o[3][16];
        const uint32_t ox = sb + Q_OX + 2 * w * 512 + lane * 16, pb = sb + B_P + 8 * (t & 1);
        const uint64_t dp = D_PX + (t & 1) * 384;
        mbar_wait(sb + B_OXFREE, par ^ 1);
        mbar_wait(pb, ((t - 1) >> 1) & 1);
        PROF_W(w == 0, 7);
#pragma unroll
        for (int j = 0; j < 7; j++) {
          if (j >= 3) {
            const int i = j - 3;
            if (i < 2) wg_wait<2>(); else if (i == 2) wg_wait<1>(); else wg_wait<0>();
            if (i == 3 && t < NT) bar_arrive<3, 384>();
            reg_fence(o[i % 3]);
#pragma unroll
            for (int h = 0; h < 2; h++) {
              stsm4(ox + i * 4096 + h * 512, pack_bf16(o[i % 3][2 * h], o[i % 3][2 * h + 1]), pack_bf16(o[i % 3][4 + 2 * h], o[i % 3][5 + 2 * h]),
                    pack_bf16(o[i % 3][8 + 2 * h], o[i % 3][9 + 2 * h]), pack_bf16(o[i % 3][12 + 2 * h], o[i % 3][13 + 2 * h]));
              if (SP_V && i) spin_until(rd_clock() + SP_V);
            }
          }
          if (j < 4) {
            if (j % 3 == 0) wg_fence();
            wg_sskk<0>(o[j % 3], D_V, (j >> 1) * 384 + (j & 1) * 768, dp, (j >> 1) * 192);
            wg_sskk<1>(o[j % 3], D_V, (j >> 1) * 384 + (j & 1) * 768 + 16, dp, (j >> 1) * 192 + 16);
            wg_sskk<1>(o[j % 3], D_V, (j >> 1) * 384 + (j & 1) * 768 + 32, dp, (j >> 1) * 192 + 32);
            wg_commit();
          }
        }
        mbar_expect_if0(lane | w, pb, PX_BYTES);
      }
      fence_async_smem();
      __syncwarp();
      mbar_arrive_if0(lane, sb + B_OXREADY);
      PROF_W(w == 0, 23);
    }
  }
  cluster_sync();
}

__device__ __forceinline__ void softmax_x(uint32_t sb, int w, int rank, int t) {
  float s[10];
  const int lane = rd_lane();
  mbar_wait(sb + B_SM, (t - 1) & 1);
  PROF_W(w == 3, 20);
  load_scores(s, sb + Q_SIN + w * 512 + lane * 16);
  const int last = 8 + 8 * w + (lane >> 2) - 2 * (lane & 3);
#pragma unroll
  for (int i = 2; i < 10; i++) s[i] = (8 * (i >> 1) + (i & 1) <= last) ? s[i] : -INFINITY;
  softmax_num(s);
  float sum = ((s[0] + s[1]) + (s[2] + s[3])) + ((s[4] + s[5]) + (s[6] + s[7])) + (s[8] + s[9]);
  sum = (sum + __shfl_xor_sync(0xffffffffu, sum, 1)) + (__shfl_xor_sync(0xffffffffu, sum, 2) + __shfl_xor_sync(0xffffffffu, sum, 3));
  const float r = rcp(sum);
  const uint32_t po = sb + Q_SOUT + 6144 + w * 768;
#pragma unroll
  for (int j = 0; j < 5; j++) sts1(po + lane * 4 + j * 128, pack_bf16(s[2 * j] * r, s[2 * j + 1] * r));
  fence_async_smem();
  __syncwarp();
  if (elect_one()) bulk_s2s(mapa(sb + Q_PX + ((t & 1) * 2 + rank) * 3072 + w * 768, 2), po, 128 * (w + 2), mapa(sb + B_P + 8 * (t & 1), 2));
  __syncwarp();
  PROF_W(w == 3, 22);
}

__device__ __forceinline__ void head_service(uint32_t sb, const Params& P) {
  const int lane = threadIdx.x & 31, rank = rd_rank(), w = rd_warp() & 3, i3 = w - 1;
  const int head = rd_cid(), c = tile_of(rank, i3);
  uint32_t dof = c * 8192 + (lane & 4) * 1024 + (lane & 8) * 128 + head * 32 + (lane & 16) + (lane & 3) * 4;
  uint32_t sof = part_of(blockIdx.x) + i3 * 8192, gof = 0, dly = tile_delay(rank, i3), g0 = 0, c0 = 0, ref = 0;
  asm volatile("barrier.cluster.arrive.aligned;" ::: "memory");
  if (w) {
#pragma unroll 1
    for (int j = 0; j < 16; j++) st_gpu4((uint4*)((char*)P.memx + sof) + j * 32 + lane, 1, 1, 1, 1);
    st_gpu1((uint32_t*)((char*)P.memx + dof), SENT);
    st_gpu1((uint32_t*)((char*)P.memx + dof + 2048), SENT);
    if (w == 2 && lane < 4) st_gpu4(P.memx + (blockIdx.x & 63) * 2 + (lane & 2) * 128 + (lane & 1), SENT, SENT, SENT, SENT);
    bar_sync<9, 224>();
    if (w < 3) probe_pages(sb, P, w == 1);
    bar_sync<12, 96>();
    if (w == 1) PROF_G(0);
    sof += __shfl_sync(0xffffffffu, lds1(sb + Q_SEL + 36 + 4 * i3), 0);
    asm volatile("st.release.gpu.global.u32 [%0], %1;" :: "l"(g_flags + FL_SEL + blockIdx.x * 4 + i3), "r"(((sof >> 12) & 1) + 1) : "memory");
    if (w == 1) PROF_G(1);
    gof = c * 8192 + __shfl_sync(0xffffffffu, lds1(sb + Q_SEL + 4 * c), 0);
  }
  asm volatile("barrier.cluster.wait.aligned;" ::: "memory");
#pragma unroll 1
  for (int t = 0; t <= NT; t++) {
    if (w == 0 && rank == 0 && t < NT) {
      const uint32_t* fl = g_flags + FL_XS + t * 32;
      warp_flag_wait(fl + (lane & 1 ? (t >= LAG ? 16 : 0) : (t <= NSEG ? 0 : 16)), 4);
      fence_async_global();
      const char* src = (const char*)g_xs + (size_t)t * 73728;
      if (t > 0) mbar_wait(sb + B_E, (t - 1) & 1);
      PROF_T(24);
      uint32_t at = rd_clock();
#pragma unroll 1
      for (int k = 0; k < 9; k++) {
        if (elect_one()) bulk_g2s_mc(sb + Q_X + 3072 + k * Q_CS, src + 1024 + k * 8192, 7168, sb + B_XF + 8 * k, 7);
        __syncwarp();
        at += t ? XP_V : 0;
        spin_until(at);
      }
      if (t == 0) PROF_G(31);
    }
    if (t > 0) {
    if (rank == 2 && w) { if (t > 1) check_tiles<3>(sb, P, w - 1, t); else mbar_arrive_if0(lane, sb + B_E + 24); }
    if (w == 1 && rank == 2 && t < NT) {
      const uint32_t due = ref + D_GX + D_DUE * 9 / 16;
      const uint32_t g1 = next_tick(), c1 = rd_clock();
      const uint32_t rate = t > 1 ? __float2uint_rn(65536.f * (g1 - g0) * rcp(c1 - c0)) : 36400;
      g0 = g1; c0 = c1;
      uint4* pub = P.memx + 9 * 512 + (lane & 1) * 256 + (lane & 2) * 16 + head;
      const uint32_t lead = D_RED * rate >> 16, late = D_LATE * rate >> 16, r1 = rank_delay(1) * rate >> 10, r0 = rank_delay(0) * rate >> 10;
      mbar_wait(sb + B_E, (t - 1) & 1);
      PROF_T(4);
      mbar_spin(sb + B_E + 24, (t - 1) & 1);
      uint32_t now = g0 + ((rd_clock() - c0) * rate >> 16);
      now = (now + (t < 3 ? lead + ST0_V : (int)(now + 90 - due) > 0 ? late : lead)) << 6;
      st_gpu4(pub, ((now + r0) & ~255u) | t, ((now + r1) & ~255u) | t, (now & ~255u) | t, 0);
      PROF_T(22);
      PROF_V(true, 1, now >> 6);
      read_reference(sb, P, ref, 2, t);
    }
    if (w == 2 && rank == 2 && t < NT) {
      mbar_wait(sb + B_SM, (t - 1) & 1);
      mbar_rarrive_if0(lane >> 1, mapa(sb + B_AN, lane & 1));
      bar_sync<5, 160>();
      fence_async_smem();
      if (elect_one()) {
        bulk_s2s(mapa(sb + Q_OB, 1), sb + Q_OB, 4096, mapa(sb + B_O, 1));
        bulk_s2s(mapa(sb + Q_OB, 0), sb + Q_OB, 4096, mapa(sb + B_O, 0));
      }
      __syncwarp();
    }
    if (rank != 2) {
      softmax_x(sb, w, rank, t);
      if (w == 0 && t < NT) bar_arrive<7, 64>();
      mbar_expect_if0(lane | (w - 1), sb + B_SM, SX_BYTES);
    }
    }
    if (t == 0) continue;
    if (w == 3) PROF_MID();
    if (w && t < NT) {
      mbar_wait(sb + B_REF, (t - 1) & 1);
      uint32_t when = lds1(sb + Q_REF) + dly;
      sof ^= 2048; dof ^= 2048;
      uint4* src = (uint4*)((char*)P.memx + sof) + lane;
      uint32_t* dst = (uint32_t*)((char*)P.memx + (dof ^ 2048));
      const bool inj = t == LAG && (lane & 8);
      if (t == LAG) {
        const __nv_bfloat16* m0 = P.mem0 + (lane & 3) * 2 * DM + c * 64 + head * 2 + (lane >> 4);
        st_gpu1_if(inj, dst, bf2_add(__bfloat16_as_ushort(m0[0]) | (uint32_t)__bfloat16_as_ushort(m0[DM]) << 16, 0));
      }
      asm volatile("" : "+l"(dst), "+l"(src));
      uint4 v[4];
      wait_ns(when);
      PROF_W(i3 == 0, 18);
      const uint32_t nr = poll4<true>(v, src, (t - 1) >> 1);
      if (GT_V < 3 && w == GT_V + 1 && rank == 2) bar_arrive<12, 160>();
      PROF_T(26 + i3);
      const uint32_t z = bf2_add(bf2_add(v[0].z, v[1].z), bf2_add(v[2].z, v[3].z)), u = bf2_add(bf2_add(v[0].w, v[1].w), bf2_add(v[2].w, v[3].w));
      const uint32_t x = bf2_add(bf2_add(v[0].x, v[1].x), bf2_add(v[2].x, v[3].x)), y = bf2_add(bf2_add(v[0].y, v[1].y), bf2_add(v[2].y, v[3].y));
      const uint32_t x2 = bf2_add(bf2_add(x, 0), __shfl_xor_sync(0xffffffffu, z, 16)), y2 = bf2_add(y, __shfl_xor_sync(0xffffffffu, u, 16));
      const uint32_t x3 = bf2_add(x2, __shfl_xor_sync(0xffffffffu, y2, 8));
      st_gpu1_if(!inj, dst, bf2_add(x3, __shfl_xor_sync(0xffffffffu, x3, 4)));
      if (GT_V >= 3 && w == GT_V - 2 && rank == 2) bar_arrive<12, 160>();
      PROF_T(29 + i3);
      PROF_A(10 + i3, nr);
      when += D_GX + min(lds1(sb + Q_REF + 4), 8u) * D_ADAPT;
      if (nr && t > LAG + 3 && dly < tile_delay(rank, i3) + 8 * D_ADAPT) dly += D_ADAPT;
      fence_async_global();
      if (w == 3 && rank != 2) bar_sync<7, 64>();
      wait_ns(when);
      if (elect_one()) bulk_g2s_mc(sb + Q_X + c * Q_CS, (const char*)P.memx + gof + (~t & 1) * 2048, 2048, sb + B_CP + 8 * c, 7);
      __syncwarp();
      if (i3 == 0) PROF_T(21);
      st_gpu1((uint32_t*)((char*)P.memx + dof), SENT);
    }
    if (w == 0 && rank == 2) {
      if (t < NT) mbar_wait(sb + B_XF, t & 1); else warp_flag_wait(g_flags + FL_XS + NT * 32 + 16, 4);
      mbar_wait(sb + B_OXREADY, (t - 1) & 1);
      if (elect_one()) {
        uint4* od = g_ox + (size_t)(t & (OXRING - 1)) * 32768 + head * 512;
        if (t <= NSEG) bulk_s2g(od, sb + Q_OX, 8192);
        if (t > LAG) bulk_s2g(od + 16384, sb + Q_OX + 8192, 8192);
        bulk_commit_wait();
        mbar_arrive(sb + B_OXFREE);
        flag_add(g_flags + FL_OX + t * 32 + head);
      }
      __syncwarp();
      PROF_T(25);
    }
  }
  cluster_sync();
}

__global__ void __cluster_dims__(3, 1, 1) __launch_bounds__(512, 1) head_kernel(const __grid_constant__ Params P) {
  extern __shared__ uint8_t smem_raw[];
  const uint32_t sb = (uint32_t)__cvta_generic_to_shared(smem_raw);
  if ((sb & 0xFFFFFFu) != SB0) __trap();
  asm volatile("griddepcontrol.launch_dependents;");
  if (threadIdx.x < 96) {
    const int i = blockIdx.x * 24 + threadIdx.x % 24, m = threadIdx.x / 24;
    const __nv_bfloat16* p = m == 3 ? P.ssm_k + (size_t)(i >> 2) * SEQ + (i & 3) * 64 : (m == 0 ? P.ck : m == 1 ? P.cv : P.x0) + (size_t)i * 64;
    asm volatile("prefetch.global.L2 [%0];" :: "l"(p));
  } else if (threadIdx.x == 96 && blockIdx.x < 45) {
    asm volatile("prefetch.global.L2 [%0];" :: "l"(blockIdx.x < 36 ? P.shift + blockIdx.x * 64 : P.ssm_d + (blockIdx.x - 36) * 64));
  } else if (threadIdx.x == 97 && blockIdx.x < 72) {
    asm volatile("prefetch.global.L2 [%0];" :: "l"(P.mem0 + blockIdx.x * 64));
  }
  PROF_BEGIN();
  if (threadIdx.x == 416) sts1(sb + Q_SET, (__ldcg(&g_epoch) & 1) * FL_TOTAL);
  const int rank = rd_rank(), wg = rd_warp() >> 2;
  if (threadIdx.x == 448) {
    for (int c = 0; c < 9; c++) { mbar_init(sb + B_CP + 8 * c, 1); mbar_arrive(sb + B_CP + 8 * c); mbar_init(sb + B_OK + 8 * c, 1); mbar_arrive(sb + B_OK + 8 * c); mbar_init(sb + B_XF + 8 * c, 1); mbar_expect(sb + B_XF + 8 * c, 7168); }
    mbar_init(sb + B_E, 6); mbar_init(sb + B_G0, 1); mbar_expect(sb + B_G0, 9216); mbar_init(sb + B_E + 16, 6); mbar_init(sb + B_E + 24, 7);
    mbar_init(sb + B_SM, rank == 2 ? 1 : 2); mbar_init(sb + B_O, 1); mbar_init(sb + B_P, 1); mbar_init(sb + B_P + 8, 1);
    mbar_init(sb + B_REF, 1); mbar_init(sb + B_RES, 1); mbar_init(sb + B_PZ, 1); mbar_init(sb + B_AN, 1); mbar_init(sb + B_OXREADY, 4); mbar_init(sb + B_OXFREE, 1);
    mbar_expect(sb + B_SM, rank == 2 ? SM_BYTES : SX_BYTES); mbar_expect(sb + B_P, PX_BYTES); mbar_expect(sb + B_P + 8, PX_BYTES);
    mbar_expect(sb + B_O, 4096);
    sts1(sb + Q_REF + 4, 0); sts1(sb + Q_SEL + 48, 0);
    asm volatile("fence.mbarrier_init.release.cluster;" ::: "memory");
  }
  __syncthreads();
  PROF_G(6);
  if (wg < 2) {
    asm volatile("setmaxnreg.inc.sync.aligned.u32 176;");
    head_main(sb, P);
    PROF_END();
  } else if (wg == 2) {
    asm volatile("setmaxnreg.dec.sync.aligned.u32 120;");
    head_aux(sb, P);
    PROF_END();
  } else {
    asm volatile("setmaxnreg.dec.sync.aligned.u32 40;");
    head_service(sb, P);
    PROF_END();
  }
}

__device__ __forceinline__ void tail_gemm(uint32_t sb, const Params& P) {
  const int lane = threadIdx.x & 31, warp = rd_warp(), w = warp & 3, wg = warp >> 2, tid = threadIdx.x & 127;
  uint32_t a[4 * W_KR];
  fence_async_smem();
  if (elect_one()) {
#pragma unroll 1
    for (int k = w; k < 32; k += 4)
      tma_box(k < W_KR ? sb + wg * 65536 + k * 2048 : sb + W_WS + wg * 6144 + (k - W_KR) * 2048, &P.tm, (blockIdx.x % 3) * 192 + wg * 64, (blockIdx.x / 3) * 512 + k * 16, sb + B_WT + 8 * wg);
  }
  __syncwarp();
  mbar_wait(sb + B_WT + 8 * wg, 0);
  load_afrags<W_KR>(a, sb + wg * 65536, w, lane);
  fence_async_smem();
  bar_sync<1, 416>();
  PROF_G(26);
  if (wg == 2) bar_arrive<2, 256>();
  const uint64_t dw = P.d_ws + wg * 384;
  float4* dst0 = g_acc + ((blockIdx.x % 3) * 12 + warp) * 32 + lane;
#pragma unroll 1
  for (int t = 1; t <= NT; t++) {
#pragma unroll 1
    for (int l = t > NSEG; l <= (t > LAG); l++) {
      const int seg = t - 1 - l * LAG, grp = (seg & 1) * 2 + l;
      const uint64_t db = P.d_ring + grp * 2048;
      float acc[16];
      bar_sync_r(2 + wg, 256);
#pragma unroll
      for (int c = 0; c < 4; c++) {
        if (wg == 0) mbar_wait(sb + B_FULL + 32 * grp + 8 * c, (seg >> 1) & 1);
        if (c == 0) PROF_T(6 * l + wg);
        wg_fence();
#pragma unroll
        for (int i = 0; i < 8; i++) {
          if (c == 0 && i == 0) wg_rs<0, 1>(acc, a, db, 0);
          else if (8 * c + i < W_KR) wg_rs<1, 1>(acc, a + 32 * c + 4 * i, db, 512 * c + 64 * i);
          else wg_ss<1, 1>(acc, dw, 128 * (8 * c + i - W_KR), db, 512 * c + 64 * i);
        }
      }
      wg_commit();
      bar_arrive_r(wg == 2 ? 2 : 3 + wg, 256);
      wg_wait<0>();
      reg_fence(acc);
      mbar_arrive_if0(tid, sb + B_EMPTY + 8 * grp);
      float4* dst = dst0 + (size_t)(l * 256 + seg * 4) * 1152;
#pragma unroll
      for (int j = 0; j < 4; j++)
        asm volatile("red.relaxed.gpu.global.add.v4.f32 [%0], {%1,%2,%3,%4};" :: "l"(dst + j * 1152),
                     "f"(acc[4 * j]), "f"(acc[4 * j + 1]), "f"(acc[4 * j + 2]), "f"(acc[4 * j + 3]) : "memory");
      bar_sync_r(5 + wg, 160);
    }
  }
}
__device__ __forceinline__ void tail_service(uint32_t sb) {
  const int lane = threadIdx.x & 31, warp = rd_warp();
  if (warp == 12) bar_sync<1, 416>();
#pragma unroll 1
  for (int t = 1; t <= NT; t++) {
    if (warp == 12) {
      const int h0 = (blockIdx.x / 3) * 4;
      warp_flag_wait(g_flags + FL_OX + t * 32 + h0 + (lane & 3), 1);
      fence_async_global();
#pragma unroll 1
      for (int l = t > NSEG; l <= (t > LAG); l++) {
        const int seg = t - 1 - l * LAG, grp = (seg & 1) * 2 + l;
        const uint4* src = g_ox + (size_t)(t % OXRING) * 32768 + l * 16384 + h0 * 512;
        const uint32_t bar = sb + B_FULL + 32 * grp;
        mbar_wait_lim(sb + B_EMPTY + 8 * grp, ((seg >> 1) & 1) ^ 1);
        mbar_expect_if0(lane > 3, bar + 8 * lane, 8192);
        if (elect_one()) {
#pragma unroll
          for (int j = 0; j < 4; j++) bulk_g2s(sb + W_RING + (grp * 4 + j) * 8192, src + j * 512, 8192, bar + 8 * j);
        }
        __syncwarp();
      }
      PROF_T(12);
      PROF_MID();
    } else {
#pragma unroll 1
      for (int l = t > NSEG; l <= (t > LAG); l++) {
        bar_sync_r(warp - 8, 160);
        if (lane == 0) flag_add(g_flags + FL_ACC + (l * 64 + t - 1 - l * LAG) * 32);
        __syncwarp();
        PROF_T(6 * l + warp - 10);
      }
    }
  }
}

__device__ __forceinline__ void wait_k1(uint32_t sb, int n) {
  uint32_t c = 0;
  while ((int)lds1(sb + W_K1) < n) {
    __nanosleep(64);
    if (++c > SPIN_LIMIT) __trap();
  }
}
__device__ __forceinline__ void tail_finisher(uint32_t sb, const Params& P) {
  const int lane = threadIdx.x & 31, warp = rd_warp(), kind = warp < 12 ? warp / 6 : warp & 1, f = warp - 6 * kind, tg = blockIdx.x & 3;
  if (warp >= 14) {
    const uint32_t set = lds1(sb + Q_SET), ft = sb + W_FO + kind * 576;
    if (tg == 0) for (int i = kind * 32 + lane; i < FL_TOTAL; i += 64) g_flagsets[FL_TOTAL - set + i] = 0;
#pragma unroll 1
    for (int t = 0; t < NSEG; t++) {
      warp_flag_wait(g_flags + FL_ACC + (64 + t) * 32, 72);
      PROF_T(17);
      if (t == 0 && tg == 0 && threadIdx.x == 448) g_epoch = set ? 0 : 1;
      const float4* ac = g_acc + ((size_t)(256 + t * 4 + tg) * 36 + kind * 18) * 32 + lane;
      float4 v[18];
#pragma unroll
      for (int i = 0; i < 18; i++) v[i] = __ldcg(ac + i * 32);
#pragma unroll
      for (int i = 0; i < 9; i++) {
        const uint4 r = lds4(sb + W_RS + (8 + (t & 7)) * 9216 + (kind * 9 + i) * 512 + lane * 16);
        stsm4t(ft + (lane & 7) * 1168 + (lane >> 3) * 16 + 64 * i, bf2_add(r.x, pack_bf16(v[2 * i].x, v[2 * i].y)), bf2_add(r.y, pack_bf16(v[2 * i].z, v[2 * i].w)),
               bf2_add(r.z, pack_bf16(v[2 * i + 1].x, v[2 * i + 1].y)), bf2_add(r.w, pack_bf16(v[2 * i + 1].z, v[2 * i + 1].w)));
      }
      fence_async_smem();
      __syncwarp();
      mbar_arrive_if0(lane, sb + B_RF + 8 * (t & 7));
      wait_k1(sb, min(t + LAG + 1, NSEG));
      if (lane < 8) {
        bulk_s2g(P.out + (size_t)((t * 4 + tg) * 8 + lane) * DM + kind * 288, ft + lane * 1168, 576);
        bulk_commit_wait();
      }
      __syncwarp();
      PROF_T(18);
    }
    return;
  }
  if (warp >= 12) {
    for (int i = kind * 32 + lane; i < 1152; i += 64) sts4(sb + W_Z + i * 16, make_uint4(0, 0, 0, 0));
    fence_async_smem();
    bar_sync<12, 64>();
#pragma unroll 1
    for (int t = -1; t <= NSEG; t++) {
      if (kind == 0 && t + 1 < NSEG) {
        const uint32_t bar = sb + B_FT + 8 * ((t + 1) & 1);
        mbar_expect_if0(lane, bar, 9216);
        __syncwarp();
        if (lane < 8) bulk_g2s(sb + W_FT + ((t + 1) & 1) * 9344 + lane * 1168, P.x0 + (size_t)(((t + 1) * 4 + tg) * 8 + lane) * DM, 1152, bar);
      }
      if (t < 0) continue;
      if (t < NSEG) bar_sync_r(9 + 2 * kind, 224);
      if (lane == 0) {
        flag_add(g_flags + FL_XS + (t + kind * LAG) * 32 + kind * 16);
        if (kind) { sts1(sb + W_K1, t + 1); PROF_T(14); }
        if (kind ? t < NSEG : t < LAG) bulk_s2g(g_acc + (size_t)(kind * 256 + t * 4 + tg) * 1152, sb + W_Z, 18432);
        if (kind && t + LAG < NSEG) bulk_s2g(g_acc + (size_t)((t + LAG) * 4 + tg) * 1152, sb + W_Z, 18432);
        bulk_commit_wait();
      }
      __syncwarp();
      if (kind) PROF_MID();
    }
    return;
  }
  const uint32_t BF_1 = 0x3F803F80u;
  const uint32_t* ys = (const uint32_t*)(g_y + ((tg >> 1) * DM + f * 96 + (lane >> 2)) * 2 + (tg & 1)) + (lane & 3);
  const uint32_t rs = sb + W_RS + f * 1536 + lane * 16;
  uint32_t y[12] = {};
#pragma unroll 1
  for (int t = 0; t < NSEG; t++) {
    uint32_t x[12];
    if (kind == 0) {
      wait_k1(sb, t - 6);
      mbar_wait(sb + B_FT + 8 * (t & 1), (t >> 1) & 1);
#pragma unroll
      for (int i = 0; i < 3; i++)
        ldsm4t(x[4 * i], x[4 * i + 1], x[4 * i + 2], x[4 * i + 3], sb + W_FT + (t & 1) * 9344 + (lane & 7) * 1168 + f * 192 + (lane >> 3) * 16 + 64 * i);
    } else {
      warp_flag_wait(g_flags + FL_ACC + t * 32, 72);
      PROF_T(13);
#pragma unroll
      for (int i = 0; i < 6; i++) {
        const float4 v = __ldcg(g_acc + ((size_t)(t * 4 + tg) * 36 + f * 6 + i) * 32 + lane);
        x[2 * i] = pack_bf16(v.x, v.y); x[2 * i + 1] = pack_bf16(v.z, v.w);
      }
#pragma unroll
      for (int i = 0; i < 3; i++) {
        const uint4 r = lds4(rs + (t & 7) * 9216 + i * 512);
        x[4 * i] = bf2_add(x[4 * i], r.x); x[4 * i + 1] = bf2_add(x[4 * i + 1], r.y); x[4 * i + 2] = bf2_add(x[4 * i + 2], r.z); x[4 * i + 3] = bf2_add(x[4 * i + 3], r.w);
      }
      mbar_wait(sb + B_RF + 8 * (t & 7), ((t >> 3) & 1) ^ 1);
      PROF_T(15);
    }
    {
      if (t == 0) PROF_G(27);
#pragma unroll 1
      for (int pass = 0; pass < 2; pass++) {
        float g[2][4] = {};
#pragma unroll
        for (int i = 0; i < 12; i++) {
          uint32_t u;
          asm volatile("movmatrix.sync.aligned.m8n8.trans.b16 %0, %1;" : "=r"(u) : "r"(x[i]));
          mma1688(g[i & 1], u, BF_1, u);
        }
        const uint32_t st = sb + W_ST + kind * 1024 + pass * 512 + (lane & 3) * 16;
        if ((lane >> 3) == (lane & 3))
          asm volatile("st.shared.v2.f32 [%0], {%1,%2};" :: "r"(st + f * 64 + (lane & 4) * 2), "f"(lane & 4 ? g[0][3] + g[1][3] : g[0][2] + g[1][2]),
                       "f"(lane & 4 ? g[0][1] + g[1][1] : g[0][0] + g[1][0]) : "memory");
        bar_sync_r(8 + 2 * kind, 192);
        float s0 = 0.f, s1 = 0.f, q0 = 0.f, q1 = 0.f;
        if (kind && pass == 0) PROF_T(19);
        if (kind && pass == 1) PROF_T(21);
#pragma unroll
        for (int i = 0; i < 6; i++) {
          const float4 e = lds4f(st + i * 64);
          s0 += e.x; q0 += e.y; s1 += e.z; q1 += e.w;
        }
        s0 *= 1.f / 576.f; s1 *= 1.f / 576.f;
        const float v0 = fmaf(q0, 1.f / 576.f, -s0 * s0), v1 = fmaf(q1, 1.f / 576.f, -s1 * s1);
        const uint32_t nmean = pack_bf16(-s0, -s1), vb = pack_bf16(fmaxf(v0, 0.f), fmaxf(v1, 0.f));
        const uint32_t ve = pack_bf16(bf_lo(vb) + 1e-5f, bf_hi(vb) + 1e-5f), sd = pack_bf16(sqr(bf_lo(ve)), sqr(bf_hi(ve)));
        const float r0 = rcp(bf_lo(sd)), r1 = rcp(bf_hi(sd));
        const uint32_t rh = pack_bf16(r0, r1), rl = pack_bf16(r0 - bf_lo(rh), r1 - bf_hi(rh));
        if (pass == 0 && (t == 0 || t == 4 * CT_A || t == 4 * CT_B || t == 4 * CT_C)) {
          if (t == 0) PROF_G(25);
          warp_flag_wait(g_flags + FL_Y + t * 8, t < 4 * CT_B ? 32 : DM);
          if (t == 0) PROF_G(26);
#pragma unroll
          for (int i = 0; i < 12; i++) y[i] = __ldcg(ys + t * (DM * 16) + i * 64);
        }
        uint32_t* xd = (uint32_t*)(g_xs + (size_t)(t + kind * LAG) * 4608 + (kind * 4 + tg) * 64 + (f * 3 >> 1) * 512 + (f & 1) * 32) + lane;
#pragma unroll
        for (int i = 0; i < 12; i++) {
          const uint32_t d = bf2_add(x[i], nmean), q = bf2_op(d, rh, bf2_mul(d, rl));
          if (pass == 0) x[i] = bf2_add(x[i], bf2_mul(q, y[i]));
          else xd[i < 4 ? i * 32 : i < 8 ? i * 32 + (f & 1) * 1792 : i * 32 + 1792] = q;
        }
        if (pass == 0) {
#pragma unroll
          for (int i = 0; i < 3; i++) sts4(rs + (kind * 8 + (t & 7)) * 9216 + i * 512, make_uint4(x[4 * i], x[4 * i + 1], x[4 * i + 2], x[4 * i + 3]));
        }
        if (kind && pass == 0) PROF_T(20);
        if (kind && pass == 1) PROF_T(22);
      }
      if (kind) PROF_T(16);
      if (t < 3) PROF_G(28 + t);
      bar_sync_r(9 + 2 * kind, 224);
#pragma unroll
      for (int i = 0; i < 12; i++) y[i] = __ldcg(ys + ((t + 1) & 63) * (DM * 16) + i * 64);
    }
  }
}

template <int NP, typename V>
__device__ __forceinline__ void kv_block(uint4 (&o)[2 * NP], const Params& P, int r0, int c0) {
  V kk[11], vv[8];
  uint4 sw[NP];
#pragma unroll
  for (int i = 0; i < NP; i++) sw[i] = __ldg((const uint4*)(P.shift + (c0 + 2 * i) * 4));
#pragma unroll
  for (int i = 0; i < 11; i++) kk[i] = r0 + i >= 3 ? __ldg((const V*)(P.ck + (size_t)(r0 + i - 3) * DM + c0)) : V{};
#pragma unroll
  for (int i = 0; i < 8; i++) vv[i] = __ldg((const V*)(P.cv + (size_t)(r0 + i) * DM + c0));
#pragma unroll
  for (int cp = 0; cp < NP; cp++) {
    const uint32_t wt[4] = {__byte_perm(sw[cp].y, sw[cp].w, 0x7632), __byte_perm(sw[cp].y, sw[cp].w, 0x5410),
                            __byte_perm(sw[cp].x, sw[cp].z, 0x7632), __byte_perm(sw[cp].x, sw[cp].z, 0x5410)};
    uint32_t e[8];
#pragma unroll
    for (int i = 0; i < 8; i++) {
      uint32_t a = bf2_mul(((const uint32_t*)&kk[i])[cp], wt[0]);
#pragma unroll
      for (int j = 1; j < 4; j++) a = bf2_add(a, bf2_mul(((const uint32_t*)&kk[i + j])[cp], wt[j]));
      e[i] = bf2_mul(a, ((const uint32_t*)&vv[i])[cp]);
    }
    o[2 * cp] = make_uint4(__byte_perm(e[0], e[1], 0x5410), __byte_perm(e[2], e[3], 0x5410), __byte_perm(e[4], e[5], 0x5410), __byte_perm(e[6], e[7], 0x5410));
    o[2 * cp + 1] = make_uint4(__byte_perm(e[0], e[1], 0x7632), __byte_perm(e[2], e[3], 0x7632), __byte_perm(e[4], e[5], 0x7632), __byte_perm(e[6], e[7], 0x7632));
  }
}
__device__ __forceinline__ void kv_task(const Params& P, int id) {
  const int lane = threadIdx.x & 31, tq = id / 9, c0 = (id % 9) * 64 + (lane >> 2) * 8;
  uint4 o[8];
  kv_block<4, uint4>(o, P, tq * 32 + (lane & 3) * 8, c0);
#pragma unroll
  for (int c = 0; c < 8; c++) g_kv[((size_t)tq * DM + c0 + c) * 4 + (lane & 3)] = o[c];
}
__device__ __forceinline__ int next_job(uint32_t sb) {
  int j = 0;
  if ((threadIdx.x & 31) == 0) j = atomicAdd(g_flags + FL_KV + 96, 1);
  return __shfl_sync(0xffffffffu, j, 0);
}
__device__ __forceinline__ uint2 lds2_ro(uint32_t a) { uint2 v; asm("ld.shared.v2.u32 {%0,%1}, [%2];" : "=r"(v.x), "=r"(v.y) : "r"(a)); return v; }

template <int T0, int T1>
__device__ __forceinline__ void conv_job(uint32_t sb, const Params& P, int ch, int sets = 1) {
  const int lane = threadIdx.x & 31, w = threadIdx.x >> 5;
  uint32_t ub = sb + w * C_CH, zb = ub + C_U;
  constexpr int NL = (T1 + 1) / 2, NS = T0 == 0 ? 2 : 1;
  constexpr bool CTA = T1 <= CT_B;
  static_assert(T0 > 0 || T1 == 2, "second set: buffer offsets, warps");
  PROF_G(13 + 4 * (T0 == 0 ? 0 : T0 == CT_A ? 1 : 2));
  uint2 q[NS][T1];
  uint32_t dd[NS];
#pragma unroll
  for (int n = 0; n < NS; n++) {
    const int c = n < sets ? ch - n * 128 : ch;
#pragma unroll
    for (int u = 0; u < T1; u++) q[n][u] = __ldg((const uint2*)(P.ssm_k + (size_t)c * SEQ) + u * 32 + lane);
    dd[n] = (uint32_t)__bfloat16_as_ushort(P.ssm_d[c]) * 0x10001u;
  }
  if (CTA) {
#pragma unroll
    for (int tq = w; tq < 4 * T1 * sets; tq += 16) {
      uint4 o[2];
      const int n = T0 == 0 ? tq >> 3 : 0, tgp = (tq - 8 * n) * 4 + (lane & 3), c0 = (lane >> 2) * 2;
      kv_block<1, uint32_t>(o, P, tgp * 8, ch - w + c0 - n * 128);
#pragma unroll
      for (int c = 0; c < 2; c++) {
        sts4(sb + (c0 + c) * C_CH + n * 2048 + 256 + tgp * 16, o[c]);
        if (T0) g_kv[((size_t)tq * DM + ch - w + c0 + c) * 4 + (lane & 3)] = o[c];
      }
    }
    __syncwarp();
  } else {
    uint4 o[NL];
#pragma unroll
    for (int u = 0; u < NL; u++) o[u] = __ldcg(g_kv + ((size_t)(u * 8 + (lane >> 2)) * DM + ch) * 4 + (lane & 3));
#pragma unroll
    for (int u = 0; u < NL; u++) sts4(ub + 256 + (u * 32 + lane) * 16, o[u]);
  }
#pragma unroll
  for (int n = 0; n < NS; n++) {
    if (lane < 16) { sts4(ub + n * 2048 + lane * 16, make_uint4(0, 0, 0, 0)); sts1(zb + n * 4096 + lane * 4, 0); }
#pragma unroll
    for (int u = 0; u < T1; u++) {
      const uint2 k = q[n][u];
      const uint32_t pv = __shfl_sync(0xffffffffu, lane == 31 ? (u ? q[n][u ? u - 1 : 0].y : 0u) : k.y, (lane + 31) & 31);
      sts4(zb + n * 4096 + 64 + (u * 32 + lane) * 16, make_uint4(__byte_perm(k.x, pv, 0x7610), __byte_perm(k.x, k.x, 0x1032),
                                                                __byte_perm(k.y, k.x, 0x7610), __byte_perm(k.y, k.y, 0x1032)));
    }
  }
  if (CTA) __syncthreads(); else __syncwarp();
  PROF_G(14 + 4 * (T0 == 0 ? 0 : T0 == CT_A ? 1 : 2));
#pragma unroll 1
  for (int n = 0; n < sets; n++, ub += 2048, zb += 4096) {
    float acc[T1 - T0][4];
#pragma unroll
    for (int i = 0; i < T1 - T0; i++) acc[i][0] = acc[i][1] = acc[i][2] = acc[i][3] = 0.f;
#pragma unroll(T0 == 0 ? 4 : 1)
    for (int r = 0; r < 8; r++) {
      uint2 b[T1];
      uint32_t ba = ub + 256 - r * 32 + lane * 8, zp = zb + 64 + (16 * r + 2 * (lane >> 2) - 4 * (lane & 3)) * 4;
      asm volatile("" : "+r"(zp), "+r"(ba) :: "memory");
#pragma unroll
      for (int i = 0; i < T1; i++) b[i] = lds2_ro(ba + i * 256);
#pragma unroll
      for (int mu = 0; mu < T1; mu++) {
        const uint2 a01 = lds2_ro(zp + 512 * mu), a23 = lds2_ro(zp + 512 * mu - 8);
#pragma unroll
        for (int i = (mu > T0 ? mu : T0); i < T1; i++) mma16816(acc[i - T0], a01.x, a01.y, a23.x, a23.y, b[i - mu].x, b[i - mu].y);
      }
    }
    PROF_G(15 + 4 * (T0 == 0 ? 0 : T0 == CT_A ? 1 : 2));
#pragma unroll
    for (int i = 0; i < T1 - T0; i++)
#pragma unroll
      for (int e = 0; e < 2; e++) {
        const int col = (T0 + i) * 8 + 2 * (lane & 3) + e;
        ((uint32_t*)g_y)[((size_t)col * DM + ch - n * 128) * 8 + (lane >> 2)] =
            bf2_add(pack_bf16(acc[i][e], acc[i][2 + e]), bf2_mul(lds1(ub + 256 + col * 32 + (lane >> 2) * 4), n ? dd[NS - 1] : dd[0]));
      }
  }
  if (CTA) __syncthreads(); else __syncwarp();
  PROF_G(16 + 4 * (T0 == 0 ? 0 : T0 == CT_A ? 1 : 2));
  if (CTA ? threadIdx.x == 480 && (T0 == 0 || ch < 512) : lane == 0) flag_add(g_flags + FL_Y + T0 * 32);
  __syncwarp();
}

__global__ void __launch_bounds__(512, 1) tail_kernel(const __grid_constant__ Params P) {
  extern __shared__ uint8_t smem_raw[];
  const uint32_t sb = (uint32_t)__cvta_generic_to_shared(smem_raw);
  if (sb != SB0) __trap();
  PROF_BEGIN();
  if (threadIdx.x == 0) {
    for (int c = 0; c < 16; c++) mbar_init(sb + B_FULL + 8 * c, 1);
    for (int c = 0; c < 4; c++) mbar_init(sb + B_EMPTY + 8 * c, 3);
    for (int c = 0; c < 2; c++) mbar_init(sb + B_FT + 8 * c, 1);
    for (int c = 0; c < 8; c++) mbar_init(sb + B_RF + 8 * c, 2);
    for (int c = 0; c < 3; c++) { mbar_init(sb + B_WT + 8 * c, 1); mbar_expect(sb + B_WT + 8 * c, 65536); }
    sts1(sb + W_K1, 0);
    sts1(sb + Q_SET, (__ldcg(&g_epoch) & 1) * FL_TOTAL);
    fence_async_smem();
  }
  const int b = blockIdx.x, w = threadIdx.x >> 5;
  if ((b >> 2) == 6) {
    __syncthreads();
  } else {
    conv_job<0, CT_A>(sb, P, b * 16 + w, b < 32 ? 1 : 2);
    PROF_G(3);
#pragma unroll 1
    for (int g = b; g == b || (g >> 2) == 6; g -= 8) conv_job<CT_A, CT_B>(sb, P, g * 16 + w);
    PROF_G(4);
    if (b >= 28) {
      constexpr int KV0 = 36 * CT_B, KV1 = KV0 + 192, NK = 576 - KV1;
      const int lane = threadIdx.x & 31;
      auto draw = [&]() {
        const int j = next_job(sb), ch = j < DM ? j : j - DM - NK;
        if (ch >= 0 && ch < DM && lane < (j < DM ? 2 * CT_C : 32)) asm volatile("prefetch.global.L2 [%0];" :: "l"(P.ssm_k + (size_t)ch * SEQ + lane * 64));
        return j;
      };
      int job = draw();
#pragma unroll 1
      for (int k = KV0 + (b - 28) * 16 + w; b < 32 && k < KV1; k += 64) {
        kv_task(P, k);
        __syncwarp();
        if (lane == 0) flag_add(g_flags + FL_KV);
      }
      warp_flag_wait(g_flags + FL_Y + CT_A * 32, 32);
      warp_flag_wait(g_flags + FL_KV, 192);
      spin_until(rd_clock() + (w >> 2) * DP_V);
#pragma unroll 1
      while (job < DM) { const int nx = draw(); conv_job<CT_B, CT_C>(sb, P, job); job = nx; }
      PROF_G(6);
#pragma unroll 1
      while (job < DM + NK) {
        const int nx = draw();
        kv_task(P, job - DM + KV1);
        __syncwarp();
        if (lane == 0) flag_add(g_flags + FL_KV + 32);
        job = nx;
      }
      warp_flag_wait(g_flags + FL_KV + 32, NK);
#pragma unroll 1
      while (job < 2 * DM + NK) { const int nx = draw(); conv_job<CT_C, 16>(sb, P, job - DM - NK); job = nx; }
      PROF_G(5);
      PROF_END();
      return;
    }
    __syncwarp();
  }
  if (blockIdx.x >= 24) {
    PROF_G(24);
    tail_finisher(sb, P);
    PROF_END();
    asm volatile("griddepcontrol.wait;" ::: "memory");
  } else if (rd_warp() < 12) {
    asm volatile("setmaxnreg.inc.sync.aligned.u32 160;");
    tail_gemm(sb, P);
    PROF_END();
  } else {
    asm volatile("setmaxnreg.dec.sync.aligned.u32 32;");
    tail_service(sb);
    PROF_END();
  }
}

}

extern "C" void kernel_launch(void* const* d_in, const int* in_sizes, int n_in, void* d_out, int out_size) {
  typedef const __nv_bfloat16* bp;
  Params P;
  P.x0 = (bp)d_in[0]; P.ck = (bp)d_in[1]; P.cv = (bp)d_in[2]; P.shift = (bp)d_in[3]; P.ssm_k = (bp)d_in[4]; P.ssm_d = (bp)d_in[5];
  P.mem0 = (bp)d_in[7]; P.wq = (bp)d_in[8]; P.wk = (bp)d_in[9]; P.wv = (bp)d_in[10]; P.wo = (bp)d_in[11];
  P.out = (__nv_bfloat16*)d_out;
  typedef CUresult (*Encode)(CUtensorMap*, CUtensorMapDataType, cuuint32_t, void*, const cuuint64_t*, const cuuint64_t*, const cuuint32_t*, const cuuint32_t*,
                             CUtensorMapInterleave, CUtensorMapSwizzle, CUtensorMapL2promotion, CUtensorMapFloatOOBfill);
  static Encode encode = nullptr;
  if (!encode) {
    cudaDriverEntryPointQueryResult qr;
    cudaGetDriverEntryPoint("cuTensorMapEncodeTiled", (void**)&encode, cudaEnableDefault, &qr);
  }
  const cuuint64_t dims[2] = {DM, 4096}, pitch[1] = {DM * 2};
  const cuuint32_t box[2] = {64, 16}, es[2] = {1, 1};
  encode(&P.tm, CU_TENSOR_MAP_DATA_TYPE_BFLOAT16, 2, d_in[11], dims, pitch, box, es, CU_TENSOR_MAP_INTERLEAVE_NONE,
         CU_TENSOR_MAP_SWIZZLE_128B, CU_TENSOR_MAP_L2_PROMOTION_NONE, CU_TENSOR_MAP_FLOAT_OOB_FILL_NONE);
  void* xc = nullptr;
  cudaGetSymbolAddress(&xc, g_xchg);
  P.memx = (uint4*)(((uintptr_t)xc + 0x1FFFFF) & ~(uintptr_t)0x1FFFFF);
  P.d_x = mkdesc(Q_X, 128, 1024, 0); P.d_wl = mkdesc(Q_WL, 16, 1024, 1);
  P.d_ring = mkdesc(W_RING, 512, 128, 0); P.d_ws = mkdesc(W_WS, 16, 1024, 1);
  cudaFuncSetAttribute(head_kernel, cudaFuncAttributeMaxDynamicSharedMemorySize, SMEM_TOTAL);
  cudaFuncSetAttribute(tail_kernel, cudaFuncAttributeMaxDynamicSharedMemorySize, SMEM_TOTAL);
  head_kernel<<<96, 512, SMEM_TOTAL>>>(P);
  cudaLaunchConfig_t cfg = {};
  cfg.gridDim = dim3(36); cfg.blockDim = dim3(512); cfg.dynamicSmemBytes = SMEM_TOTAL; cfg.stream = 0;
  cudaLaunchAttribute attr[1];
  attr[0].id = cudaLaunchAttributeProgrammaticStreamSerialization;
  attr[0].val.programmaticStreamSerializationAllowed = 1;
  cfg.attrs = attr; cfg.numAttrs = 1;
  cudaLaunchKernelEx(&cfg, tail_kernel, P);
}
```

```cpp
#include <cuda.h>
#include <cuda_runtime.h>
#include <cuda_bf16.h>
#include <stdint.h>

namespace {

constexpr int SEQ = 2048, DM = 576, NSEG = 64;
#define LAG_V 5
#define RV_V 1950
#define R1_V 380
#define R0_V 590
#define V1_V 80
#define V2_V 200
#define Q1_V 150
#define Q2_V 290
#define SWAP_V 1
#define ST0_V 200
#define GX_V 1130
#define RS_V 5
#define CALIB 0
#define RF_V 2350
#define RL_V 2000
#define PA1_V 500
#define PA0_V 700
#define XA_V 1
#define XP_V 160
#define CTB_V 6
#define CTC_V 11
#define DP_V 2000
#define NFV_V 24
#define ST_V 5
#define VG_V 0
#define MG_V 3
#define KPV_V 16
#define KP1_V 24
#define KP0_V 28
constexpr int LAG = LAG_V;
constexpr int NT = NSEG + LAG;
constexpr int OXRING = 8;
static_assert(LAG >= 3 && LAG < OXRING, "pipeline lag");
constexpr uint32_t D_RED = RV_V;
__host__ __device__ constexpr uint32_t rank_delay(int r) { return r == 2 ? 0 : r ? R1_V : R0_V; }
__host__ __device__ constexpr int tile_of(int r, int i) { return r == 2 ? i : SWAP_V ? (r ? 3 + i + (i >> 1) : 5 + i + (i > 0)) : 6 - 3 * r + i; }
__host__ __device__ constexpr uint32_t tile_delay(int r, int i) { return (i == 0 ? 0 : r == 2 ? (i == 1 ? V1_V : V2_V) : i == 1 ? Q1_V : Q2_V) * 9 / 16; }
constexpr uint32_t D_DUE = RF_V, D_LATE = RL_V;
constexpr uint32_t D_GX = GX_V * 9 / 16;
constexpr int KP_V = KPV_V, KP_1 = KP1_V, KP_0 = KP0_V;
constexpr int KP_MAX = KP_0 > KP_1 ? KP_0 : KP_1;
constexpr uint32_t SB0 = 1024;
constexpr float SM_SCALE = 0.08838834764831845f * 1.4426950408889634f;
constexpr uint32_t SENT = 0x80008000u;
constexpr uint32_t SPIN_LIMIT = 1u << 21;

constexpr int FL_XS = 0;
constexpr int FL_ACC = (NT + 2) * 32;
constexpr int FL_OX = FL_ACC + 128 * 32;
constexpr int FL_SEL = FL_OX + (NT + 1) * 32;
constexpr int FL_Y = FL_SEL + 96 * 4;
constexpr int FL_KV = FL_Y + 512;
constexpr int FL_TOTAL = FL_KV + 128;

__device__ __align__(1024) uint4 g_y[256 * DM];
__device__ __align__(1024) uint4 g_kv[256 * DM];
__device__ __align__(1024) float4 g_acc[2 * 256 * 36 * 32];
__device__ __align__(1024) uint4 g_xs[NT * 4608];
__device__ __align__(1024) uint4 g_ox[OXRING * 512 * 8 * 8];
__device__ __align__(1024) uint4 g_xchg[(256 + 256 + 45) * 512];
__host__ __device__ constexpr uint32_t part_of(int cta) { return (cta < 81 ? 12 + cta * 3 : 13 + cta * 3) * 8192; }
__device__ __align__(1024) uint32_t g_flagsets[2 * FL_TOTAL];
__device__ uint32_t g_epoch;
#define PROF_T(slot) do {} while (0)
#define PROF_END() do {} while (0)
#define PROF_W(cond, slot) do {} while (0)
#define PROF_V(cond, slot, val) do { (void)(val); } while (0)
#define PROF_G(slot) do {} while (0)
#define PROF_OR(slot, val) do {} while (0)
#define PROF_A(idx, val) do { (void)(val); } while (0)
#define PROF_BEGIN() do {} while (0)
#define PROF_MID() do {} while (0)

#define CHINT ""
#define HINT ", 100000"
__device__ __forceinline__ uint32_t pack_bf16(float lo, float hi) {
  uint32_t r; asm("cvt.rn.bf16x2.f32 %0, %1, %2;" : "=r"(r) : "f"(hi), "f"(lo)); return r;
}
__device__ __forceinline__ float bf_lo(uint32_t w) { return __uint_as_float(__byte_perm(w, 0, 0x1044)); }
__device__ __forceinline__ float bf_hi(uint32_t w) { return __uint_as_float(w & 0xFFFF0000u); }
__device__ __forceinline__ uint32_t mapa(uint32_t a, uint32_t r) {
  uint32_t o; asm("mapa.shared::cluster.u32 %0, %1, %2;" : "=r"(o) : "r"(a), "r"(r)); return o;
}
__device__ __forceinline__ void mbar_init(uint32_t bar, uint32_t cnt) {
  asm volatile("mbarrier.init.shared::cta.b64 [%0], %1;" :: "r"(bar), "r"(cnt) : "memory");
}
__device__ __forceinline__ void mbar_expect(uint32_t bar, uint32_t bytes) {
  asm volatile("mbarrier.arrive.expect_tx.shared::cta.b64 _, [%0], %1;" :: "r"(bar), "r"(bytes) : "memory");
}
__device__ __forceinline__ void mbar_arrive(uint32_t bar) {
  asm volatile("mbarrier.arrive.shared::cta.b64 _, [%0];" :: "r"(bar) : "memory");
}
__device__ __forceinline__ void mbar_arrive_if0(uint32_t sel, uint32_t bar) {
  asm volatile("{\n.reg .pred p;\nsetp.eq.u32 p, %1, 0;\n@p mbarrier.arrive.shared::cta.b64 _, [%0];\n}" :: "r"(bar), "r"(sel) : "memory");
}
__device__ __forceinline__ void mbar_expect_if0(uint32_t sel, uint32_t bar, uint32_t bytes) {
  asm volatile("{\n.reg .pred p;\nsetp.eq.u32 p, %1, 0;\n@p mbarrier.arrive.expect_tx.shared::cta.b64 _, [%0], %2;\n}" :: "r"(bar), "r"(sel), "r"(bytes) : "memory");
}
__device__ __forceinline__ void mbar_rarrive_if0(uint32_t sel, uint32_t bar) {
  asm volatile("{\n.reg .pred p;\nsetp.eq.u32 p, %1, 0;\n@p mbarrier.arrive.relaxed.cluster.shared::cluster.b64 _, [%0];\n}" :: "r"(bar), "r"(sel) : "memory");
}
__device__ __forceinline__ void mbar_wait_lim(uint32_t bar, uint32_t par) {
  asm volatile(
    "{\n.reg .pred p;\n.reg .u32 c;\nmov.u32 c, 0;\n"
    "W_%=:\n"
    "mbarrier.try_wait.parity.shared::cta.b64 p, [%0], %1;\n"
    "@p bra D_%=;\n"
    "add.u32 c, c, 1;\nsetp.lt.u32 p, c, %2;\n@p bra W_%=;\ntrap;\n"
    "D_%=:\n}\n" :: "r"(bar), "r"(par), "n"(SPIN_LIMIT) : "memory");
}
__device__ __forceinline__ void mbar_wait(uint32_t bar, uint32_t par) {
  asm volatile(
    "{\n.reg .pred p;\n"
    "W_%=:\n"
    "mbarrier.try_wait.parity.shared::cta.b64 p, [%0], %1" HINT ";\n"
    "@!p bra W_%=;\n}\n" :: "r"(bar), "r"(par) : "memory");
}
__device__ __forceinline__ void mbar_spin(uint32_t bar, uint32_t par) {
  asm volatile("{\n.reg .pred p;\nW_%=:\nmbarrier.try_wait.parity.shared::cta.b64 p, [%0], %1;\n@!p bra W_%=;\n}\n" :: "r"(bar), "r"(par) : "memory");
}
__device__ __forceinline__ uint32_t mbar_test(uint32_t bar, uint32_t par) {
  uint32_t r;
  asm volatile("{\n.reg .pred p;\nmbarrier.test_wait.parity.shared::cta.b64 p, [%1], %2;\nselp.u32 %0, 1, 0, p;\n}" : "=r"(r) : "r"(bar), "r"(par) : "memory");
  return __shfl_sync(0xffffffffu, r, 0);
}
__device__ __forceinline__ void mbar_wait_if(uint32_t& done, uint32_t test, uint32_t bar, uint32_t par, bool force) {
  asm volatile(
    "{\n.reg .pred p, q;\nsetp.ne.u32 p, %0, 0;\n@p bra.uni D_%=;\nsetp.ne.u32 q, %4, 0;\n"
    "mbarrier.test_wait.parity.shared::cta.b64 p, [%1], %3;\n"
    "or.pred p, p, q;\n@!p bra D_%=;\n"
    "W_%=:\n"
    "mbarrier.try_wait.parity.shared::cta.b64 p, [%2], %3, 100000;\n"
    "@!p bra W_%=;\nmov.u32 %0, 1;\nD_%=:\n}\n" : "+r"(done) : "r"(test), "r"(bar), "r"(par), "r"((uint32_t)force) : "memory");
}
template <int ID, int N> __device__ __forceinline__ void bar_sync() { asm volatile("bar.sync %0, %1;" :: "n"(ID), "n"(N) : "memory"); }
template <int ID, int N> __device__ __forceinline__ void bar_arrive() { asm volatile("bar.arrive %0, %1;" :: "n"(ID), "n"(N) : "memory"); }
__device__ __forceinline__ void bar_sync_r(int id, int n) { asm volatile("bar.sync %0, %1;" :: "r"(id), "r"(n) : "memory"); }
__device__ __forceinline__ void bar_arrive_r(int id, int n) { asm volatile("bar.arrive %0, %1;" :: "r"(id), "r"(n) : "memory"); }
__device__ __forceinline__ uint32_t pin(uint32_t x) { return __shfl_sync(0xffffffffu, x, threadIdx.x); }
__device__ __forceinline__ void cluster_sync() {
  asm volatile("barrier.cluster.arrive.aligned;\nbarrier.cluster.wait.aligned;" ::: "memory");
}
__device__ __forceinline__ void fence_async_smem() { asm volatile("fence.proxy.async.shared::cta;" ::: "memory"); }
__device__ __forceinline__ void fence_async_global() { asm volatile("fence.proxy.async.global;" ::: "memory"); }
__device__ __forceinline__ uint4 ld_poll(const uint4* p) {
  uint4 v;
  asm volatile("ld.relaxed.gpu.global.v4.u32 {%0,%1,%2,%3}, [%4];" : "=r"(v.x), "=r"(v.y), "=r"(v.z), "=r"(v.w) : "l"(p) : "memory");
  return v;
}
__device__ __forceinline__ uint32_t rd_clock() { uint64_t c; asm volatile("mov.u64 %0, %%clock64;" : "=l"(c) :: "memory"); return (uint32_t)c; }
__device__ __forceinline__ void spin_until(uint32_t when) {
  asm volatile("{\n.reg .pred p;\n.reg .b64 c;\n.reg .s32 lo;\nS_%=:\nmov.u64 c, %%clock64;\ncvt.u32.u64 lo, c;\nsub.s32 lo, lo, %0;\n"
               "setp.lt.s32 p, lo, 0;\n@p bra.uni S_%=;\n}" :: "r"(when) : "memory");
}
__device__ __forceinline__ uint32_t near_page(uint4* pair, uint32_t mark) {
  uint32_t best0 = ~0u, best1 = ~0u;
  const int lane = threadIdx.x & 31;
#pragma unroll 1
  for (int r = 0; r < 8; r++) {
    if (r >= 4 && !(r & 1) && __all_sync(0xffffffffu, max(best0, best1) - min(best0, best1) > 110u && min(best0, best1) < 420u)) break;
    uint32_t t0, t1, v;
    asm volatile("mov.u32 %0, %%clock;" : "=r"(t0) :: "memory");
    asm volatile("{\n.reg .pred p;\nsetp.eq.u32 p, %2, 0;\nmov.u32 %0, 0;\n@p atom.relaxed.gpu.global.exch.b32 %0, [%1], %3;\n}"
                 : "=&r"(v) : "l"(pair + (r & 1) * 256), "r"(lane), "r"(mark) : "memory");
    asm volatile("{\n.reg .pred p;\nsetp.ne.u32 p, %1, 0x9E3779B9;\nmov.u32 %0, %2;\n@p mov.u32 %0, %%clock;\n}" : "=&r"(t1) : "r"(v), "r"(t0 - 1) : "memory");
    if (r & 1) best1 = min(best1, t1 - t0); else best0 = min(best0, t1 - t0);
  }
  return best1 < best0;
}
__device__ __forceinline__ void st_gpu4(uint4* p, uint32_t a, uint32_t b, uint32_t c, uint32_t d) {
  asm volatile("st.relaxed.gpu.global.v4.u32 [%0], {%1,%2,%3,%4};" :: "l"(p), "r"(a), "r"(b), "r"(c), "r"(d) : "memory");
}
__device__ __forceinline__ void st_gpu1(uint32_t* p, uint32_t a) {
  asm volatile("st.relaxed.gpu.global.u32 [%0], %1;" :: "l"(p), "r"(a) : "memory");
}
__device__ __forceinline__ void st_gpu1_if(bool c, uint32_t* p, uint32_t a) {
  asm volatile("{\n.reg .pred p;\nsetp.ne.u32 p, %2, 0;\n@p st.relaxed.gpu.global.u32 [%0], %1;\n}" :: "l"(p), "r"(a), "r"((uint32_t)c) : "memory");
}
__device__ __forceinline__ void warp_flag_wait(const uint32_t* p, uint32_t target) {
  uint32_t v, n = 0;
  do {
    asm volatile("ld.relaxed.gpu.global.u32 %0, [%1];" : "=r"(v) : "l"(p) : "memory");
    if (++n > SPIN_LIMIT) __trap();
  } while (__any_sync(0xffffffffu, v < target));
}
__device__ __forceinline__ void flag_add(uint32_t* p) {
  asm volatile("red.release.gpu.global.add.u32 [%0], 1;" :: "l"(p) : "memory");
}
__device__ __forceinline__ void bulk_g2s(uint32_t dst, const void* src, uint32_t bytes, uint32_t bar) {
  asm volatile("cp.async.bulk.shared::cluster.global.mbarrier::complete_tx::bytes [%0], [%1], %2, [%3];"
               :: "r"(dst), "l"(src), "r"(bytes), "r"(bar) : "memory");
}
__device__ __forceinline__ void bulk_g2s_mc(uint32_t dst, const void* src, uint32_t bytes, uint32_t bar, uint16_t mask) {
  asm volatile("cp.async.bulk.shared::cluster.global.mbarrier::complete_tx::bytes.multicast::cluster [%0], [%1], %2, [%3], %4;"
               :: "r"(dst), "l"(src), "r"(bytes), "r"(bar), "h"(mask) : "memory");
}
__device__ __forceinline__ void tma_box(uint32_t dst, const CUtensorMap* tm, int col, int row, uint32_t bar) {
  asm volatile("cp.async.bulk.tensor.2d.shared::cluster.global.mbarrier::complete_tx::bytes [%0], [%1, {%2, %3}], [%4];"
               :: "r"(dst), "l"(tm), "r"(col), "r"(row), "r"(bar) : "memory");
}
__device__ __forceinline__ void bulk_s2s(uint32_t dst, uint32_t src, uint32_t bytes, uint32_t bar) {
  asm volatile("cp.async.bulk.shared::cluster.shared::cta.mbarrier::complete_tx::bytes [%0], [%1], %2, [%3];"
               :: "r"(dst), "r"(src), "r"(bytes), "r"(bar) : "memory");
}
__device__ __forceinline__ void bulk_s2g(void* dst, uint32_t src, uint32_t bytes) {
  asm volatile("cp.async.bulk.global.shared::cta.bulk_group [%0], [%1], %2;" :: "l"(dst), "r"(src), "r"(bytes) : "memory");
}
__device__ __forceinline__ void bulk_commit_wait() {
  asm volatile("cp.async.bulk.commit_group;\ncp.async.bulk.wait_group 0;" ::: "memory");
}
__device__ __forceinline__ bool elect_one() {
  uint32_t p; asm volatile("{\n.reg .pred p;\nelect.sync _|p, 0xffffffff;\nselp.u32 %0, 1, 0, p;\n}" : "=r"(p)); return p;
}
__device__ __forceinline__ void ldsm4(uint32_t& r0, uint32_t& r1, uint32_t& r2, uint32_t& r3, uint32_t a) {
  asm volatile("ldmatrix.sync.aligned.m8n8.x4.shared.b16 {%0,%1,%2,%3}, [%4];" : "=r"(r0), "=r"(r1), "=r"(r2), "=r"(r3) : "r"(a) : "memory");
}
__device__ __forceinline__ void ldsm4t(uint32_t& r0, uint32_t& r1, uint32_t& r2, uint32_t& r3, uint32_t a) {
  asm volatile("ldmatrix.sync.aligned.m8n8.x4.trans.shared.b16 {%0,%1,%2,%3}, [%4];" : "=r"(r0), "=r"(r1), "=r"(r2), "=r"(r3) : "r"(a) : "memory");
}
__device__ __forceinline__ void stsm4(uint32_t a, uint32_t r0, uint32_t r1, uint32_t r2, uint32_t r3) {
  asm volatile("stmatrix.sync.aligned.m8n8.x4.shared.b16 [%0], {%1,%2,%3,%4};" :: "r"(a), "r"(r0), "r"(r1), "r"(r2), "r"(r3) : "memory");
}
__device__ __forceinline__ void stsm2(uint32_t a, uint32_t r0, uint32_t r1) {
  asm volatile("stmatrix.sync.aligned.m8n8.x2.shared.b16 [%0], {%1,%2};" :: "r"(a), "r"(r0), "r"(r1) : "memory");
}
__device__ __forceinline__ void stsm4t(uint32_t a, uint32_t r0, uint32_t r1, uint32_t r2, uint32_t r3) {
  asm volatile("stmatrix.sync.aligned.m8n8.x4.trans.shared.b16 [%0], {%1,%2,%3,%4};" :: "r"(a), "r"(r0), "r"(r1), "r"(r2), "r"(r3) : "memory");
}
__device__ __forceinline__ float4 lds4f(uint32_t a) {
  float4 v; asm volatile("ld.shared.v4.f32 {%0,%1,%2,%3}, [%4];" : "=f"(v.x), "=f"(v.y), "=f"(v.z), "=f"(v.w) : "r"(a) : "memory"); return v;
}
__device__ __forceinline__ uint4 lds4(uint32_t a) {
  uint4 v; asm volatile("ld.shared.v4.u32 {%0,%1,%2,%3}, [%4];" : "=r"(v.x), "=r"(v.y), "=r"(v.z), "=r"(v.w) : "r"(a) : "memory"); return v;
}
__device__ __forceinline__ uint32_t lds1(uint32_t a) {
  uint32_t v; asm volatile("ld.shared.u32 %0, [%1];" : "=r"(v) : "r"(a) : "memory"); return v;
}
__device__ __forceinline__ void sts4(uint32_t a, uint4 v) {
  asm volatile("st.shared.v4.u32 [%0], {%1,%2,%3,%4};" :: "r"(a), "r"(v.x), "r"(v.y), "r"(v.z), "r"(v.w) : "memory");
}
__device__ __forceinline__ void sts1(uint32_t a, uint32_t v) { asm volatile("st.shared.u32 [%0], %1;" :: "r"(a), "r"(v) : "memory"); }
__device__ __forceinline__ void mma16816(float (&d)[4], uint32_t a0, uint32_t a1, uint32_t a2, uint32_t a3, uint32_t b0, uint32_t b1) {
  asm volatile("mma.sync.aligned.m16n8k16.row.col.f32.bf16.bf16.f32 {%0,%1,%2,%3}, {%4,%5,%6,%7}, {%8,%9}, {%0,%1,%2,%3};"
               : "+f"(d[0]), "+f"(d[1]), "+f"(d[2]), "+f"(d[3]) : "r"(a0), "r"(a1), "r"(a2), "r"(a3), "r"(b0), "r"(b1));
}
__device__ __forceinline__ void mma1688(float (&d)[4], uint32_t a0, uint32_t a1, uint32_t b0) {
  asm volatile("mma.sync.aligned.m16n8k8.row.col.f32.bf16.bf16.f32 {%0,%1,%2,%3}, {%4,%5}, {%6}, {%0,%1,%2,%3};"
               : "+f"(d[0]), "+f"(d[1]), "+f"(d[2]), "+f"(d[3]) : "r"(a0), "r"(a1), "r"(b0));
}
__device__ __forceinline__ float rcp(float x) { float r; asm("rcp.approx.ftz.f32 %0, %1;" : "=f"(r) : "f"(x)); return r; }
__device__ __forceinline__ float sqr(float x) { float r; asm("sqrt.approx.f32 %0, %1;" : "=f"(r) : "f"(x)); return r; }
__device__ __forceinline__ float ex2(float x) { float r; asm("ex2.approx.ftz.f32 %0, %1;" : "=f"(r) : "f"(x)); return r; }

__device__ __forceinline__ uint32_t bf2_op(uint32_t a, uint32_t b, uint32_t c) {
  uint32_t r; asm("fma.rn.bf16x2 %0, %1, %2, %3;" : "=r"(r) : "r"(a), "r"(b), "r"(c)); return r;
}
__device__ __forceinline__ uint32_t bf2_mul(uint32_t a, uint32_t b) {
  uint32_t r; asm("mul.rn.bf16x2 %0, %1, %2;" : "=r"(r) : "r"(a), "r"(b)); return r;
}
__device__ __forceinline__ uint32_t bf2_add(uint32_t a, uint32_t b) {
  uint32_t r; asm("add.rn.bf16x2 %0, %1, %2;" : "=r"(r) : "r"(a), "r"(b)); return r;
}

__host__ __device__ constexpr uint64_t mkdesc(uint32_t off, uint32_t lbo, uint32_t sbo, uint32_t sw) {
  return (uint64_t)((SB0 + off) >> 4) | ((uint64_t)(lbo >> 4) << 16) | ((uint64_t)(sbo >> 4) << 32) | ((uint64_t)sw << 62);
}
__device__ __forceinline__ void wg_fence() { asm volatile("wgmma.fence.sync.aligned;" ::: "memory"); }
__device__ __forceinline__ void wg_commit() { asm volatile("wgmma.commit_group.sync.aligned;" ::: "memory"); }
template <int N> __device__ __forceinline__ void wg_wait() { asm volatile("wgmma.wait_group.sync.aligned %0;" :: "n"(N) : "memory"); }
template <int N> __device__ __forceinline__ void reg_fence(float (&d)[N]) {
#pragma unroll
  for (int i = 0; i < N; i++) asm volatile("" : "+f"(d[i]) :: "memory");
}

#define F4(d, o) "+f"(d[o]), "+f"(d[o + 1]), "+f"(d[o + 2]), "+f"(d[o + 3])
template <int SC, int TB> __device__ __forceinline__ void wg_rs(float (&d)[8], const uint32_t* a, uint64_t db, int ob) {
  asm volatile("{\n.reg .pred p;\n.reg .b64 b;\nsetp.ne.b32 p, %13, 0;\nadd.s64 b, %12, %15;\n"
    "wgmma.mma_async.sync.aligned.m64n16k16.f32.bf16.bf16 {%0,%1,%2,%3,%4,%5,%6,%7}, {%8,%9,%10,%11}, b, p, 1, 1, %14;\n}\n"
    : F4(d, 0), F4(d, 4) : "r"(a[0]), "r"(a[1]), "r"(a[2]), "r"(a[3]), "l"(db), "n"(SC), "n"(TB), "l"((uint64_t)ob));
}
template <int SC, int TB> __device__ __forceinline__ void wg_rs(float (&d)[12], const uint32_t* a, uint64_t db, int ob) {
  asm volatile("{\n.reg .pred p;\n.reg .b64 b;\nsetp.ne.b32 p, %17, 0;\nadd.s64 b, %16, %19;\n"
    "wgmma.mma_async.sync.aligned.m64n24k16.f32.bf16.bf16 {%0,%1,%2,%3,%4,%5,%6,%7,%8,%9,%10,%11}, {%12,%13,%14,%15}, b, p, 1, 1, %18;\n}\n"
    : F4(d, 0), F4(d, 4), F4(d, 8) : "r"(a[0]), "r"(a[1]), "r"(a[2]), "r"(a[3]), "l"(db), "n"(SC), "n"(TB), "l"((uint64_t)ob));
}
template <int SC, int TB> __device__ __forceinline__ void wg_rs(float (&d)[16], const uint32_t* a, uint64_t db, int ob) {
  asm volatile("{\n.reg .pred p;\n.reg .b64 b;\nsetp.ne.b32 p, %21, 0;\nadd.s64 b, %20, %23;\n"
    "wgmma.mma_async.sync.aligned.m64n32k16.f32.bf16.bf16 {%0,%1,%2,%3,%4,%5,%6,%7,%8,%9,%10,%11,%12,%13,%14,%15}, {%16,%17,%18,%19}, b, p, 1, 1, %22;\n}\n"
    : F4(d, 0), F4(d, 4), F4(d, 8), F4(d, 12) : "r"(a[0]), "r"(a[1]), "r"(a[2]), "r"(a[3]), "l"(db), "n"(SC), "n"(TB), "l"((uint64_t)ob));
}
template <int SC, int TB> __device__ __forceinline__ void wg_rs(float (&d)[28], const uint32_t* a, uint64_t db, int ob) {
  asm volatile("{\n.reg .pred p;\n.reg .b64 b;\nsetp.ne.b32 p, %33, 0;\nadd.s64 b, %32, %35;\n"
    "wgmma.mma_async.sync.aligned.m64n56k16.f32.bf16.bf16 {%0,%1,%2,%3,%4,%5,%6,%7,%8,%9,%10,%11,%12,%13,%14,%15,%16,%17,%18,%19,%20,%21,%22,%23,%24,%25,%26,%27}, {%28,%29,%30,%31}, b, p, 1, 1, %34;\n}\n"
    : F4(d, 0), F4(d, 4), F4(d, 8), F4(d, 12), F4(d, 16), F4(d, 20), F4(d, 24) : "r"(a[0]), "r"(a[1]), "r"(a[2]), "r"(a[3]), "l"(db), "n"(SC), "n"(TB), "l"((uint64_t)ob));
}
template <int SC, int TB> __device__ __forceinline__ void wg_ss(float (&d)[8], uint64_t da, int oa, uint64_t db, int ob) {
  asm volatile("{\n.reg .pred p;\n.reg .b64 a, b;\nsetp.ne.b32 p, %10, 0;\nadd.s64 a, %8, %12;\nadd.s64 b, %9, %13;\n"
    "wgmma.mma_async.sync.aligned.m64n16k16.f32.bf16.bf16 {%0,%1,%2,%3,%4,%5,%6,%7}, a, b, p, 1, 1, 1, %11;\n}\n"
    : F4(d, 0), F4(d, 4) : "l"(da), "l"(db), "n"(SC), "n"(TB), "l"((uint64_t)oa), "l"((uint64_t)ob));
}
template <int SC, int TB> __device__ __forceinline__ void wg_ss(float (&d)[12], uint64_t da, int oa, uint64_t db, int ob) {
  asm volatile("{\n.reg .pred p;\n.reg .b64 a, b;\nsetp.ne.b32 p, %14, 0;\nadd.s64 a, %12, %16;\nadd.s64 b, %13, %17;\n"
    "wgmma.mma_async.sync.aligned.m64n24k16.f32.bf16.bf16 {%0,%1,%2,%3,%4,%5,%6,%7,%8,%9,%10,%11}, a, b, p, 1, 1, 1, %15;\n}\n"
    : F4(d, 0), F4(d, 4), F4(d, 8) : "l"(da), "l"(db), "n"(SC), "n"(TB), "l"((uint64_t)oa), "l"((uint64_t)ob));
}
template <int SC, int TB> __device__ __forceinline__ void wg_ss(float (&d)[16], uint64_t da, int oa, uint64_t db, int ob) {
  asm volatile("{\n.reg .pred p;\n.reg .b64 a, b;\nsetp.ne.b32 p, %18, 0;\nadd.s64 a, %16, %20;\nadd.s64 b, %17, %21;\n"
    "wgmma.mma_async.sync.aligned.m64n32k16.f32.bf16.bf16 {%0,%1,%2,%3,%4,%5,%6,%7,%8,%9,%10,%11,%12,%13,%14,%15}, a, b, p, 1, 1, 1, %19;\n}\n"
    : F4(d, 0), F4(d, 4), F4(d, 8), F4(d, 12) : "l"(da), "l"(db), "n"(SC), "n"(TB), "l"((uint64_t)oa), "l"((uint64_t)ob));
}
template <int SC, int TB> __device__ __forceinline__ void wg_ss(float (&d)[20], uint64_t da, int oa, uint64_t db, int ob) {
  asm volatile("{\n.reg .pred p;\n.reg .b64 a, b;\nsetp.ne.b32 p, %22, 0;\nadd.s64 a, %20, %24;\nadd.s64 b, %21, %25;\n"
    "wgmma.mma_async.sync.aligned.m64n40k16.f32.bf16.bf16 {%0,%1,%2,%3,%4,%5,%6,%7,%8,%9,%10,%11,%12,%13,%14,%15,%16,%17,%18,%19}, a, b, p, 1, 1, 1, %23;\n}\n"
    : F4(d, 0), F4(d, 4), F4(d, 8), F4(d, 12), F4(d, 16) : "l"(da), "l"(db), "n"(SC), "n"(TB), "l"((uint64_t)oa), "l"((uint64_t)ob));
}
template <int SC, int TB> __device__ __forceinline__ void wg_ss(float (&d)[28], uint64_t da, int oa, uint64_t db, int ob) {
  asm volatile("{\n.reg .pred p;\n.reg .b64 a, b;\nsetp.ne.b32 p, %30, 0;\nadd.s64 a, %28, %32;\nadd.s64 b, %29, %33;\n"
    "wgmma.mma_async.sync.aligned.m64n56k16.f32.bf16.bf16 {%0,%1,%2,%3,%4,%5,%6,%7,%8,%9,%10,%11,%12,%13,%14,%15,%16,%17,%18,%19,%20,%21,%22,%23,%24,%25,%26,%27}, a, b, p, 1, 1, 1, %31;\n}\n"
    : F4(d, 0), F4(d, 4), F4(d, 8), F4(d, 12), F4(d, 16), F4(d, 20), F4(d, 24) : "l"(da), "l"(db), "n"(SC), "n"(TB), "l"((uint64_t)oa), "l"((uint64_t)ob));
}

template <int SC> __device__ __forceinline__ void wg_sskk(float (&d)[16], uint64_t da, int oa, uint64_t db, int ob) {
  asm volatile("{\n.reg .pred p;\n.reg .b64 a, b;\nsetp.ne.b32 p, %18, 0;\nadd.s64 a, %16, %19;\nadd.s64 b, %17, %20;\n"
    "wgmma.mma_async.sync.aligned.m64n32k16.f32.bf16.bf16 {%0,%1,%2,%3,%4,%5,%6,%7,%8,%9,%10,%11,%12,%13,%14,%15}, a, b, p, 1, 1, 0, 0;\n}\n"
    : F4(d, 0), F4(d, 4), F4(d, 8), F4(d, 12) : "l"(da), "l"(db), "n"(SC), "l"((uint64_t)oa), "l"((uint64_t)ob));
}

template <int NK> __device__ __forceinline__ void load_afrags(uint32_t* a, uint32_t tile, int w, int lane) {
  int i = lane >> 3, r = lane & 7;
  uint32_t base = tile + ((i >> 1) * 8 + r) * 128 + (((2 * w + (i & 1)) ^ r) << 4);
#pragma unroll
  for (int kk = 0; kk < NK; kk++) ldsm4t(a[4 * kk], a[4 * kk + 1], a[4 * kk + 2], a[4 * kk + 3], base + kk * 2048);
}

constexpr uint32_t Q_WL = 0;
constexpr uint32_t Q_WO = 24576;
constexpr uint32_t Q_OX = Q_WO;
constexpr uint32_t Q_X = 73728;
constexpr uint32_t Q_CS = 10240;
constexpr uint32_t Q_STG = 165888;
constexpr uint32_t Q_OB = 190464;
constexpr uint32_t Q_SIN = 194560;
constexpr uint32_t Q_PX = 204800;
constexpr uint32_t Q_SOUT = Q_PX;
constexpr int Q_KR = 30;
constexpr uint32_t BARS = 228352;
constexpr uint32_t B_CP = BARS;
constexpr uint32_t B_OK = BARS + 408;
constexpr uint32_t B_G0 = BARS + 272;
constexpr uint32_t B_XF = BARS + 72;
constexpr uint32_t B_E = BARS + 224;
constexpr uint32_t B_SM = BARS + 160;
constexpr uint32_t B_O = BARS + 168;
constexpr uint32_t B_P = BARS + 176;
constexpr uint32_t B_OXREADY = BARS + 192;
constexpr uint32_t B_OXFREE = BARS + 200;
constexpr uint32_t B_REF = BARS + 208;
constexpr uint32_t B_AN = BARS + 264;
constexpr uint32_t B_PZ = BARS + 256;
constexpr uint32_t B_RES = BARS + 216;
constexpr uint32_t Q_REF = BARS + 288;
constexpr uint32_t Q_SEL = BARS + 304;
constexpr uint32_t Q_SET = BARS + 360;
constexpr uint32_t SM_BYTES = 4 * 1024, SX_BYTES = 2560, PX_BYTES = 2 * 14 * 128;
constexpr int W_KR = 29;
constexpr uint32_t W_RING = 0;
constexpr uint32_t W_WS = 196608;
constexpr uint32_t W_FT = 0;
constexpr uint32_t W_FO = 18688;
constexpr uint32_t W_Z = 30720;
constexpr uint32_t W_RS = 49152;
constexpr uint32_t W_ST = 28672;
constexpr int CT_A = 2, CT_B = CTB_V, CT_C = CTC_V;
static_assert(36 * CT_C <= 36 * CT_B + 192, "kv stages");
constexpr uint32_t C_U = 256 + 4096;
constexpr uint32_t C_CH = C_U + 64 + 8192 + 96;
constexpr uint32_t B_FULL = BARS;
constexpr uint32_t B_EMPTY = BARS + 128;
constexpr uint32_t B_FT = BARS + 160;
constexpr uint32_t B_RF = BARS + 176;
constexpr uint32_t B_WT = BARS + 248;
constexpr uint32_t W_K1 = BARS + 240;
constexpr uint32_t SMEM_TOTAL = BARS + 512;

struct Params {
  CUtensorMap tm;
  const __nv_bfloat16 *x0, *wq, *wk, *wv, *wo, *mem0, *ck, *cv, *shift, *ssm_k, *ssm_d;
  __nv_bfloat16* out;
  uint4* memx;
  uint64_t d_x, d_wl, d_ring, d_ws;
};

constexpr uint64_t D_QK = mkdesc(Q_STG, 768, 128, 0), D_WO = mkdesc(Q_WO, 16, 1024, 1), D_OB = mkdesc(Q_OB, 128, 2048, 0), D_PX = mkdesc(Q_PX, 128, 768, 0);
constexpr uint64_t D_V = mkdesc(Q_STG, 128, 768, 0);

#define g_flags (g_flagsets + lds1(sb + Q_SET))

__device__ __forceinline__ int rd_cid() { uint32_t v; asm volatile("mov.u32 %0, %%clusterid.x;" : "=r"(v)); return v; }
__device__ __forceinline__ int rd_rank() { uint32_t v; asm volatile("mov.u32 %0, %%cluster_ctarank;" : "=r"(v)); return v; }
__device__ __forceinline__ int rd_lane() { uint32_t v; asm volatile("mov.u32 %0, %%laneid;" : "=r"(v)); return v; }
__device__ __forceinline__ int rd_warp() { uint32_t v; asm volatile("mov.u32 %0, %%tid.x;" : "=r"(v)); return __shfl_sync(0xffffffffu, v >> 5, 0); }

template <int NA>
__device__ __forceinline__ void proj_step(float (&acc)[NA], const uint32_t* a, uint64_t db, uint64_t dwl, int k) {
  const int ob = (k >> 2) * (Q_CS / 16) + (k & 3) * 16;
  if (k == 0) wg_rs<0, 1>(acc, a, db, ob);
  else if (k % 6 != 5) wg_rs<1, 1>(acc, a + 4 * (k - k / 6), db, ob);
  else wg_ss<1, 1>(acc, dwl, 128 * (k / 6), db, ob);
}
__device__ __forceinline__ void stage_groups(uint32_t stl, const uint32_t (&pk)[14]) {
#pragma unroll
  for (int h = 0; h < 2; h++) {
    stsm4(stl + h * 768 + 256, pk[h], pk[2 + h], pk[4 + h], 0);
    stsm4(stl + h * 768 + 6144 + 128, pk[6 + h], pk[8 + h], pk[10 + h], pk[12 + h]);
  }
}
__device__ __forceinline__ void head_main(uint32_t sb, const Params& P) {
  const int lane = threadIdx.x & 31, warp = rd_warp(), w = warp & 3, wg = warp >> 2, rank = rd_rank();
  uint32_t a[4 * Q_KR];
  {
    const int tid = threadIdx.x & 127;
    const __nv_bfloat16* src = (rank == 2 ? P.wv + wg * 64 : (wg ? P.wk : P.wq) + rank * 64) + rd_cid() * 128 + (size_t)(tid >> 3) * 4096 + (tid & 7) * 8;
    const uint32_t so = (tid >> 3) * 128 + (((tid & 7) ^ ((tid >> 3) & 7)) << 4), st = sb + Q_X + wg * (Q_KR * 2048);
    uint4 v[36];
#pragma unroll
    for (int k = 0; k < 36; k++) v[k] = __ldg((const uint4*)(src + (size_t)k * 65536));
#pragma unroll
    for (int k = 0; k < 36; k++) sts4(so + (k % 6 == 5 ? sb + Q_WL + wg * 12288 + (k / 6) * 2048 : st + (k - k / 6) * 2048), v[k]);
    bar_sync_r(9 + wg, wg ? 128 : 224);
    PROF_G(7);
    load_afrags<Q_KR>(a, st, w, lane);
    fence_async_smem();
    bar_arrive<11, 384>();
  }
  cluster_sync();
  PROF_G(8);
  const uint64_t dwl = P.d_wl + wg * 768, dq = D_QK + wg * 384;
  const uint32_t stg = sb + Q_STG + wg * 12288 + 2 * w * 768;
  const uint32_t stm = pin(stg + (lane >> 4) * 6144 + ((lane >> 3) & 1) * 768 + (lane & 7) * 16), stl = pin(stg + lane * 16);
  const uint32_t rel = mapa(sb + B_E, 0), rev = mapa(sb + B_E, 2), sel = pin(threadIdx.x & 127), arm = pin(threadIdx.x - 128 > 8), xfa = pin(sb + B_XF + 8 * lane);
  const uint32_t sx = sb + (wg == rank ? Q_SIN + rank * 4096 : Q_SOUT + 2048), s0 = w ? sx + (2 * w - 1) * 512 : sb + Q_SOUT + wg * 1024, s1 = sx + 2 * w * 512;
  const uint32_t sd0 = pin(s0 + lane * 16), sd1 = pin(s1 + lane * 16), sr = sb + Q_SIN + rank * 4096;
  const int kp = rank == 2 ? KP_V : rank ? KP_1 : KP_0;
  const uint32_t selq = pin(sel | rank >> 1);
    const uint32_t pz = sb + (rank == 2 ? B_SM : B_PZ);
  uint32_t pk[14] = {};
#pragma unroll 1
  for (int t = 0;; t++) {
    const uint32_t par = t & 1;
    uint32_t paused = 0;
    if (t == 0) {
      mbar_wait(sb + B_XF, 0);
    } else {
      float m[12];
#pragma unroll
      for (int c = 0; c < 9; c++) {
        mbar_spin(sb + B_OK + 8 * c, par ^ 1);
        if (c == 0 || c == 3 || c == 8) PROF_W(warp == 0, c == 0 ? 0 : c == 3 ? 1 : 3);
        if (c == 8) mbar_rarrive_if0(selq, rev + 24);
        wg_fence();
#pragma unroll
        for (int k = 4 * c; k < 4 * c + 4; k++) proj_step(m, a, P.d_x, dwl, k);
        if (c == 0) { mbar_expect_if0(arm, xfa, 7168); mbar_rarrive_if0(sel | (rank ^ 2), rel); }
        if (c == XA_V) mbar_rarrive_if0(selq, rel);
        if (c == MG_V) mbar_rarrive_if0(sel, rev);
        if (c == ST_V && rank == 2) {
          if (t > 1) bar_sync<3, 384>();
          stage_groups(stl, pk);
        }
      }
      wg_commit();
      if (rank == 2 && t < NT) { mbar_wait(sb + B_XF, par); paused = mbar_test(pz, par ^ 1); }
      wg_wait<0>();
      reg_fence(m);
      PROF_W(warp == 0, 2);
      stsm4(stm, pack_bf16(m[0], m[1]), pack_bf16(m[2], m[3]), pack_bf16(m[4], m[5]), pack_bf16(m[6], m[7]));
      stsm2(stm + 128, pack_bf16(m[8], m[9]), pack_bf16(m[10], m[11]));
      if (rank == 2) {
        bar_arrive<1, 384>();
        mbar_rarrive_if0(sel, rel + 16);
        if (t == NT) break;
        if (paused) mbar_wait(sb + B_RES, par ^ 1);
      } else {
        float s[20];
        bar_sync<1, 256>();
        fence_async_smem();
        wg_fence();
        wg_ss<0, 1>(s, dq, 0, dq, 768);
#pragma unroll
        for (int i = 1; i < 4; i++) wg_ss<1, 1>(s, dq, 96 * i, dq, 768 + 96 * i);
        wg_commit();
        mbar_rarrive_if0(sel ^ 96, rel + 16);
        if (t < NT) mbar_wait(sb + B_XF, par);
        wg_wait<0>();
        reg_fence(s);
        if (w < 3) {
          sts4(sd0, make_uint4(pack_bf16(s[0], s[1]), pack_bf16(s[4], s[5]), pack_bf16(s[8], s[9]), pack_bf16(s[12], s[13])));
          if (w != 1) sts1(sd0 + 512, pack_bf16(s[16], s[17]));
          if (w == 0) {
            fence_async_smem();
            __syncwarp();
            if (elect_one()) bulk_s2s(mapa(sr + wg * 1024, 2), s0, 1024, mapa(sb + B_SM, 2));
            __syncwarp();
            PROF_W(wg == 1, 4); PROF_W(wg == 0, 8);
          }
          if (w < 2) sts4(sd1, make_uint4(pack_bf16(s[2], s[3]), pack_bf16(s[6], s[7]), pack_bf16(s[10], s[11]), pack_bf16(s[14], s[15])));
          bar_arrive<8, 224>();
        }
        if (t == NT) break;
      }
    }
    float e[28];
#pragma unroll
    for (int k = 0; k < 36; k++) {
      if (k == 2 && t > 0) {
        mbar_expect_if0(arm, xfa - (B_XF - B_CP), 2048);
        mbar_expect_if0(sel | wg, sb + B_G0, 9216);
      }
      if (k % 4 == 0 && k) mbar_wait(sb + B_XF + 2 * k, par);
      if (k == 0) PROF_W(warp == 0, 5);
      if (k % 2 == 0 && k && k <= KP_MAX) {
        mbar_wait_if(paused, pz, sb + B_RES, par ^ 1, k == kp);
      }
      if (k % 4 == 0 || (k % 2 == 0 && k <= KP_MAX)) wg_fence();
      proj_step(e, a, P.d_x + 192, dwl, k);
    }
    wg_commit();
    mbar_wait(sb + B_G0, par);
    wg_wait<0>();
    reg_fence(e);
    PROF_W(warp == 0, 10);
#pragma unroll
    for (int i = 0; i < 14; i++) pk[i] = pack_bf16(e[2 * i], e[2 * i + 1]);
    if (rank != 2) stage_groups(stl, pk);
    PROF_W(warp == 0, 12);
  }
  cluster_sync();
}

__device__ __forceinline__ uint32_t next_tick() {
  uint64_t g0, g1;
  asm volatile("mov.u64 %0, %%globaltimer;" : "=l"(g0) :: "memory");
#pragma unroll 1
  for (int n = 0; n < 8; n++) {
    asm volatile("mov.u64 %0, %%globaltimer;" : "=l"(g1) :: "memory");
    if (__any_sync(0xffffffffu, (uint32_t)g1 != (uint32_t)g0)) break;
  }
  return (uint32_t)g1;
}
__device__ __forceinline__ void wait_ns(uint32_t when) {
  uint32_t c;
  asm volatile("{\n.reg .pred p;\n.reg .b64 g;\n.reg .s32 lo;\nS_%=:\nmov.u64 g, %%globaltimer;\ncvt.u32.u64 lo, g;\nsub.s32 lo, %1, lo;\n"
               "setp.gt.s32 p, lo, 31;\n@p bra.uni S_%=;\nmov.u64 g, %%clock64;\ncvt.u32.u64 %0, g;\nshl.b32 lo, lo, 1;\nadd.s32 %0, %0, lo;\n}" : "=&r"(c) : "r"(when) : "memory");
  spin_until(c - 30);
}
template <bool TAG>
__device__ __forceinline__ uint32_t poll4(uint4 (&v)[4], const uint4* src, uint32_t tag) {
#pragma unroll
  for (int j = 0; j < 4; j++) v[j] = ld_poll(src + j * 32);
  uint32_t n = 0;
  while (__any_sync(0xffffffffu, TAG ? (((v[0].x ^ tag) | (v[1].x ^ tag) | (v[2].x ^ tag) | (v[3].x ^ tag)) & 1) != 0
                                     : (v[0].x == SENT || v[1].x == SENT || v[2].x == SENT || v[3].x == SENT))) {
#pragma unroll
    for (int j = 0; j < 4; j++) if (TAG ? ((v[j].x ^ tag) & 1) != 0 : v[j].x == SENT) v[j] = ld_poll(src + j * 32);
    if (++n > SPIN_LIMIT) __trap();
  }
  return n;
}

__device__ __forceinline__ void read_reference(uint32_t sb, const Params& P, uint32_t& ref, int rank, int t) {
  const int lane = rd_lane();
  const uint32_t* tms = (const uint32_t*)(P.memx + 9 * 512 + lds1(sb + Q_SEL + 48) / 16 + (rd_cid() >> 4) * 32 + lane) + rank;
  if (t > 1) wait_ns(ref + D_GX + (D_DUE - rank_delay(rank)) * 9 / 16); else ref = next_tick();
  uint32_t d, n = 0;
  do {
    asm volatile("ld.relaxed.gpu.global.u32 %0, [%1];" : "=r"(d) : "l"(tms) : "memory");
    if (++n > SPIN_LIMIT) __trap();
  } while (__any_sync(0xffffffffu, (d ^ t) & 255));
  ref += __reduce_max_sync(0xffffffffu, (int)(d - (ref << 6))) >> 6;
  sts1(sb + Q_REF, ref);
  __syncwarp();
  mbar_arrive_if0(lane, sb + B_REF);
  PROF_A(13, n);
  PROF_T(19);
  PROF_V(true, 11, ref - (D_RED + rank_delay(rank)) * 9 / 16);
}
template <int STEP>
__device__ __forceinline__ void check_tiles(uint32_t sb, const Params& P, int w, int t) {
  const int lane = rd_lane();
  uint32_t chk = sb + Q_X + w * Q_CS + lane * 32 + (lane >> 2) * 4, bad = 0;
#pragma unroll 1
  for (uint32_t bar = sb + B_CP + 8 * w; bar <= sb + B_CP + 64; bar += 8 * STEP, chk += STEP * Q_CS) {
    uint32_t ok;
    asm volatile("{\n.reg .pred p, q;\n.reg .b32 a, b;\nsetp.eq.u32 q, %4, 0;\n"
                 "W_%=:\nmbarrier.try_wait.parity.shared::cta.b64 p, [%1], %2" CHINT ";\n@!p bra W_%=;\n"
                 "ld.shared.u32 a, [%3];\nld.shared.u32 b, [%3 + 1024];\nsetp.ne.u32 p, a, 0x80008000;\nsetp.ne.and.u32 p, b, 0x80008000, p;\n"
                 "vote.sync.all.pred p, p, 0xFFFFFFFF;\nand.pred q, q, p;\n@q mbarrier.arrive.shared::cta.b64 _, [%1 + %5];\nselp.u32 %0, 1, 0, p;\n}"
                 : "=r"(ok) : "r"(bar), "r"(~t & 1), "r"(chk), "r"(lane), "n"(B_OK - B_CP) : "memory");
    const int c = (bar - sb - B_CP) / 8;
    if (!ok) {
      uint4 v[4];
      poll4<false>(v, P.memx + c * 512 + (t & 1) * 128 + lds1(sb + Q_SEL + 4 * c) / 16 + lane, 0);
#pragma unroll
      for (int j = 0; j < 4; j++) sts4(sb + Q_X + c * Q_CS + j * 512 + lane * 16, v[j]);
      fence_async_smem();
      __syncwarp();
      mbar_arrive_if0(lane, bar + B_OK - B_CP);
      PROF_OR(7, 1 << c);
      PROF_A(c, 1);
      bad |= c < 3 * VG_V + 3;
    }
    if (STEP == 3) mbar_arrive_if0(lane | (c / 3 != (bad ? 2 : VG_V)), sb + B_E + 24);
  }
}
__device__ __forceinline__ void load_scores(float (&s)[10], uint32_t sa) {
  const uint4 a = lds4(sa), b = lds4(sa + 4096);
  const uint32_t a4 = lds1(sa + 512), b4 = lds1(sa + 4608);
  const uint32_t e[5] = {bf2_add(a.x, b.x), bf2_add(a.y, b.y), bf2_add(a.z, b.z), bf2_add(a.w, b.w), bf2_add(a4, b4)};
#pragma unroll
  for (int i = 0; i < 5; i++) { s[2 * i] = bf_lo(e[i]); s[2 * i + 1] = bf_hi(e[i]); }
}
__device__ __forceinline__ void softmax_num(float (&s)[10]) {
  float mx = fmaxf(fmaxf(fmaxf(s[0], s[1]), fmaxf(s[2], s[3])), fmaxf(fmaxf(s[4], s[5]), fmaxf(s[6], s[7])));
  mx = fmaxf(mx, fmaxf(s[8], s[9]));
  const float m1 = __shfl_xor_sync(0xffffffffu, mx, 1), m2 = __shfl_xor_sync(0xffffffffu, mx, 2), m3 = __shfl_xor_sync(0xffffffffu, mx, 3);
  mx = fmaxf(fmaxf(mx, m1), fmaxf(m2, m3));
  mx *= -SM_SCALE;
#pragma unroll
  for (int i = 0; i < 10; i++) s[i] = ex2(fmaf(s[i], SM_SCALE, mx));
}

template <int NF>
__device__ __forceinline__ void wo_tiles(uint32_t sb, const uint32_t (&f)[76], char* d0, uint32_t pg, uint32_t rs, int t) {
  float d[2][8];
  auto mma = [&](int i, int k0, int k1) {
#pragma unroll
    for (int k = k0; k < k1; k++) {
      if (8 * i + k >= NF && k == 0) wg_ss<0, 0>(d[i & 1], D_WO, 1024 * i, D_OB, 0);
      else if (8 * i + k >= NF || (i == 2 && ((k & 1) || k == 6))) wg_ss<1, 0>(d[i & 1], D_WO, 1024 * i + 128 * k, D_OB, 16 * k);
      else if (k == 0) wg_rs<0, 0>(d[i & 1], f + 32 * i, D_OB, 0);
      else wg_rs<1, 0>(d[i & 1], f + (i < 2 ? 32 * i + 4 * k : 64 + 2 * k), D_OB, 16 * k);
    }
    wg_commit();
  };
  auto put = [&](float (&q)[8]) {
    reg_fence(q);
    st_gpu4((uint4*)d0, (pack_bf16(q[0], q[1]) & ~1u) | ((t - 1) >> 1 & 1), pack_bf16(q[4], q[5]), pack_bf16(q[2], q[3]), pack_bf16(q[6], q[7]));
    __syncwarp();
  };
  wg_fence();
  mma(0, 0, 8);
  mma(1, 0, 8);
  wg_wait<1>();
  put(d[0]);
  PROF_W(threadIdx.x < 288, 14);
  wg_fence();
  mma(2, 0, RS_V);
  d0 += pg & 0xFFFF;
  wg_wait<1>();
  put(d[1]);
  PROF_W(threadIdx.x < 288, 15);
  mma(2, RS_V, 8);
  d0 += pg >> 16;
  wg_wait<1>();
  mbar_arrive_if0(rs, sb + B_RES);
  PROF_W(threadIdx.x < 288, 17);
  wg_wait<0>();
  put(d[0]);
  PROF_W(threadIdx.x < 288, 16);
}
__device__ __forceinline__ void probe_pages(uint32_t sb, const Params& P, int own) {
  const int lane = threadIdx.x & 31;
  const uint32_t first = own ? part_of(blockIdx.x) : 0;
  const uint32_t sel = __shfl_sync(0xffffffffu, near_page(P.memx + first / 16 + (own ? 0 : (blockIdx.x & 63) * 2), own ? 1 : SENT), 0);
  if (lane < (own ? 3 : 10))
    sts1(sb + Q_SEL + 4 * (own ? 9 + lane : lane == 9 ? 12 : lane), ((sel ^ __popc(((first + lane * 8192) ^ first) & 0xB2000)) & 1) * 4096);
}
__device__ __forceinline__ void head_aux(uint32_t sb, const Params& P) {
  const int tid = threadIdx.x & 127, w = rd_warp() & 3, rank = rd_rank(), head = __shfl_sync(0xffffffffu, rd_cid(), 0);
  uint32_t m0[20];
  {
    uint4 a[12], b[12];
#pragma unroll
    for (int j = 0; j < 12; j++) {
      const int u = j;
      const int r = (u & 3) * 32 + (tid >> 2);
      const uint4* src = (const uint4*)(P.wo + (size_t)(head * 128 + (r & 64) + (r & 7) * 8 + ((r >> 3) & 7)) * DM + tile_of(rank, u >> 2) * 64) + (tid & 3) * 2;
      a[j] = __ldg(src); b[j] = __ldg(src + 1);
    }
#pragma unroll
    for (int j = 0; j < 12; j++) {
      const int u = j;
      const int r = (u & 3) * 32 + (tid >> 2);
      const uint32_t dst = sb + Q_WO + (u >> 2) * 16384 + r * 128 + ((((tid & 3) * 2) ^ (r & 7) ^ ((head >> 2) & 1)) << 4);
      sts4(dst, make_uint4(__byte_perm(a[j].x, a[j].y, 0x5410), __byte_perm(a[j].z, a[j].w, 0x5410), __byte_perm(b[j].x, b[j].y, 0x5410), __byte_perm(b[j].z, b[j].w, 0x5410)));
      sts4(dst ^ 16, make_uint4(__byte_perm(a[j].x, a[j].y, 0x7632), __byte_perm(a[j].z, a[j].w, 0x7632), __byte_perm(b[j].x, b[j].y, 0x7632), __byte_perm(b[j].z, b[j].w, 0x7632)));
    }
  }
#pragma unroll
  for (int j = 0; j < 20; j++) {
    const int k = min(tid + (j >> 2) * 128, DM - 1);
    m0[j] = bf2_add(__bfloat16_as_ushort(P.mem0[2 * (j & 3) * DM + k]) | (uint32_t)__bfloat16_as_ushort(P.mem0[(2 * (j & 3) + 1) * DM + k]) << 16, 0);
  }
#pragma unroll
  for (int i = 0; i < 6; i++) sts4(sb + Q_PX + (i * 128 + tid) * 16, make_uint4(0, 0, 0, 0));
  bar_sync<11, 384>();
#pragma unroll
  for (int j = 0; j < 5; j++) {
    const int k = min(tid + j * 128, DM - 1);
    sts4(sb + Q_X + (k >> 6) * Q_CS + (k & 63) * 16, make_uint4(m0[4 * j], m0[4 * j + 1], m0[4 * j + 2], m0[4 * j + 3]));
    sts4(sb + Q_X + (k >> 6) * Q_CS + (k & 63) * 16 + 1024, make_uint4(m0[4 * j], m0[4 * j + 1], m0[4 * j + 2], m0[4 * j + 3]));
  }
#pragma unroll
  for (int i = 0; i < 2; i++) sts4(sb + Q_STG + (i * 16 + (tid >> 3)) * 768 + 640 + (tid & 7) * 16, make_uint4(0, 0, 0, 0));
  fence_async_smem();
  PROF_G(2);
  const uint32_t wa = pin(sb + Q_WO + ((tid >> 4 & 1) * 8 + (tid & 7)) * 128 + (((2 * w + ((tid >> 3) & 1)) ^ (tid & 7)) << 4));
  char* pd = nullptr;
  uint32_t pg = 0;
  auto find_pieces = [&]() {
    const int lane = tid & 31, dcta = (w * 8 + (lane >> 2)) * 3 + rank;
    uint4 f;
    uint32_t n = 0;
    do {
      f = ld_poll((const uint4*)(g_flags + FL_SEL) + dcta);
      if (++n > SPIN_LIMIT) __trap();
    } while (__any_sync(0xffffffffu, !f.x || !f.y || !f.z));
    pd = (char*)P.memx + part_of(dcta) + (head * 4 + (lane & 3) + (f.x - 1) * 256) * 16;
    pg = (8192 + (f.y - f.x) * 4096) | (8192 + (f.z - f.y) * 4096) << 16;
  };
  auto load_group0 = [&](int t) {
    mbar_wait(sb + B_XF, t & 1);
    if (t > 0) mbar_wait(sb + B_E + 16, (t - 1) & 1);
    fence_async_global();
    if (elect_one()) {
#pragma unroll
      for (int k = 0; k < 9; k++) bulk_g2s_mc(sb + Q_X + 2048 + k * Q_CS, (const char*)g_xs + (size_t)t * 73728 + k * 8192, 1024, sb + B_G0, 7);
    }
    __syncwarp();
  };
  uint32_t f[76];
  if (rank != 2) {
#pragma unroll
    for (int k = 0; k < 19; k++) ldsm4t(f[4 * k], f[4 * k + 1], f[4 * k + 2], f[4 * k + 3], wa + (k < 16 ? k : 2 * k - 16) * 2048);
    const uint32_t rs = pin(tid);
    cluster_sync();
    if (w == 3 && rank == 0) load_group0(0);
#pragma unroll 1
    for (int t = 1;; t++) {
      if (t > 1) check_tiles<4>(sb, P, w, t);
      if (w == 0) {
        bar_sync<8, 224>();
        fence_async_smem();
        if (elect_one()) {
          bulk_s2s(mapa(sb + Q_SIN + rank * 4096, rank ^ 1), sb + Q_SOUT + 2048, SX_BYTES, mapa(sb + B_SM, rank ^ 1));
          mbar_arrive(sb + B_SM);
        }
        __syncwarp();
      }
      if (t == NT) break;
      if (t == 1) find_pieces();
      pd = (char*)((uintptr_t)pd ^ 2048);
      if (w == 3 && rank == 0) load_group0(t);
      if (w == 2) { uint32_t ref = lds1(sb + Q_REF); read_reference(sb, P, ref, rank, t); }
      if (w == 1) {
        mbar_wait(sb + B_AN, (t - 1) & 1);
        spin_until(rd_clock() + (rank ? PA1_V : PA0_V));
        mbar_arrive_if0(rs - 32, sb + B_PZ);
      }
      mbar_spin(sb + B_O, (t - 1) & 1);
      PROF_W(w == 0, 13);
      wo_tiles<24>(sb, f, pd, pg, rs, t);
      mbar_expect_if0(rs, sb + B_O, 4096);
    }
  } else {
#pragma unroll
    for (int k = 0; k < 8; k++) ldsm4t(f[4 * k], f[4 * k + 1], f[4 * k + 2], f[4 * k + 3], wa + k * 2048);
    cluster_sync();
    find_pieces();
    const int l = w & 1, tile = w >> 1;
    const uint32_t ob = pin(sb + Q_OB + (l ^ ((head >> 1) & 1)) * 2048 + tile * 1024 + (tid >> 2 & 7) * 128 + (tid & 3) * 16);
    const uint32_t ob0 = sb + Q_OB + ((head >> 1) & 1) * 2048;
    const uint32_t sa = pin(sb + Q_SIN + l * 1024 + (tid & 31) * 16);
#pragma unroll 1
    for (int t = 1; t <= NT; t++) {
      const uint32_t par = (t - 1) & 1;
      {
        uint32_t vf[4][10], p[5];
        float s[10], o[4][4];
        const int lane = rd_lane();
        const uint32_t vb = sb + Q_STG + tile * 12288 + l * 6144 + (lane & 7) * 16;
        const uint32_t ax = vb + ((lane >> 3) & 1) * 768 + (lane >> 4) * 128;
        pd = (char*)((uintptr_t)pd ^ 2048);
        bar_sync<1, 384>();
#pragma unroll
        for (int i = 0; i < 4; i++) ldsm4(vf[i][4], vf[i][5], vf[i][6], vf[i][7], ax + i * 1536 + 256);
        ldsm4(vf[0][8], vf[0][9], vf[1][8], vf[1][9], vb + (lane >> 3) * 768 + 512);
        ldsm4(vf[2][8], vf[2][9], vf[3][8], vf[3][9], vb + (lane >> 3) * 768 + 512 + 3072);
#pragma unroll
        for (int i = 0; i < 4; i++) ldsm4(vf[i][0], vf[i][1], vf[i][2], vf[i][3], ax + i * 1536);
        mbar_spin(sb + B_SM, par);
        PROF_W(w == 0, 20);
        if (t < NT) {
          load_scores(s, sa);
          __syncwarp();
          softmax_num(s);
#pragma unroll
          for (int j = 0; j < 5; j++) p[j] = pack_bf16(s[2 * j], s[2 * j + 1]);
          __syncwarp();
          PROF_W(w == 0, 9);
          float z[4] = {0.f, 0.f, 0.f, 0.f};
          const uint32_t ONE = 0x3F803F80u;
          mma16816(z, ONE, ONE, ONE, ONE, p[0], p[1]);
#pragma unroll
          for (int i = 0; i < 4; i++) { o[i][0] = o[i][1] = o[i][2] = o[i][3] = 0.f; mma16816(o[i], vf[i][0], vf[i][1], vf[i][2], vf[i][3], p[0], p[1]); }
#pragma unroll
          for (int k = 8; k < (NFV_V < 12 ? NFV_V : 12); k++) ldsm4t(f[4 * k], f[4 * k + 1], f[4 * k + 2], f[4 * k + 3], wa + k * 2048);
          mma16816(z, ONE, ONE, ONE, ONE, p[2], p[3]);
#pragma unroll
          for (int i = 0; i < 4; i++) mma16816(o[i], vf[i][4], vf[i][5], vf[i][6], vf[i][7], p[2], p[3]);
#pragma unroll
          for (int k = 12; k < (NFV_V < 16 ? NFV_V : 16); k++) ldsm4t(f[4 * k], f[4 * k + 1], f[4 * k + 2], f[4 * k + 3], wa + k * 2048);
          mma1688(z, ONE, ONE, p[4]);
#pragma unroll
          for (int i = 0; i < 4; i++) mma1688(o[i], vf[i][8], vf[i][9], p[4]);
#pragma unroll
          for (int k = 16; k < 19 && 2 * k - 16 < NFV_V; k++) ldsm4t(f[4 * k], f[4 * k + 1], f[4 * k + 2], f[4 * k + 3], wa + (2 * k - 16) * 2048);
          const float r0 = rcp(z[0]), r1 = rcp(z[1]);
          const uint4 u0 = make_uint4(pack_bf16(o[0][0] * r0, o[0][2] * r0), pack_bf16(o[1][0] * r0, o[1][2] * r0),
                                      pack_bf16(o[2][0] * r0, o[2][2] * r0), pack_bf16(o[3][0] * r0, o[3][2] * r0));
          const uint4 u1 = make_uint4(pack_bf16(o[0][1] * r1, o[0][3] * r1), pack_bf16(o[1][1] * r1, o[1][3] * r1),
                                      pack_bf16(o[2][1] * r1, o[2][3] * r1), pack_bf16(o[3][1] * r1, o[3][3] * r1));
          PROF_W(w == 0, 8);
          sts4(ob, u0);
          sts4(ob + 64, u1);
          bar_sync<5, 160>();
          fence_async_smem();
          PROF_W(w == 0, 13);
          wo_tiles<NFV_V>(sb, f, pd, pg, ob ^ ob0, t);
        }
      }
      const int lane = rd_lane();
      mbar_expect_if0(lane | w, sb + B_SM, SM_BYTES);
      if (t == NT) fence_async_smem();
      {
        float o[2][16];
        uint32_t px[16];
        const uint32_t ox = sb + Q_OX + 2 * w * 512 + lane * 16, pb = sb + B_P + 8 * (t & 1);
        const uint64_t dp = D_PX + (t & 1) * 384;
        mbar_wait(pb, ((t - 1) >> 1) & 1);
        PROF_W(w == 0, 7);
#pragma unroll
        for (int l2 = 0; l2 < 3; l2++) {
          if (l2 == 1) {
            if (t < NT) bar_sync<12, 160>();
            mbar_wait(sb + B_OXFREE, par ^ 1);
          }
          if (l2 < 2) {
            wg_fence();
#pragma unroll
            for (int i = 0; i < 2; i++) {
              wg_sskk<0>(o[i], D_V, l2 * 384 + i * 768, dp, l2 * 192);
              wg_sskk<1>(o[i], D_V, l2 * 384 + i * 768 + 16, dp, l2 * 192 + 16);
              wg_sskk<1>(o[i], D_V, l2 * 384 + i * 768 + 32, dp, l2 * 192 + 32);
            }
            wg_commit();
          }
          if (l2 > 0) {
#pragma unroll
            for (int i = 0; i < 4; i++)
              stsm4(ox + (l2 - 1) * 8192 + (i >> 1) * 4096 + (i & 1) * 512, px[(i >> 1) * 8 + (i & 1)], px[(i >> 1) * 8 + 2 + (i & 1)], px[(i >> 1) * 8 + 4 + (i & 1)], px[(i >> 1) * 8 + 6 + (i & 1)]);
          }
          if (l2 < 2) {
            wg_wait<0>();
            if (l2 == 1 && t < NT) bar_arrive<3, 384>();
            reg_fence(o[0]); reg_fence(o[1]);
#pragma unroll
            for (int i = 0; i < 16; i++) px[i] = pack_bf16(o[i >> 3][2 * (i & 7)], o[i >> 3][2 * (i & 7) + 1]);
          }
        }
        mbar_expect_if0(lane | w, pb, PX_BYTES);
      }
      fence_async_smem();
      __syncwarp();
      mbar_arrive_if0(lane, sb + B_OXREADY);
      PROF_W(w == 0, 23);
    }
  }
  cluster_sync();
}

__device__ __forceinline__ void softmax_x(uint32_t sb, int w, int rank, int t) {
  float s[10];
  const int lane = rd_lane();
  mbar_wait(sb + B_SM, (t - 1) & 1);
  PROF_W(w == 3, 20);
  load_scores(s, sb + Q_SIN + w * 512 + lane * 16);
  const int last = 8 + 8 * w + (lane >> 2) - 2 * (lane & 3);
#pragma unroll
  for (int i = 2; i < 10; i++) s[i] = (8 * (i >> 1) + (i & 1) <= last) ? s[i] : -INFINITY;
  softmax_num(s);
  float sum = ((s[0] + s[1]) + (s[2] + s[3])) + ((s[4] + s[5]) + (s[6] + s[7])) + (s[8] + s[9]);
  sum = (sum + __shfl_xor_sync(0xffffffffu, sum, 1)) + (__shfl_xor_sync(0xffffffffu, sum, 2) + __shfl_xor_sync(0xffffffffu, sum, 3));
  const float r = rcp(sum);
  const uint32_t po = sb + Q_SOUT + 6144 + w * 768;
#pragma unroll
  for (int j = 0; j < 5; j++) sts1(po + lane * 4 + j * 128, pack_bf16(s[2 * j] * r, s[2 * j + 1] * r));
  fence_async_smem();
  __syncwarp();
  if (elect_one()) bulk_s2s(mapa(sb + Q_PX + ((t & 1) * 2 + rank) * 3072 + w * 768, 2), po, 128 * (w + 2), mapa(sb + B_P + 8 * (t & 1), 2));
  __syncwarp();
  PROF_W(w == 3, 22);
}

__device__ __forceinline__ uint32_t word_of(int lane, int head) {
  return (lane & 4) * 1024 + (lane & 8) * 128 + head * 32 + (lane & 16) + (lane & 3) * 4;
}
__device__ __forceinline__ uint32_t service_setup(uint32_t sb, const Params& P, int rank, int w, uint32_t& sof) {
  uint32_t gof = 0;
  sof = part_of(blockIdx.x) + (w - 1) * 8192;
  asm volatile("barrier.cluster.arrive.aligned;" ::: "memory");
  if (w) {
    const int lane = rd_lane(), c = tile_of(rank, w - 1);
    char* word = (char*)P.memx + c * 8192 + word_of(lane, rd_cid());
#pragma unroll 1
    for (int j = 0; j < 16; j++) st_gpu4((uint4*)((char*)P.memx + sof) + j * 32 + lane, 1, 1, 1, 1);
    st_gpu1((uint32_t*)word, SENT);
    st_gpu1((uint32_t*)(word + 2048), SENT);
    if (w == 2 && lane < 4) st_gpu4(P.memx + (blockIdx.x & 63) * 2 + (lane & 2) * 128 + (lane & 1), SENT, SENT, SENT, SENT);
    bar_sync<9, 224>();
    if (w < 3) probe_pages(sb, P, w == 1);
    bar_sync<12, 96>();
    if (w == 1) PROF_G(0);
    sof += __shfl_sync(0xffffffffu, lds1(sb + Q_SEL + 32 + 4 * w), 0);
    asm volatile("st.release.gpu.global.u32 [%0], %1;" :: "l"(g_flags + FL_SEL + blockIdx.x * 4 + w - 1), "r"(((sof >> 12) & 1) + 1) : "memory");
    if (w == 1) PROF_G(1);
    gof = c * 8192 + lds1(sb + Q_SEL + 4 * c);
  }
  asm volatile("barrier.cluster.wait.aligned;" ::: "memory");
  return __shfl_sync(0xffffffffu, gof, 0);
}
template <bool ISV>
__device__ __forceinline__ void next_state(uint32_t sb, const Params& P, uint32_t sof, uint32_t gof, uint32_t dly, int w, int t) {
  const int lane = rd_lane(), c = gof >> 13;
  const uint4* src = (const uint4*)((char*)P.memx + (sof ^ (t & 1) * 2048)) + lane;
  uint32_t* dst = (uint32_t*)((char*)P.memx + c * 8192 + word_of(lane, rd_cid()) + (~t & 1) * 2048);
  const bool inj = t == LAG && (lane & 8);
  if (t == LAG) {
    const __nv_bfloat16* m0 = P.mem0 + (lane & 3) * 2 * DM + c * 64 + rd_cid() * 2 + (lane >> 4);
    st_gpu1_if(inj, dst, bf2_add(__bfloat16_as_ushort(m0[0]) | (uint32_t)__bfloat16_as_ushort(m0[DM]) << 16, 0));
  }
  asm volatile("" : "+l"(dst), "+l"(src));
  mbar_wait(sb + B_REF, (t - 1) & 1);
  uint32_t when = lds1(sb + Q_REF) + dly;
  uint4 v[4];
  wait_ns(when - (CALIB == 1 ? t % 10 * 28 : 0));
  PROF_W(w == 1, 18);
  const uint32_t nr = poll4<true>(v, src, (t - 1) >> 1);
  PROF_T(25 + w);
  const uint32_t z = bf2_add(bf2_add(v[0].z, v[1].z), bf2_add(v[2].z, v[3].z)), u = bf2_add(bf2_add(v[0].w, v[1].w), bf2_add(v[2].w, v[3].w));
  const uint32_t x = bf2_add(bf2_add(v[0].x, v[1].x), bf2_add(v[2].x, v[3].x)), y = bf2_add(bf2_add(v[0].y, v[1].y), bf2_add(v[2].y, v[3].y));
  const uint32_t x2 = bf2_add(bf2_add(x, 0), __shfl_xor_sync(0xffffffffu, z, 16)), y2 = bf2_add(y, __shfl_xor_sync(0xffffffffu, u, 16));
  const uint32_t x3 = bf2_add(x2, __shfl_xor_sync(0xffffffffu, y2, 8));
  st_gpu1_if(!inj, dst, bf2_add(x3, __shfl_xor_sync(0xffffffffu, x3, 4)));
  if (ISV && w == 3) bar_arrive<12, 160>();
  PROF_T(28 + w);
  PROF_A(9 + w, nr);
  if (!ISV && w == 3) bar_sync<7, 64>();
  wait_ns(when + D_GX - (CALIB == 2 ? t % 10 * 28 : 0));
  if (elect_one()) bulk_g2s_mc(sb + Q_X + c * Q_CS, (const char*)P.memx + gof + (~t & 1) * 2048, 2048, sb + B_CP + 8 * c, 7);
  __syncwarp();
  if (w == 1) PROF_T(21);
  st_gpu1((uint32_t*)((uintptr_t)dst ^ 2048), SENT);
}
__device__ __forceinline__ void service_v(uint32_t sb, const Params& P) {
  const int w = rd_warp() & 3, head = __shfl_sync(0xffffffffu, rd_cid(), 0);
  uint32_t sof, g0 = 0, c0 = 0, ref = 0;
  const uint32_t gof = service_setup(sb, P, 2, w, sof);
#pragma unroll 1
  for (int t = 1; t <= NT; t++) {
    const int lane = rd_lane();
    if (w == 0) {
      if (t < NT) mbar_wait(sb + B_XF, t & 1); else warp_flag_wait(g_flags + FL_XS + NT * 32 + 16, 4);
      mbar_wait(sb + B_OXREADY, (t - 1) & 1);
      if (t < NT) bar_sync<13, 64>();
      if (elect_one()) {
        uint4* od = g_ox + (size_t)(t & (OXRING - 1)) * 32768 + head * 512;
        if (t <= NSEG) bulk_s2g(od, sb + Q_OX, 8192);
        if (t > LAG) bulk_s2g(od + 16384, sb + Q_OX + 8192, 8192);
        bulk_commit_wait();
        mbar_arrive(sb + B_OXFREE);
        flag_add(g_flags + FL_OX + t * 32 + head);
      }
      __syncwarp();
      PROF_T(25);
      continue;
    }
    if (t > 1) check_tiles<3>(sb, P, w - 1, t); else mbar_arrive_if0(lane, sb + B_E + 24);
    if (t == NT) break;
    if (w == 1) {
      const uint32_t due = ref + D_GX + D_DUE * 9 / 16;
      const uint32_t g1 = next_tick(), c1 = rd_clock();
      const uint32_t rate = t > 1 ? __float2uint_rn(65536.f * (g1 - g0) * rcp(c1 - c0)) : 36400;
      g0 = g1; c0 = c1;
      uint4* pub = P.memx + 9 * 512 + (lane & 1) * 256 + (lane & 2) * 16 + head;
      const uint32_t lead = D_RED * rate >> 16, late = D_LATE * rate >> 16, r1 = rank_delay(1) * rate >> 10, r0 = rank_delay(0) * rate >> 10;
      mbar_wait(sb + B_E, (t - 1) & 1);
      PROF_T(4);
      mbar_spin(sb + B_E + 24, (t - 1) & 1);
      uint32_t now = g0 + ((rd_clock() - c0) * rate >> 16);
      now = (now + (t < 3 ? lead + ST0_V : (int)(now + 90 - due) > 0 ? late : lead)) << 6;
      st_gpu4(pub, ((now + r0) & ~255u) | t, ((now + r1) & ~255u) | t, (now & ~255u) | t, 0);
      PROF_T(22);
      PROF_V(true, 1, now >> 6);
      read_reference(sb, P, ref, 2, t);
    }
    if (w == 2) {
      mbar_wait(sb + B_SM, (t - 1) & 1);
      mbar_rarrive_if0(lane >> 1, mapa(sb + B_AN, lane & 1));
      bar_sync<5, 160>();
      fence_async_smem();
      if (elect_one()) {
        bulk_s2s(mapa(sb + Q_OB, 1), sb + Q_OB, 4096, mapa(sb + B_O, 1));
        bulk_s2s(mapa(sb + Q_OB, 0), sb + Q_OB, 4096, mapa(sb + B_O, 0));
      }
      __syncwarp();
    }
    if (w == 3) PROF_MID();
    next_state<true>(sb, P, sof, gof, tile_delay(2, w - 1), w, t);
    if (w == 3) bar_arrive<13, 64>();
  }
  cluster_sync();
}
__device__ __forceinline__ void service_qk(uint32_t sb, const Params& P) {
  const int rank = rd_rank(), w = rd_warp() & 3;
  uint32_t sof;
  const uint32_t gof = service_setup(sb, P, rank, w, sof);
#pragma unroll 1
  for (int t = 0;; t++) {
    const int lane = rd_lane();
    if (w == 0 && rank == 0 && t < NT) {
      const uint32_t* fl = g_flags + FL_XS + t * 32;
      warp_flag_wait(fl + (lane & 1 ? (t >= LAG ? 16 : 0) : (t <= NSEG ? 0 : 16)), 4);
      fence_async_global();
      const char* src = (const char*)g_xs + (size_t)t * 73728;
      if (t > 0) mbar_wait(sb + B_E, (t - 1) & 1);
      PROF_T(24);
      uint32_t at = rd_clock();
#pragma unroll 1
      for (int k = 0; k < 9; k++) {
        if (elect_one()) bulk_g2s_mc(sb + Q_X + 3072 + k * Q_CS, src + 1024 + k * 8192, 7168, sb + B_XF + 8 * k, 7);
        __syncwarp();
        at += t ? XP_V : 0;
        spin_until(at);
      }
      if (t == 0) PROF_G(31);
    }
    if (t == 0) continue;
    softmax_x(sb, w, rank, t);
    if (t == NT) break;
    if (w == 0) bar_arrive<7, 64>();
    mbar_expect_if0(lane | (w - 1), sb + B_SM, SX_BYTES);
    if (w == 3) PROF_MID();
    if (w) next_state<false>(sb, P, sof, gof, tile_delay(rank, w - 1), w, t);
  }
  cluster_sync();
}

__global__ void __cluster_dims__(3, 1, 1) __launch_bounds__(512, 1) head_kernel(const __grid_constant__ Params P) {
  extern __shared__ uint8_t smem_raw[];
  const uint32_t sb = (uint32_t)__cvta_generic_to_shared(smem_raw);
  if ((sb & 0xFFFFFFu) != SB0) __trap();
  asm volatile("griddepcontrol.launch_dependents;");
  if (threadIdx.x < 96) {
    const int i = blockIdx.x * 24 + threadIdx.x % 24, m = threadIdx.x / 24;
    const __nv_bfloat16* p = m == 3 ? P.ssm_k + (size_t)(i >> 2) * SEQ + (i & 3) * 64 : (m == 0 ? P.ck : m == 1 ? P.cv : P.x0) + (size_t)i * 64;
    asm volatile("prefetch.global.L2 [%0];" :: "l"(p));
  } else if (threadIdx.x == 96 && blockIdx.x < 45) {
    asm volatile("prefetch.global.L2 [%0];" :: "l"(blockIdx.x < 36 ? P.shift + blockIdx.x * 64 : P.ssm_d + (blockIdx.x - 36) * 64));
  } else if (threadIdx.x == 97 && blockIdx.x < 72) {
    asm volatile("prefetch.global.L2 [%0];" :: "l"(P.mem0 + blockIdx.x * 64));
  }
  PROF_BEGIN();
  if (threadIdx.x == 416) sts1(sb + Q_SET, (__ldcg(&g_epoch) & 1) * FL_TOTAL);
  const int rank = rd_rank(), wg = rd_warp() >> 2;
  if (threadIdx.x == 448) {
    for (int c = 0; c < 9; c++) { mbar_init(sb + B_CP + 8 * c, 1); mbar_arrive(sb + B_CP + 8 * c); mbar_init(sb + B_OK + 8 * c, 1); mbar_arrive(sb + B_OK + 8 * c); mbar_init(sb + B_XF + 8 * c, 1); mbar_expect(sb + B_XF + 8 * c, 7168); }
    mbar_init(sb + B_E, 6); mbar_init(sb + B_G0, 1); mbar_expect(sb + B_G0, 9216); mbar_init(sb + B_E + 16, 6); mbar_init(sb + B_E + 24, 7);
    mbar_init(sb + B_SM, rank == 2 ? 1 : 2); mbar_init(sb + B_O, 1); mbar_init(sb + B_P, 1); mbar_init(sb + B_P + 8, 1);
    mbar_init(sb + B_REF, 1); mbar_init(sb + B_RES, 1); mbar_init(sb + B_PZ, 1); mbar_init(sb + B_AN, 1); mbar_init(sb + B_OXREADY, 4); mbar_init(sb + B_OXFREE, 1);
    mbar_expect(sb + B_SM, rank == 2 ? SM_BYTES : SX_BYTES); mbar_expect(sb + B_P, PX_BYTES); mbar_expect(sb + B_P + 8, PX_BYTES);
    mbar_expect(sb + B_O, 4096);
    sts1(sb + Q_SEL + 48, 0);
    asm volatile("fence.mbarrier_init.release.cluster;" ::: "memory");
  }
  __syncthreads();
  PROF_G(6);
  if (wg < 2) {
    asm volatile("setmaxnreg.inc.sync.aligned.u32 176;");
    head_main(sb, P);
    PROF_END();
  } else if (wg == 2) {
    asm volatile("setmaxnreg.dec.sync.aligned.u32 120;");
    head_aux(sb, P);
    PROF_END();
  } else {
    asm volatile("setmaxnreg.dec.sync.aligned.u32 40;");
    if (rank == 2) service_v(sb, P); else service_qk(sb, P);
    PROF_END();
  }
}

__device__ __forceinline__ void tail_gemm(uint32_t sb, const Params& P) {
  const int lane = threadIdx.x & 31, warp = rd_warp(), w = warp & 3, wg = warp >> 2, tid = threadIdx.x & 127;
  uint32_t a[4 * W_KR];
  fence_async_smem();
  if (elect_one()) {
#pragma unroll 1
    for (int k = w; k < 32; k += 4)
      tma_box(k < W_KR ? sb + wg * 65536 + k * 2048 : sb + W_WS + wg * 6144 + (k - W_KR) * 2048, &P.tm, (blockIdx.x % 3) * 192 + wg * 64, (blockIdx.x / 3) * 512 + k * 16, sb + B_WT + 8 * wg);
  }
  __syncwarp();
  mbar_wait(sb + B_WT + 8 * wg, 0);
  load_afrags<W_KR>(a, sb + wg * 65536, w, lane);
  fence_async_smem();
  bar_sync<1, 416>();
  PROF_G(26);
  if (wg == 2) bar_arrive<2, 256>();
  const uint64_t dw = P.d_ws + wg * 384;
  float4* dst0 = g_acc + ((blockIdx.x % 3) * 12 + warp) * 32 + lane;
#pragma unroll 1
  for (int t = 1; t <= NT; t++) {
#pragma unroll 1
    for (int l = t > NSEG; l <= (t > LAG); l++) {
      const int seg = t - 1 - l * LAG, grp = (seg & 1) * 2 + l;
      const uint64_t db = P.d_ring + grp * 2048;
      float acc[16];
      bar_sync_r(2 + wg, 256);
#pragma unroll
      for (int c = 0; c < 4; c++) {
        if (wg == 0) mbar_wait(sb + B_FULL + 32 * grp + 8 * c, (seg >> 1) & 1);
        if (c == 0) PROF_T(6 * l + wg);
        wg_fence();
#pragma unroll
        for (int i = 0; i < 8; i++) {
          if (c == 0 && i == 0) wg_rs<0, 1>(acc, a, db, 0);
          else if (8 * c + i < W_KR) wg_rs<1, 1>(acc, a + 32 * c + 4 * i, db, 512 * c + 64 * i);
          else wg_ss<1, 1>(acc, dw, 128 * (8 * c + i - W_KR), db, 512 * c + 64 * i);
        }
      }
      wg_commit();
      bar_arrive_r(wg == 2 ? 2 : 3 + wg, 256);
      wg_wait<0>();
      reg_fence(acc);
      mbar_arrive_if0(tid, sb + B_EMPTY + 8 * grp);
      float4* dst = dst0 + (size_t)(l * 256 + seg * 4) * 1152;
#pragma unroll
      for (int j = 0; j < 4; j++)
        asm volatile("red.relaxed.gpu.global.add.v4.f32 [%0], {%1,%2,%3,%4};" :: "l"(dst + j * 1152),
                     "f"(acc[4 * j]), "f"(acc[4 * j + 1]), "f"(acc[4 * j + 2]), "f"(acc[4 * j + 3]) : "memory");
      bar_sync_r(5 + wg, 160);
    }
  }
}
__device__ __forceinline__ void tail_service(uint32_t sb) {
  const int lane = threadIdx.x & 31, warp = rd_warp();
  if (warp == 12) bar_sync<1, 416>();
#pragma unroll 1
  for (int t = 1; t <= NT; t++) {
    if (warp == 12) {
      const int h0 = (blockIdx.x / 3) * 4;
      warp_flag_wait(g_flags + FL_OX + t * 32 + h0 + (lane & 3), 1);
      fence_async_global();
#pragma unroll 1
      for (int l = t > NSEG; l <= (t > LAG); l++) {
        const int seg = t - 1 - l * LAG, grp = (seg & 1) * 2 + l;
        const uint4* src = g_ox + (size_t)(t % OXRING) * 32768 + l * 16384 + h0 * 512;
        const uint32_t bar = sb + B_FULL + 32 * grp;
        mbar_wait_lim(sb + B_EMPTY + 8 * grp, ((seg >> 1) & 1) ^ 1);
        mbar_expect_if0(lane > 3, bar + 8 * lane, 8192);
        if (elect_one()) {
#pragma unroll
          for (int j = 0; j < 4; j++) bulk_g2s(sb + W_RING + (grp * 4 + j) * 8192, src + j * 512, 8192, bar + 8 * j);
        }
        __syncwarp();
      }
      PROF_T(12);
      PROF_MID();
    } else {
#pragma unroll 1
      for (int l = t > NSEG; l <= (t > LAG); l++) {
        bar_sync_r(warp - 8, 160);
        if (lane == 0) flag_add(g_flags + FL_ACC + (l * 64 + t - 1 - l * LAG) * 32);
        __syncwarp();
        PROF_T(6 * l + warp - 10);
      }
    }
  }
}

__device__ __forceinline__ void wait_k1(uint32_t sb, int n) {
  uint32_t c = 0;
  while ((int)lds1(sb + W_K1) < n) {
    __nanosleep(64);
    if (++c > SPIN_LIMIT) __trap();
  }
}
__device__ __forceinline__ void tail_finisher(uint32_t sb, const Params& P) {
  const int lane = threadIdx.x & 31, warp = rd_warp(), kind = warp < 12 ? warp / 6 : warp & 1, f = warp - 6 * kind, tg = blockIdx.x & 3;
  if (warp >= 14) {
    const uint32_t set = lds1(sb + Q_SET), ft = sb + W_FO + kind * 576;
    if (tg == 0) for (int i = kind * 32 + lane; i < FL_TOTAL; i += 64) g_flagsets[FL_TOTAL - set + i] = 0;
#pragma unroll 1
    for (int t = 0; t < NSEG; t++) {
      warp_flag_wait(g_flags + FL_ACC + (64 + t) * 32, 72);
      PROF_T(17);
      if (t == 0 && tg == 0 && threadIdx.x == 448) g_epoch = set ? 0 : 1;
      const float4* ac = g_acc + ((size_t)(256 + t * 4 + tg) * 36 + kind * 18) * 32 + lane;
      float4 v[18];
#pragma unroll
      for (int i = 0; i < 18; i++) v[i] = __ldcg(ac + i * 32);
#pragma unroll
      for (int i = 0; i < 9; i++) {
        const uint4 r = lds4(sb + W_RS + (8 + (t & 7)) * 9216 + (kind * 9 + i) * 512 + lane * 16);
        stsm4t(ft + (lane & 7) * 1168 + (lane >> 3) * 16 + 64 * i, bf2_add(r.x, pack_bf16(v[2 * i].x, v[2 * i].y)), bf2_add(r.y, pack_bf16(v[2 * i].z, v[2 * i].w)),
               bf2_add(r.z, pack_bf16(v[2 * i + 1].x, v[2 * i + 1].y)), bf2_add(r.w, pack_bf16(v[2 * i + 1].z, v[2 * i + 1].w)));
      }
      fence_async_smem();
      __syncwarp();
      mbar_arrive_if0(lane, sb + B_RF + 8 * (t & 7));
      wait_k1(sb, min(t + LAG + 1, NSEG));
      if (lane < 8) {
        bulk_s2g(P.out + (size_t)((t * 4 + tg) * 8 + lane) * DM + kind * 288, ft + lane * 1168, 576);
        bulk_commit_wait();
      }
      __syncwarp();
      PROF_T(18);
    }
    return;
  }
  if (warp >= 12) {
    for (int i = kind * 32 + lane; i < 1152; i += 64) sts4(sb + W_Z + i * 16, make_uint4(0, 0, 0, 0));
    fence_async_smem();
    bar_sync<12, 64>();
#pragma unroll 1
    for (int t = -1; t <= NSEG; t++) {
      if (kind == 0 && t + 1 < NSEG) {
        const uint32_t bar = sb + B_FT + 8 * ((t + 1) & 1);
        mbar_expect_if0(lane, bar, 9216);
        __syncwarp();
        if (lane < 8) bulk_g2s(sb + W_FT + ((t + 1) & 1) * 9344 + lane * 1168, P.x0 + (size_t)(((t + 1) * 4 + tg) * 8 + lane) * DM, 1152, bar);
      }
      if (t < 0) continue;
      if (t < NSEG) bar_sync_r(9 + 2 * kind, 224);
      if (lane == 0) {
        flag_add(g_flags + FL_XS + (t + kind * LAG) * 32 + kind * 16);
        if (kind) { sts1(sb + W_K1, t + 1); PROF_T(14); }
        if (kind ? t < NSEG : t < LAG) bulk_s2g(g_acc + (size_t)(kind * 256 + t * 4 + tg) * 1152, sb + W_Z, 18432);
        if (kind && t + LAG < NSEG) bulk_s2g(g_acc + (size_t)((t + LAG) * 4 + tg) * 1152, sb + W_Z, 18432);
        bulk_commit_wait();
      }
      __syncwarp();
      if (kind) PROF_MID();
    }
    return;
  }
  const uint32_t BF_1 = 0x3F803F80u;
  const uint32_t* ys = (const uint32_t*)(g_y + ((tg >> 1) * DM + f * 96 + (lane >> 2)) * 2 + (tg & 1)) + (lane & 3);
  const uint32_t rs = sb + W_RS + f * 1536 + lane * 16;
  uint32_t y[12] = {};
#pragma unroll 1
  for (int t = 0; t < NSEG; t++) {
    uint32_t x[12];
    if (kind == 0) {
      wait_k1(sb, t - 6);
      mbar_wait(sb + B_FT + 8 * (t & 1), (t >> 1) & 1);
#pragma unroll
      for (int i = 0; i < 3; i++)
        ldsm4t(x[4 * i], x[4 * i + 1], x[4 * i + 2], x[4 * i + 3], sb + W_FT + (t & 1) * 9344 + (lane & 7) * 1168 + f * 192 + (lane >> 3) * 16 + 64 * i);
    } else {
      warp_flag_wait(g_flags + FL_ACC + t * 32, 72);
      PROF_T(13);
#pragma unroll
      for (int i = 0; i < 6; i++) {
        const float4 v = __ldcg(g_acc + ((size_t)(t * 4 + tg) * 36 + f * 6 + i) * 32 + lane);
        x[2 * i] = pack_bf16(v.x, v.y); x[2 * i + 1] = pack_bf16(v.z, v.w);
      }
#pragma unroll
      for (int i = 0; i < 3; i++) {
        const uint4 r = lds4(rs + (t & 7) * 9216 + i * 512);
        x[4 * i] = bf2_add(x[4 * i], r.x); x[4 * i + 1] = bf2_add(x[4 * i + 1], r.y); x[4 * i + 2] = bf2_add(x[4 * i + 2], r.z); x[4 * i + 3] = bf2_add(x[4 * i + 3], r.w);
      }
      mbar_wait(sb + B_RF + 8 * (t & 7), ((t >> 3) & 1) ^ 1);
      PROF_T(15);
    }
    {
      if (t == 0) PROF_G(27);
#pragma unroll 1
      for (int pass = 0; pass < 2; pass++) {
        float g[2][4] = {};
#pragma unroll
        for (int i = 0; i < 12; i++) {
          uint32_t u;
          asm volatile("movmatrix.sync.aligned.m8n8.trans.b16 %0, %1;" : "=r"(u) : "r"(x[i]));
          mma1688(g[i & 1], u, BF_1, u);
        }
        const uint32_t st = sb + W_ST + kind * 1024 + pass * 512 + (lane & 3) * 16;
        if ((lane >> 3) == (lane & 3))
          asm volatile("st.shared.v2.f32 [%0], {%1,%2};" :: "r"(st + f * 64 + (lane & 4) * 2), "f"(lane & 4 ? g[0][3] + g[1][3] : g[0][2] + g[1][2]),
                       "f"(lane & 4 ? g[0][1] + g[1][1] : g[0][0] + g[1][0]) : "memory");
        bar_sync_r(8 + 2 * kind, 192);
        float s0 = 0.f, s1 = 0.f, q0 = 0.f, q1 = 0.f;
        if (kind && pass == 0) PROF_T(19);
        if (kind && pass == 1) PROF_T(21);
#pragma unroll
        for (int i = 0; i < 6; i++) {
          const float4 e = lds4f(st + i * 64);
          s0 += e.x; q0 += e.y; s1 += e.z; q1 += e.w;
        }
        s0 *= 1.f / 576.f; s1 *= 1.f / 576.f;
        const float v0 = fmaf(q0, 1.f / 576.f, -s0 * s0), v1 = fmaf(q1, 1.f / 576.f, -s1 * s1);
        const uint32_t nmean = pack_bf16(-s0, -s1), vb = pack_bf16(fmaxf(v0, 0.f), fmaxf(v1, 0.f));
        const uint32_t ve = pack_bf16(bf_lo(vb) + 1e-5f, bf_hi(vb) + 1e-5f), sd = pack_bf16(sqr(bf_lo(ve)), sqr(bf_hi(ve)));
        const float r0 = rcp(bf_lo(sd)), r1 = rcp(bf_hi(sd));
        const uint32_t rh = pack_bf16(r0, r1), rl = pack_bf16(r0 - bf_lo(rh), r1 - bf_hi(rh));
        if (pass == 0 && (t == 0 || t == 4 * CT_A || t == 4 * CT_B || t == 4 * CT_C)) {
          if (t == 0) PROF_G(25);
          warp_flag_wait(g_flags + FL_Y + t * 8, t < 4 * CT_B ? 32 : DM);
          if (t == 0) PROF_G(26);
#pragma unroll
          for (int i = 0; i < 12; i++) y[i] = __ldcg(ys + t * (DM * 16) + i * 64);
        }
        uint32_t* xd = (uint32_t*)(g_xs + (size_t)(t + kind * LAG) * 4608 + (kind * 4 + tg) * 64 + (f * 3 >> 1) * 512 + (f & 1) * 32) + lane;
#pragma unroll
        for (int i = 0; i < 12; i++) {
          const uint32_t d = bf2_add(x[i], nmean), q = bf2_op(d, rh, bf2_mul(d, rl));
          if (pass == 0) x[i] = bf2_add(x[i], bf2_mul(q, y[i]));
          else xd[i < 4 ? i * 32 : i < 8 ? i * 32 + (f & 1) * 1792 : i * 32 + 1792] = q;
        }
        if (pass == 0) {
#pragma unroll
          for (int i = 0; i < 3; i++) sts4(rs + (kind * 8 + (t & 7)) * 9216 + i * 512, make_uint4(x[4 * i], x[4 * i + 1], x[4 * i + 2], x[4 * i + 3]));
        }
        if (kind && pass == 0) PROF_T(20);
        if (kind && pass == 1) PROF_T(22);
      }
      if (kind) PROF_T(16);
      if (t < 3) PROF_G(28 + t);
      bar_sync_r(9 + 2 * kind, 224);
#pragma unroll
      for (int i = 0; i < 12; i++) y[i] = __ldcg(ys + ((t + 1) & 63) * (DM * 16) + i * 64);
    }
  }
}

template <int NP, typename V>
__device__ __forceinline__ void kv_block(uint4 (&o)[2 * NP], const Params& P, int r0, int c0) {
  V kk[11], vv[8];
  uint4 sw[NP];
#pragma unroll
  for (int i = 0; i < NP; i++) sw[i] = __ldg((const uint4*)(P.shift + (c0 + 2 * i) * 4));
#pragma unroll
  for (int i = 0; i < 11; i++) kk[i] = r0 + i >= 3 ? __ldg((const V*)(P.ck + (size_t)(r0 + i - 3) * DM + c0)) : V{};
#pragma unroll
  for (int i = 0; i < 8; i++) vv[i] = __ldg((const V*)(P.cv + (size_t)(r0 + i) * DM + c0));
#pragma unroll
  for (int cp = 0; cp < NP; cp++) {
    const uint32_t wt[4] = {__byte_perm(sw[cp].y, sw[cp].w, 0x7632), __byte_perm(sw[cp].y, sw[cp].w, 0x5410),
                            __byte_perm(sw[cp].x, sw[cp].z, 0x7632), __byte_perm(sw[cp].x, sw[cp].z, 0x5410)};
    uint32_t e[8];
#pragma unroll
    for (int i = 0; i < 8; i++) {
      uint32_t a = bf2_mul(((const uint32_t*)&kk[i])[cp], wt[0]);
#pragma unroll
      for (int j = 1; j < 4; j++) a = bf2_add(a, bf2_mul(((const uint32_t*)&kk[i + j])[cp], wt[j]));
      e[i] = bf2_mul(a, ((const uint32_t*)&vv[i])[cp]);
    }
    o[2 * cp] = make_uint4(__byte_perm(e[0], e[1], 0x5410), __byte_perm(e[2], e[3], 0x5410), __byte_perm(e[4], e[5], 0x5410), __byte_perm(e[6], e[7], 0x5410));
    o[2 * cp + 1] = make_uint4(__byte_perm(e[0], e[1], 0x7632), __byte_perm(e[2], e[3], 0x7632), __byte_perm(e[4], e[5], 0x7632), __byte_perm(e[6], e[7], 0x7632));
  }
}
__device__ __forceinline__ void kv_task(const Params& P, int id) {
  const int lane = threadIdx.x & 31, tq = id / 9, c0 = (id % 9) * 64 + (lane >> 2) * 8;
  uint4 o[8];
  kv_block<4, uint4>(o, P, tq * 32 + (lane & 3) * 8, c0);
#pragma unroll
  for (int c = 0; c < 8; c++) g_kv[((size_t)tq * DM + c0 + c) * 4 + (lane & 3)] = o[c];
}
__device__ __forceinline__ int next_job(uint32_t sb) {
  int j = 0;
  if ((threadIdx.x & 31) == 0) j = atomicAdd(g_flags + FL_KV + 96, 1);
  return __shfl_sync(0xffffffffu, j, 0);
}
__device__ __forceinline__ uint2 lds2_ro(uint32_t a) { uint2 v; asm("ld.shared.v2.u32 {%0,%1}, [%2];" : "=r"(v.x), "=r"(v.y) : "r"(a)); return v; }

template <int T0, int T1>
__device__ __forceinline__ void conv_job(uint32_t sb, const Params& P, int ch, int sets = 1) {
  const int lane = threadIdx.x & 31, w = threadIdx.x >> 5;
  uint32_t ub = sb + w * C_CH, zb = ub + C_U;
  constexpr int NL = (T1 + 1) / 2, NS = T0 == 0 ? 2 : 1;
  constexpr bool CTA = T1 <= CT_B;
  static_assert(T0 > 0 || T1 == 2, "second set: buffer offsets, warps");
  PROF_G(13 + 4 * (T0 == 0 ? 0 : T0 == CT_A ? 1 : 2));
  uint2 q[NS][T1];
  uint32_t dd[NS];
#pragma unroll
  for (int n = 0; n < NS; n++) {
    const int c = n < sets ? ch - n * 128 : ch;
#pragma unroll
    for (int u = 0; u < T1; u++) q[n][u] = __ldg((const uint2*)(P.ssm_k + (size_t)c * SEQ) + u * 32 + lane);
    dd[n] = (uint32_t)__bfloat16_as_ushort(P.ssm_d[c]) * 0x10001u;
  }
  if (CTA) {
#pragma unroll
    for (int tq = w; tq < 4 * T1 * sets; tq += 16) {
      uint4 o[2];
      const int n = T0 == 0 ? tq >> 3 : 0, tgp = (tq - 8 * n) * 4 + (lane & 3), c0 = (lane >> 2) * 2;
      kv_block<1, uint32_t>(o, P, tgp * 8, ch - w + c0 - n * 128);
#pragma unroll
      for (int c = 0; c < 2; c++) {
        sts4(sb + (c0 + c) * C_CH + n * 2048 + 256 + tgp * 16, o[c]);
        if (T0) g_kv[((size_t)tq * DM + ch - w + c0 + c) * 4 + (lane & 3)] = o[c];
      }
    }
    __syncwarp();
  } else {
    uint4 o[NL];
#pragma unroll
    for (int u = 0; u < NL; u++) o[u] = __ldcg(g_kv + ((size_t)(u * 8 + (lane >> 2)) * DM + ch) * 4 + (lane & 3));
#pragma unroll
    for (int u = 0; u < NL; u++) sts4(ub + 256 + (u * 32 + lane) * 16, o[u]);
  }
#pragma unroll
  for (int n = 0; n < NS; n++) {
    if (lane < 16) { sts4(ub + n * 2048 + lane * 16, make_uint4(0, 0, 0, 0)); sts1(zb + n * 4096 + lane * 4, 0); }
#pragma unroll
    for (int u = 0; u < T1; u++) {
      const uint2 k = q[n][u];
      const uint32_t pv = __shfl_sync(0xffffffffu, lane == 31 ? (u ? q[n][u ? u - 1 : 0].y : 0u) : k.y, (lane + 31) & 31);
      sts4(zb + n * 4096 + 64 + (u * 32 + lane) * 16, make_uint4(__byte_perm(k.x, pv, 0x7610), __byte_perm(k.x, k.x, 0x1032),
                                                                __byte_perm(k.y, k.x, 0x7610), __byte_perm(k.y, k.y, 0x1032)));
    }
  }
  if (CTA) __syncthreads(); else __syncwarp();
  PROF_G(14 + 4 * (T0 == 0 ? 0 : T0 == CT_A ? 1 : 2));
#pragma unroll 1
  for (int n = 0; n < sets; n++, ub += 2048, zb += 4096) {
    float acc[T1 - T0][4];
#pragma unroll
    for (int i = 0; i < T1 - T0; i++) acc[i][0] = acc[i][1] = acc[i][2] = acc[i][3] = 0.f;
#pragma unroll(T0 == 0 ? 4 : 1)
    for (int r = 0; r < 8; r++) {
      uint2 b[T1];
      uint32_t ba = ub + 256 - r * 32 + lane * 8, zp = zb + 64 + (16 * r + 2 * (lane >> 2) - 4 * (lane & 3)) * 4;
      asm volatile("" : "+r"(zp), "+r"(ba) :: "memory");
#pragma unroll
      for (int i = 0; i < T1; i++) b[i] = lds2_ro(ba + i * 256);
#pragma unroll
      for (int mu = 0; mu < T1; mu++) {
        const uint2 a01 = lds2_ro(zp + 512 * mu), a23 = lds2_ro(zp + 512 * mu - 8);
#pragma unroll
        for (int i = (mu > T0 ? mu : T0); i < T1; i++) mma16816(acc[i - T0], a01.x, a01.y, a23.x, a23.y, b[i - mu].x, b[i - mu].y);
      }
    }
    PROF_G(15 + 4 * (T0 == 0 ? 0 : T0 == CT_A ? 1 : 2));
#pragma unroll
    for (int i = 0; i < T1 - T0; i++)
#pragma unroll
      for (int e = 0; e < 2; e++) {
        const int col = (T0 + i) * 8 + 2 * (lane & 3) + e;
        ((uint32_t*)g_y)[((size_t)col * DM + ch - n * 128) * 8 + (lane >> 2)] =
            bf2_add(pack_bf16(acc[i][e], acc[i][2 + e]), bf2_mul(lds1(ub + 256 + col * 32 + (lane >> 2) * 4), n ? dd[NS - 1] : dd[0]));
      }
  }
  if (CTA) __syncthreads(); else __syncwarp();
  PROF_G(16 + 4 * (T0 == 0 ? 0 : T0 == CT_A ? 1 : 2));
  if (CTA ? threadIdx.x == 480 && (T0 == 0 || ch < 512) : lane == 0) flag_add(g_flags + FL_Y + T0 * 32);
  __syncwarp();
}

__global__ void __launch_bounds__(512, 1) tail_kernel(const __grid_constant__ Params P) {
  extern __shared__ uint8_t smem_raw[];
  const uint32_t sb = (uint32_t)__cvta_generic_to_shared(smem_raw);
  if (sb != SB0) __trap();
  PROF_BEGIN();
  if (threadIdx.x == 0) {
    for (int c = 0; c < 16; c++) mbar_init(sb + B_FULL + 8 * c, 1);
    for (int c = 0; c < 4; c++) mbar_init(sb + B_EMPTY + 8 * c, 3);
    for (int c = 0; c < 2; c++) mbar_init(sb + B_FT + 8 * c, 1);
    for (int c = 0; c < 8; c++) mbar_init(sb + B_RF + 8 * c, 2);
    for (int c = 0; c < 3; c++) { mbar_init(sb + B_WT + 8 * c, 1); mbar_expect(sb + B_WT + 8 * c, 65536); }
    sts1(sb + W_K1, 0);
    sts1(sb + Q_SET, (__ldcg(&g_epoch) & 1) * FL_TOTAL);
    fence_async_smem();
  }
  const int b = blockIdx.x, w = threadIdx.x >> 5;
  if ((b >> 2) == 6) {
    __syncthreads();
  } else {
    conv_job<0, CT_A>(sb, P, b * 16 + w, b < 32 ? 1 : 2);
    PROF_G(3);
#pragma unroll 1
    for (int g = b; g == b || (g >> 2) == 6; g -= 8) conv_job<CT_A, CT_B>(sb, P, g * 16 + w);
    PROF_G(4);
    if (b >= 28) {
      constexpr int KV0 = 36 * CT_B, KV1 = KV0 + 192, NK = 576 - KV1;
      const int lane = threadIdx.x & 31;
      auto draw = [&]() {
        const int j = next_job(sb), ch = j < DM ? j : j - DM - NK;
        if (ch >= 0 && ch < DM && lane < (j < DM ? 2 * CT_C : 32)) asm volatile("prefetch.global.L2 [%0];" :: "l"(P.ssm_k + (size_t)ch * SEQ + lane * 64));
        return j;
      };
      int job = draw();
#pragma unroll 1
      for (int k = KV0 + (b - 28) * 16 + w; b < 32 && k < KV1; k += 64) {
        kv_task(P, k);
        __syncwarp();
        if (lane == 0) flag_add(g_flags + FL_KV);
      }
      warp_flag_wait(g_flags + FL_Y + CT_A * 32, 32);
      warp_flag_wait(g_flags + FL_KV, 192);
      spin_until(rd_clock() + (w >> 2) * DP_V);
#pragma unroll 1
      while (job < DM) { const int nx = draw(); conv_job<CT_B, CT_C>(sb, P, job); job = nx; }
      PROF_G(6);
#pragma unroll 1
      while (job < DM + NK) {
        const int nx = draw();
        kv_task(P, job - DM + KV1);
        __syncwarp();
        if (lane == 0) flag_add(g_flags + FL_KV + 32);
        job = nx;
      }
      warp_flag_wait(g_flags + FL_KV + 32, NK);
#pragma unroll 1
      while (job < 2 * DM + NK) { const int nx = draw(); conv_job<CT_C, 16>(sb, P, job - DM - NK); job = nx; }
      PROF_G(5);
      PROF_END();
      return;
    }
    __syncwarp();
  }
  if (blockIdx.x >= 24) {
    PROF_G(24);
    tail_finisher(sb, P);
    PROF_END();
    asm volatile("griddepcontrol.wait;" ::: "memory");
  } else if (rd_warp() < 12) {
    asm volatile("setmaxnreg.inc.sync.aligned.u32 160;");
    tail_gemm(sb, P);
    PROF_END();
  } else {
    asm volatile("setmaxnreg.dec.sync.aligned.u32 32;");
    tail_service(sb);
    PROF_END();
  }
}

}

extern "C" void kernel_launch(void* const* d_in, const int* in_sizes, int n_in, void* d_out, int out_size) {
  typedef const __nv_bfloat16* bp;
  Params P;
  P.x0 = (bp)d_in[0]; P.ck = (bp)d_in[1]; P.cv = (bp)d_in[2]; P.shift = (bp)d_in[3]; P.ssm_k = (bp)d_in[4]; P.ssm_d = (bp)d_in[5];
  P.mem0 = (bp)d_in[7]; P.wq = (bp)d_in[8]; P.wk = (bp)d_in[9]; P.wv = (bp)d_in[10]; P.wo = (bp)d_in[11];
  P.out = (__nv_bfloat16*)d_out;
  typedef CUresult (*Encode)(CUtensorMap*, CUtensorMapDataType, cuuint32_t, void*, const cuuint64_t*, const cuuint64_t*, const cuuint32_t*, const cuuint32_t*,
                             CUtensorMapInterleave, CUtensorMapSwizzle, CUtensorMapL2promotion, CUtensorMapFloatOOBfill);
  static Encode encode = nullptr;
  if (!encode) {
    cudaDriverEntryPointQueryResult qr;
    cudaGetDriverEntryPoint("cuTensorMapEncodeTiled", (void**)&encode, cudaEnableDefault, &qr);
  }
  const cuuint64_t dims[2] = {DM, 4096}, pitch[1] = {DM * 2};
  const cuuint32_t box[2] = {64, 16}, es[2] = {1, 1};
  encode(&P.tm, CU_TENSOR_MAP_DATA_TYPE_BFLOAT16, 2, d_in[11], dims, pitch, box, es, CU_TENSOR_MAP_INTERLEAVE_NONE,
         CU_TENSOR_MAP_SWIZZLE_128B, CU_TENSOR_MAP_L2_PROMOTION_NONE, CU_TENSOR_MAP_FLOAT_OOB_FILL_NONE);
  void* xc = nullptr;
  cudaGetSymbolAddress(&xc, g_xchg);
  P.memx = (uint4*)(((uintptr_t)xc + 0x1FFFFF) & ~(uintptr_t)0x1FFFFF);
  P.d_x = mkdesc(Q_X, 128, 1024, 0); P.d_wl = mkdesc(Q_WL, 16, 1024, 1);
  P.d_ring = mkdesc(W_RING, 512, 128, 0); P.d_ws = mkdesc(W_WS, 16, 1024, 1);
  cudaFuncSetAttribute(head_kernel, cudaFuncAttributeMaxDynamicSharedMemorySize, SMEM_TOTAL);
  cudaFuncSetAttribute(tail_kernel, cudaFuncAttributeMaxDynamicSharedMemorySize, SMEM_TOTAL);
  head_kernel<<<96, 512, SMEM_TOTAL>>>(P);
  cudaLaunchConfig_t cfg = {};
  cfg.gridDim = dim3(36); cfg.blockDim = dim3(512); cfg.dynamicSmemBytes = SMEM_TOTAL; cfg.stream = 0;
  cudaLaunchAttribute attr[1];
  attr[0].id = cudaLaunchAttributeProgrammaticStreamSerialization;
  attr[0].val.programmaticStreamSerializationAllowed = 1;
  cfg.attrs = attr; cfg.numAttrs = 1;
  cudaLaunchKernelEx(&cfg, tail_kernel, P);
}
```

```cpp
#include <cuda.h>
#include <cuda_runtime.h>
#include <cuda_bf16.h>
#include <stdint.h>

namespace {

constexpr int SEQ = 2048, DM = 576, NSEG = 64;
#define LAG_V 5
#define RV_V 1950
#define R1_V 380
#define R0_V 590
#define V1_V 80
#define V2_V 200
#define Q1_V 150
#define Q2_V 290
#define SWAP_V 1
#define ST0_V 200
#define GX_V 1130
#define RS_V 5
#define CALIB 0
#define RF_V 2350
#define RL_V 2000
#define PA1_V 500
#define PA0_V 700
#define XA_V 1
#define XP_V 160
#define CTB_V 6
#define CTC_V 11
#define DP_V 2000
#define NFV_V 24
#define ST_V 5
#define VG_V 0
#define MG_V 3
#define ST1_V 200
#define GS_V 400
#define KPV_V 16
#define KP1_V 24
#define KP0_V 28
constexpr int LAG = LAG_V;
constexpr int NT = NSEG + LAG;
constexpr int OXRING = 8;
static_assert(LAG >= 3 && LAG < OXRING, "pipeline lag");
constexpr uint32_t D_RED = RV_V;
__host__ __device__ constexpr uint32_t rank_delay(int r) { return r == 2 ? 0 : r ? R1_V : R0_V; }
__host__ __device__ constexpr int tile_of(int r, int i) { return r == 2 ? i : SWAP_V ? (r ? 3 + i + (i >> 1) : 5 + i + (i > 0)) : 6 - 3 * r + i; }
__host__ __device__ constexpr uint32_t tile_delay(int r, int i) { return (i == 0 ? 0 : r == 2 ? (i == 1 ? V1_V : V2_V) : i == 1 ? Q1_V : Q2_V) * 9 / 16; }
constexpr uint32_t D_DUE = RF_V, D_LATE = RL_V;
constexpr uint32_t D_GX = GX_V * 9 / 16;
constexpr int KP_V = KPV_V, KP_1 = KP1_V, KP_0 = KP0_V;
constexpr int KP_MAX = KP_0 > KP_1 ? KP_0 : KP_1;
constexpr uint32_t SB0 = 1024;
constexpr float SM_SCALE = 0.08838834764831845f * 1.4426950408889634f;
constexpr uint32_t SENT = 0x80008000u;
constexpr uint32_t SPIN_LIMIT = 1u << 21;

constexpr int FL_XS = 0;
constexpr int FL_ACC = (NT + 2) * 32;
constexpr int FL_OX = FL_ACC + 128 * 32;
constexpr int FL_SEL = FL_OX + (NT + 1) * 32;
constexpr int FL_Y = FL_SEL + 96 * 4;
constexpr int FL_KV = FL_Y + 512;
constexpr int FL_TOTAL = FL_KV + 128;

__device__ __align__(1024) uint4 g_y[256 * DM];
__device__ __align__(1024) uint4 g_kv[256 * DM];
__device__ __align__(1024) float4 g_acc[2 * 256 * 36 * 32];
__device__ __align__(1024) uint4 g_xs[NT * 4608];
__device__ __align__(1024) uint4 g_ox[OXRING * 512 * 8 * 8];
__device__ __align__(1024) uint4 g_xchg[(256 + 256 + 45) * 512];
__host__ __device__ constexpr uint32_t part_of(int cta) { return (cta < 81 ? 12 + cta * 3 : 13 + cta * 3) * 8192; }
__device__ __align__(1024) uint32_t g_flagsets[2 * FL_TOTAL];
__device__ uint32_t g_epoch;
#define PROF_T(slot) do {} while (0)
#define PROF_END() do {} while (0)
#define PROF_W(cond, slot) do {} while (0)
#define PROF_V(cond, slot, val) do { (void)(val); } while (0)
#define PROF_G(slot) do {} while (0)
#define PROF_OR(slot, val) do {} while (0)
#define PROF_A(idx, val) do { (void)(val); } while (0)
#define PROF_BEGIN() do {} while (0)
#define PROF_MID() do {} while (0)

#define CHINT ""
#define HINT ", 100000"
__device__ __forceinline__ uint32_t pack_bf16(float lo, float hi) {
  uint32_t r; asm("cvt.rn.bf16x2.f32 %0, %1, %2;" : "=r"(r) : "f"(hi), "f"(lo)); return r;
}
__device__ __forceinline__ float bf_lo(uint32_t w) { return __uint_as_float(__byte_perm(w, 0, 0x1044)); }
__device__ __forceinline__ float bf_hi(uint32_t w) { return __uint_as_float(w & 0xFFFF0000u); }
__device__ __forceinline__ uint32_t mapa(uint32_t a, uint32_t r) {
  uint32_t o; asm("mapa.shared::cluster.u32 %0, %1, %2;" : "=r"(o) : "r"(a), "r"(r)); return o;
}
__device__ __forceinline__ void mbar_init(uint32_t bar, uint32_t cnt) {
  asm volatile("mbarrier.init.shared::cta.b64 [%0], %1;" :: "r"(bar), "r"(cnt) : "memory");
}
__device__ __forceinline__ void mbar_expect(uint32_t bar, uint32_t bytes) {
  asm volatile("mbarrier.arrive.expect_tx.shared::cta.b64 _, [%0], %1;" :: "r"(bar), "r"(bytes) : "memory");
}
__device__ __forceinline__ void mbar_arrive(uint32_t bar) {
  asm volatile("mbarrier.arrive.shared::cta.b64 _, [%0];" :: "r"(bar) : "memory");
}
__device__ __forceinline__ void mbar_arrive_if0(uint32_t sel, uint32_t bar) {
  asm volatile("{\n.reg .pred p;\nsetp.eq.u32 p, %1, 0;\n@p mbarrier.arrive.shared::cta.b64 _, [%0];\n}" :: "r"(bar), "r"(sel) : "memory");
}
__device__ __forceinline__ void mbar_expect_if0(uint32_t sel, uint32_t bar, uint32_t bytes) {
  asm volatile("{\n.reg .pred p;\nsetp.eq.u32 p, %1, 0;\n@p mbarrier.arrive.expect_tx.shared::cta.b64 _, [%0], %2;\n}" :: "r"(bar), "r"(sel), "r"(bytes) : "memory");
}
__device__ __forceinline__ void mbar_rarrive_if0(uint32_t sel, uint32_t bar) {
  asm volatile("{\n.reg .pred p;\nsetp.eq.u32 p, %1, 0;\n@p mbarrier.arrive.relaxed.cluster.shared::cluster.b64 _, [%0];\n}" :: "r"(bar), "r"(sel) : "memory");
}
__device__ __forceinline__ void mbar_wait_lim(uint32_t bar, uint32_t par) {
  asm volatile(
    "{\n.reg .pred p;\n.reg .u32 c;\nmov.u32 c, 0;\n"
    "W_%=:\n"
    "mbarrier.try_wait.parity.shared::cta.b64 p, [%0], %1;\n"
    "@p bra D_%=;\n"
    "add.u32 c, c, 1;\nsetp.lt.u32 p, c, %2;\n@p bra W_%=;\ntrap;\n"
    "D_%=:\n}\n" :: "r"(bar), "r"(par), "n"(SPIN_LIMIT) : "memory");
}
__device__ __forceinline__ void mbar_wait(uint32_t bar, uint32_t par) {
  asm volatile(
    "{\n.reg .pred p;\n"
    "W_%=:\n"
    "mbarrier.try_wait.parity.shared::cta.b64 p, [%0], %1" HINT ";\n"
    "@!p bra W_%=;\n}\n" :: "r"(bar), "r"(par) : "memory");
}
__device__ __forceinline__ void mbar_spin(uint32_t bar, uint32_t par) {
  asm volatile("{\n.reg .pred p;\nW_%=:\nmbarrier.try_wait.parity.shared::cta.b64 p, [%0], %1;\n@!p bra W_%=;\n}\n" :: "r"(bar), "r"(par) : "memory");
}
__device__ __forceinline__ uint32_t mbar_test(uint32_t bar, uint32_t par) {
  uint32_t r;
  asm volatile("{\n.reg .pred p;\nmbarrier.test_wait.parity.shared::cta.b64 p, [%1], %2;\nselp.u32 %0, 1, 0, p;\n}" : "=r"(r) : "r"(bar), "r"(par) : "memory");
  return __shfl_sync(0xffffffffu, r, 0);
}
__device__ __forceinline__ void mbar_wait_if(uint32_t& done, uint32_t test, uint32_t bar, uint32_t par, bool force) {
  asm volatile(
    "{\n.reg .pred p, q;\nsetp.ne.u32 p, %0, 0;\n@p bra.uni D_%=;\nsetp.ne.u32 q, %4, 0;\n"
    "mbarrier.test_wait.parity.shared::cta.b64 p, [%1], %3;\n"
    "or.pred p, p, q;\n@!p bra D_%=;\n"
    "W_%=:\n"
    "mbarrier.try_wait.parity.shared::cta.b64 p, [%2], %3, 100000;\n"
    "@!p bra W_%=;\nmov.u32 %0, 1;\nD_%=:\n}\n" : "+r"(done) : "r"(test), "r"(bar), "r"(par), "r"((uint32_t)force) : "memory");
}
template <int ID, int N> __device__ __forceinline__ void bar_sync() { asm volatile("bar.sync %0, %1;" :: "n"(ID), "n"(N) : "memory"); }
template <int ID, int N> __device__ __forceinline__ void bar_arrive() { asm volatile("bar.arrive %0, %1;" :: "n"(ID), "n"(N) : "memory"); }
__device__ __forceinline__ void bar_sync_r(int id, int n) { asm volatile("bar.sync %0, %1;" :: "r"(id), "r"(n) : "memory"); }
__device__ __forceinline__ void bar_arrive_r(int id, int n) { asm volatile("bar.arrive %0, %1;" :: "r"(id), "r"(n) : "memory"); }
__device__ __forceinline__ uint32_t pin(uint32_t x) { return __shfl_sync(0xffffffffu, x, threadIdx.x); }
__device__ __forceinline__ void cluster_sync() {
  asm volatile("barrier.cluster.arrive.aligned;\nbarrier.cluster.wait.aligned;" ::: "memory");
}
__device__ __forceinline__ void fence_async_smem() { asm volatile("fence.proxy.async.shared::cta;" ::: "memory"); }
__device__ __forceinline__ void fence_async_global() { asm volatile("fence.proxy.async.global;" ::: "memory"); }
__device__ __forceinline__ uint4 ld_poll(const uint4* p) {
  uint4 v;
  asm volatile("ld.relaxed.gpu.global.v4.u32 {%0,%1,%2,%3}, [%4];" : "=r"(v.x), "=r"(v.y), "=r"(v.z), "=r"(v.w) : "l"(p) : "memory");
  return v;
}
__device__ __forceinline__ uint32_t rd_clock() { uint64_t c; asm volatile("mov.u64 %0, %%clock64;" : "=l"(c) :: "memory"); return (uint32_t)c; }
__device__ __forceinline__ void spin_until(uint32_t when) {
  asm volatile("{\n.reg .pred p;\n.reg .b64 c;\n.reg .s32 lo;\nS_%=:\nmov.u64 c, %%clock64;\ncvt.u32.u64 lo, c;\nsub.s32 lo, lo, %0;\n"
               "setp.lt.s32 p, lo, 0;\n@p bra.uni S_%=;\n}" :: "r"(when) : "memory");
}
__device__ __forceinline__ uint32_t near_page(uint4* pair, uint32_t mark) {
  uint32_t best0 = ~0u, best1 = ~0u;
  const int lane = threadIdx.x & 31;
#pragma unroll 1
  for (int r = 0; r < 8; r++) {
    if (r >= 4 && !(r & 1) && __all_sync(0xffffffffu, max(best0, best1) - min(best0, best1) > 110u && min(best0, best1) < 420u)) break;
    uint32_t t0, t1, v;
    asm volatile("mov.u32 %0, %%clock;" : "=r"(t0) :: "memory");
    asm volatile("{\n.reg .pred p;\nsetp.eq.u32 p, %2, 0;\nmov.u32 %0, 0;\n@p atom.relaxed.gpu.global.exch.b32 %0, [%1], %3;\n}"
                 : "=&r"(v) : "l"(pair + (r & 1) * 256), "r"(lane), "r"(mark) : "memory");
    asm volatile("{\n.reg .pred p;\nsetp.ne.u32 p, %1, 0x9E3779B9;\nmov.u32 %0, %2;\n@p mov.u32 %0, %%clock;\n}" : "=&r"(t1) : "r"(v), "r"(t0 - 1) : "memory");
    if (r & 1) best1 = min(best1, t1 - t0); else best0 = min(best0, t1 - t0);
  }
  return best1 < best0;
}
__device__ __forceinline__ void st_gpu4(uint4* p, uint32_t a, uint32_t b, uint32_t c, uint32_t d) {
  asm volatile("st.relaxed.gpu.global.v4.u32 [%0], {%1,%2,%3,%4};" :: "l"(p), "r"(a), "r"(b), "r"(c), "r"(d) : "memory");
}
__device__ __forceinline__ void st_gpu1(uint32_t* p, uint32_t a) {
  asm volatile("st.relaxed.gpu.global.u32 [%0], %1;" :: "l"(p), "r"(a) : "memory");
}
__device__ __forceinline__ void st_gpu1_if(bool c, uint32_t* p, uint32_t a) {
  asm volatile("{\n.reg .pred p;\nsetp.ne.u32 p, %2, 0;\n@p st.relaxed.gpu.global.u32 [%0], %1;\n}" :: "l"(p), "r"(a), "r"((uint32_t)c) : "memory");
}
__device__ __forceinline__ void warp_flag_wait(const uint32_t* p, uint32_t target) {
  uint32_t v, n = 0;
  do {
    asm volatile("ld.relaxed.gpu.global.u32 %0, [%1];" : "=r"(v) : "l"(p) : "memory");
    if (++n > SPIN_LIMIT) __trap();
  } while (__any_sync(0xffffffffu, v < target));
}
__device__ __forceinline__ void flag_add(uint32_t* p) {
  asm volatile("red.release.gpu.global.add.u32 [%0], 1;" :: "l"(p) : "memory");
}
__device__ __forceinline__ void bulk_g2s(uint32_t dst, const void* src, uint32_t bytes, uint32_t bar) {
  asm volatile("cp.async.bulk.shared::cluster.global.mbarrier::complete_tx::bytes [%0], [%1], %2, [%3];"
               :: "r"(dst), "l"(src), "r"(bytes), "r"(bar) : "memory");
}
__device__ __forceinline__ void bulk_g2s_mc(uint32_t dst, const void* src, uint32_t bytes, uint32_t bar, uint16_t mask) {
  asm volatile("cp.async.bulk.shared::cluster.global.mbarrier::complete_tx::bytes.multicast::cluster [%0], [%1], %2, [%3], %4;"
               :: "r"(dst), "l"(src), "r"(bytes), "r"(bar), "h"(mask) : "memory");
}
__device__ __forceinline__ void tma_box(uint32_t dst, const CUtensorMap* tm, int col, int row, uint32_t bar) {
  asm volatile("cp.async.bulk.tensor.2d.shared::cluster.global.mbarrier::complete_tx::bytes [%0], [%1, {%2, %3}], [%4];"
               :: "r"(dst), "l"(tm), "r"(col), "r"(row), "r"(bar) : "memory");
}
__device__ __forceinline__ void bulk_s2s(uint32_t dst, uint32_t src, uint32_t bytes, uint32_t bar) {
  asm volatile("cp.async.bulk.shared::cluster.shared::cta.mbarrier::complete_tx::bytes [%0], [%1], %2, [%3];"
               :: "r"(dst), "r"(src), "r"(bytes), "r"(bar) : "memory");
}
__device__ __forceinline__ void bulk_s2g(void* dst, uint32_t src, uint32_t bytes) {
  asm volatile("cp.async.bulk.global.shared::cta.bulk_group [%0], [%1], %2;" :: "l"(dst), "r"(src), "r"(bytes) : "memory");
}
__device__ __forceinline__ void bulk_commit_wait() {
  asm volatile("cp.async.bulk.commit_group;\ncp.async.bulk.wait_group 0;" ::: "memory");
}
__device__ __forceinline__ bool elect_one() {
  uint32_t p; asm volatile("{\n.reg .pred p;\nelect.sync _|p, 0xffffffff;\nselp.u32 %0, 1, 0, p;\n}" : "=r"(p)); return p;
}
__device__ __forceinline__ void ldsm4(uint32_t& r0, uint32_t& r1, uint32_t& r2, uint32_t& r3, uint32_t a) {
  asm volatile("ldmatrix.sync.aligned.m8n8.x4.shared.b16 {%0,%1,%2,%3}, [%4];" : "=r"(r0), "=r"(r1), "=r"(r2), "=r"(r3) : "r"(a) : "memory");
}
__device__ __forceinline__ void ldsm4t(uint32_t& r0, uint32_t& r1, uint32_t& r2, uint32_t& r3, uint32_t a) {
  asm volatile("ldmatrix.sync.aligned.m8n8.x4.trans.shared.b16 {%0,%1,%2,%3}, [%4];" : "=r"(r0), "=r"(r1), "=r"(r2), "=r"(r3) : "r"(a) : "memory");
}
__device__ __forceinline__ void stsm4(uint32_t a, uint32_t r0, uint32_t r1, uint32_t r2, uint32_t r3) {
  asm volatile("stmatrix.sync.aligned.m8n8.x4.shared.b16 [%0], {%1,%2,%3,%4};" :: "r"(a), "r"(r0), "r"(r1), "r"(r2), "r"(r3) : "memory");
}
__device__ __forceinline__ void stsm2(uint32_t a, uint32_t r0, uint32_t r1) {
  asm volatile("stmatrix.sync.aligned.m8n8.x2.shared.b16 [%0], {%1,%2};" :: "r"(a), "r"(r0), "r"(r1) : "memory");
}
__device__ __forceinline__ void stsm4t(uint32_t a, uint32_t r0, uint32_t r1, uint32_t r2, uint32_t r3) {
  asm volatile("stmatrix.sync.aligned.m8n8.x4.trans.shared.b16 [%0], {%1,%2,%3,%4};" :: "r"(a), "r"(r0), "r"(r1), "r"(r2), "r"(r3) : "memory");
}
__device__ __forceinline__ float4 lds4f(uint32_t a) {
  float4 v; asm volatile("ld.shared.v4.f32 {%0,%1,%2,%3}, [%4];" : "=f"(v.x), "=f"(v.y), "=f"(v.z), "=f"(v.w) : "r"(a) : "memory"); return v;
}
__device__ __forceinline__ uint4 lds4(uint32_t a) {
  uint4 v; asm volatile("ld.shared.v4.u32 {%0,%1,%2,%3}, [%4];" : "=r"(v.x), "=r"(v.y), "=r"(v.z), "=r"(v.w) : "r"(a) : "memory"); return v;
}
__device__ __forceinline__ uint32_t lds1(uint32_t a) {
  uint32_t v; asm volatile("ld.shared.u32 %0, [%1];" : "=r"(v) : "r"(a) : "memory"); return v;
}
__device__ __forceinline__ void sts4(uint32_t a, uint4 v) {
  asm volatile("st.shared.v4.u32 [%0], {%1,%2,%3,%4};" :: "r"(a), "r"(v.x), "r"(v.y), "r"(v.z), "r"(v.w) : "memory");
}
__device__ __forceinline__ void sts1(uint32_t a, uint32_t v) { asm volatile("st.shared.u32 [%0], %1;" :: "r"(a), "r"(v) : "memory"); }
__device__ __forceinline__ void mma16816(float (&d)[4], uint32_t a0, uint32_t a1, uint32_t a2, uint32_t a3, uint32_t b0, uint32_t b1) {
  asm volatile("mma.sync.aligned.m16n8k16.row.col.f32.bf16.bf16.f32 {%0,%1,%2,%3}, {%4,%5,%6,%7}, {%8,%9}, {%0,%1,%2,%3};"
               : "+f"(d[0]), "+f"(d[1]), "+f"(d[2]), "+f"(d[3]) : "r"(a0), "r"(a1), "r"(a2), "r"(a3), "r"(b0), "r"(b1));
}
__device__ __forceinline__ void mma1688(float (&d)[4], uint32_t a0, uint32_t a1, uint32_t b0) {
  asm volatile("mma.sync.aligned.m16n8k8.row.col.f32.bf16.bf16.f32 {%0,%1,%2,%3}, {%4,%5}, {%6}, {%0,%1,%2,%3};"
               : "+f"(d[0]), "+f"(d[1]), "+f"(d[2]), "+f"(d[3]) : "r"(a0), "r"(a1), "r"(b0));
}
__device__ __forceinline__ float rcp(float x) { float r; asm("rcp.approx.ftz.f32 %0, %1;" : "=f"(r) : "f"(x)); return r; }
__device__ __forceinline__ float sqr(float x) { float r; asm("sqrt.approx.f32 %0, %1;" : "=f"(r) : "f"(x)); return r; }
__device__ __forceinline__ float ex2(float x) { float r; asm("ex2.approx.ftz.f32 %0, %1;" : "=f"(r) : "f"(x)); return r; }

__device__ __forceinline__ uint32_t bf2_op(uint32_t a, uint32_t b, uint32_t c) {
  uint32_t r; asm("fma.rn.bf16x2 %0, %1, %2, %3;" : "=r"(r) : "r"(a), "r"(b), "r"(c)); return r;
}
__device__ __forceinline__ uint32_t bf2_mul(uint32_t a, uint32_t b) {
  uint32_t r; asm("mul.rn.bf16x2 %0, %1, %2;" : "=r"(r) : "r"(a), "r"(b)); return r;
}
__device__ __forceinline__ uint32_t bf2_add(uint32_t a, uint32_t b) {
  uint32_t r; asm("add.rn.bf16x2 %0, %1, %2;" : "=r"(r) : "r"(a), "r"(b)); return r;
}

__host__ __device__ constexpr uint64_t mkdesc(uint32_t off, uint32_t lbo, uint32_t sbo, uint32_t sw) {
  return (uint64_t)((SB0 + off) >> 4) | ((uint64_t)(lbo >> 4) << 16) | ((uint64_t)(sbo >> 4) << 32) | ((uint64_t)sw << 62);
}
__device__ __forceinline__ void wg_fence() { asm volatile("wgmma.fence.sync.aligned;" ::: "memory"); }
__device__ __forceinline__ void wg_commit() { asm volatile("wgmma.commit_group.sync.aligned;" ::: "memory"); }
template <int N> __device__ __forceinline__ void wg_wait() { asm volatile("wgmma.wait_group.sync.aligned %0;" :: "n"(N) : "memory"); }
template <int N> __device__ __forceinline__ void reg_fence(float (&d)[N]) {
#pragma unroll
  for (int i = 0; i < N; i++) asm volatile("" : "+f"(d[i]) :: "memory");
}

#define F4(d, o) "+f"(d[o]), "+f"(d[o + 1]), "+f"(d[o + 2]), "+f"(d[o + 3])
template <int SC, int TB> __device__ __forceinline__ void wg_rs(float (&d)[8], const uint32_t* a, uint64_t db, int ob) {
  asm volatile("{\n.reg .pred p;\n.reg .b64 b;\nsetp.ne.b32 p, %13, 0;\nadd.s64 b, %12, %15;\n"
    "wgmma.mma_async.sync.aligned.m64n16k16.f32.bf16.bf16 {%0,%1,%2,%3,%4,%5,%6,%7}, {%8,%9,%10,%11}, b, p, 1, 1, %14;\n}\n"
    : F4(d, 0), F4(d, 4) : "r"(a[0]), "r"(a[1]), "r"(a[2]), "r"(a[3]), "l"(db), "n"(SC), "n"(TB), "l"((uint64_t)ob));
}
template <int SC, int TB> __device__ __forceinline__ void wg_rs(float (&d)[12], const uint32_t* a, uint64_t db, int ob) {
  asm volatile("{\n.reg .pred p;\n.reg .b64 b;\nsetp.ne.b32 p, %17, 0;\nadd.s64 b, %16, %19;\n"
    "wgmma.mma_async.sync.aligned.m64n24k16.f32.bf16.bf16 {%0,%1,%2,%3,%4,%5,%6,%7,%8,%9,%10,%11}, {%12,%13,%14,%15}, b, p, 1, 1, %18;\n}\n"
    : F4(d, 0), F4(d, 4), F4(d, 8) : "r"(a[0]), "r"(a[1]), "r"(a[2]), "r"(a[3]), "l"(db), "n"(SC), "n"(TB), "l"((uint64_t)ob));
}
template <int SC, int TB> __device__ __forceinline__ void wg_rs(float (&d)[16], const uint32_t* a, uint64_t db, int ob) {
  asm volatile("{\n.reg .pred p;\n.reg .b64 b;\nsetp.ne.b32 p, %21, 0;\nadd.s64 b, %20, %23;\n"
    "wgmma.mma_async.sync.aligned.m64n32k16.f32.bf16.bf16 {%0,%1,%2,%3,%4,%5,%6,%7,%8,%9,%10,%11,%12,%13,%14,%15}, {%16,%17,%18,%19}, b, p, 1, 1, %22;\n}\n"
    : F4(d, 0), F4(d, 4), F4(d, 8), F4(d, 12) : "r"(a[0]), "r"(a[1]), "r"(a[2]), "r"(a[3]), "l"(db), "n"(SC), "n"(TB), "l"((uint64_t)ob));
}
template <int SC, int TB> __device__ __forceinline__ void wg_rs(float (&d)[28], const uint32_t* a, uint64_t db, int ob) {
  asm volatile("{\n.reg .pred p;\n.reg .b64 b;\nsetp.ne.b32 p, %33, 0;\nadd.s64 b, %32, %35;\n"
    "wgmma.mma_async.sync.aligned.m64n56k16.f32.bf16.bf16 {%0,%1,%2,%3,%4,%5,%6,%7,%8,%9,%10,%11,%12,%13,%14,%15,%16,%17,%18,%19,%20,%21,%22,%23,%24,%25,%26,%27}, {%28,%29,%30,%31}, b, p, 1, 1, %34;\n}\n"
    : F4(d, 0), F4(d, 4), F4(d, 8), F4(d, 12), F4(d, 16), F4(d, 20), F4(d, 24) : "r"(a[0]), "r"(a[1]), "r"(a[2]), "r"(a[3]), "l"(db), "n"(SC), "n"(TB), "l"((uint64_t)ob));
}
template <int SC, int TB> __device__ __forceinline__ void wg_ss(float (&d)[8], uint64_t da, int oa, uint64_t db, int ob) {
  asm volatile("{\n.reg .pred p;\n.reg .b64 a, b;\nsetp.ne.b32 p, %10, 0;\nadd.s64 a, %8, %12;\nadd.s64 b, %9, %13;\n"
    "wgmma.mma_async.sync.aligned.m64n16k16.f32.bf16.bf16 {%0,%1,%2,%3,%4,%5,%6,%7}, a, b, p, 1, 1, 1, %11;\n}\n"
    : F4(d, 0), F4(d, 4) : "l"(da), "l"(db), "n"(SC), "n"(TB), "l"((uint64_t)oa), "l"((uint64_t)ob));
}
template <int SC, int TB> __device__ __forceinline__ void wg_ss(float (&d)[12], uint64_t da, int oa, uint64_t db, int ob) {
  asm volatile("{\n.reg .pred p;\n.reg .b64 a, b;\nsetp.ne.b32 p, %14, 0;\nadd.s64 a, %12, %16;\nadd.s64 b, %13, %17;\n"
    "wgmma.mma_async.sync.aligned.m64n24k16.f32.bf16.bf16 {%0,%1,%2,%3,%4,%5,%6,%7,%8,%9,%10,%11}, a, b, p, 1, 1, 1, %15;\n}\n"
    : F4(d, 0), F4(d, 4), F4(d, 8) : "l"(da), "l"(db), "n"(SC), "n"(TB), "l"((uint64_t)oa), "l"((uint64_t)ob));
}
template <int SC, int TB> __device__ __forceinline__ void wg_ss(float (&d)[16], uint64_t da, int oa, uint64_t db, int ob) {
  asm volatile("{\n.reg .pred p;\n.reg .b64 a, b;\nsetp.ne.b32 p, %18, 0;\nadd.s64 a, %16, %20;\nadd.s64 b, %17, %21;\n"
    "wgmma.mma_async.sync.aligned.m64n32k16.f32.bf16.bf16 {%0,%1,%2,%3,%4,%5,%6,%7,%8,%9,%10,%11,%12,%13,%14,%15}, a, b, p, 1, 1, 1, %19;\n}\n"
    : F4(d, 0), F4(d, 4), F4(d, 8), F4(d, 12) : "l"(da), "l"(db), "n"(SC), "n"(TB), "l"((uint64_t)oa), "l"((uint64_t)ob));
}
template <int SC, int TB> __device__ __forceinline__ void wg_ss(float (&d)[20], uint64_t da, int oa, uint64_t db, int ob) {
  asm volatile("{\n.reg .pred p;\n.reg .b64 a, b;\nsetp.ne.b32 p, %22, 0;\nadd.s64 a, %20, %24;\nadd.s64 b, %21, %25;\n"
    "wgmma.mma_async.sync.aligned.m64n40k16.f32.bf16.bf16 {%0,%1,%2,%3,%4,%5,%6,%7,%8,%9,%10,%11,%12,%13,%14,%15,%16,%17,%18,%19}, a, b, p, 1, 1, 1, %23;\n}\n"
    : F4(d, 0), F4(d, 4), F4(d, 8), F4(d, 12), F4(d, 16) : "l"(da), "l"(db), "n"(SC), "n"(TB), "l"((uint64_t)oa), "l"((uint64_t)ob));
}
template <int SC, int TB> __device__ __forceinline__ void wg_ss(float (&d)[28], uint64_t da, int oa, uint64_t db, int ob) {
  asm volatile("{\n.reg .pred p;\n.reg .b64 a, b;\nsetp.ne.b32 p, %30, 0;\nadd.s64 a, %28, %32;\nadd.s64 b, %29, %33;\n"
    "wgmma.mma_async.sync.aligned.m64n56k16.f32.bf16.bf16 {%0,%1,%2,%3,%4,%5,%6,%7,%8,%9,%10,%11,%12,%13,%14,%15,%16,%17,%18,%19,%20,%21,%22,%23,%24,%25,%26,%27}, a, b, p, 1, 1, 1, %31;\n}\n"
    : F4(d, 0), F4(d, 4), F4(d, 8), F4(d, 12), F4(d, 16), F4(d, 20), F4(d, 24) : "l"(da), "l"(db), "n"(SC), "n"(TB), "l"((uint64_t)oa), "l"((uint64_t)ob));
}

template <int SC> __device__ __forceinline__ void wg_sskk(float (&d)[16], uint64_t da, int oa, uint64_t db, int ob) {
  asm volatile("{\n.reg .pred p;\n.reg .b64 a, b;\nsetp.ne.b32 p, %18, 0;\nadd.s64 a, %16, %19;\nadd.s64 b, %17, %20;\n"
    "wgmma.mma_async.sync.aligned.m64n32k16.f32.bf16.bf16 {%0,%1,%2,%3,%4,%5,%6,%7,%8,%9,%10,%11,%12,%13,%14,%15}, a, b, p, 1, 1, 0, 0;\n}\n"
    : F4(d, 0), F4(d, 4), F4(d, 8), F4(d, 12) : "l"(da), "l"(db), "n"(SC), "l"((uint64_t)oa), "l"((uint64_t)ob));
}

template <int NK> __device__ __forceinline__ void load_afrags(uint32_t* a, uint32_t tile, int w, int lane) {
  int i = lane >> 3, r = lane & 7;
  uint32_t base = tile + ((i >> 1) * 8 + r) * 128 + (((2 * w + (i & 1)) ^ r) << 4);
#pragma unroll
  for (int kk = 0; kk < NK; kk++) ldsm4t(a[4 * kk], a[4 * kk + 1], a[4 * kk + 2], a[4 * kk + 3], base + kk * 2048);
}

constexpr uint32_t Q_WL = 0;
constexpr uint32_t Q_WO = 24576;
constexpr uint32_t Q_OX = Q_WO;
constexpr uint32_t Q_X = 73728;
constexpr uint32_t Q_CS = 10240;
constexpr uint32_t Q_STG = 165888;
constexpr uint32_t Q_OB = 190464;
constexpr uint32_t Q_SIN = 194560;
constexpr uint32_t Q_PX = 204800;
constexpr uint32_t Q_SOUT = Q_PX;
constexpr int Q_KR = 30;
constexpr uint32_t BARS = 228352;
constexpr uint32_t B_CP = BARS;
constexpr uint32_t B_OK = BARS + 408;
constexpr uint32_t B_G0 = BARS + 272;
constexpr uint32_t B_XF = BARS + 72;
constexpr uint32_t B_E = BARS + 224;
constexpr uint32_t B_SM = BARS + 160;
constexpr uint32_t B_O = BARS + 168;
constexpr uint32_t B_P = BARS + 176;
constexpr uint32_t B_OXREADY = BARS + 192;
constexpr uint32_t B_OXFREE = BARS + 200;
constexpr uint32_t B_REF = BARS + 208;
constexpr uint32_t B_AN = BARS + 264;
constexpr uint32_t B_PZ = BARS + 256;
constexpr uint32_t B_RES = BARS + 216;
constexpr uint32_t Q_REF = BARS + 288;
constexpr uint32_t Q_SEL = BARS + 304;
constexpr uint32_t Q_M0 = BARS + 384;
constexpr uint32_t Q_SET = BARS + 360;
constexpr uint32_t SM_BYTES = 4 * 1024, SX_BYTES = 2560, PX_BYTES = 2 * 14 * 128;
constexpr int W_KR = 29;
constexpr uint32_t W_RING = 0;
constexpr uint32_t W_WS = 196608;
constexpr uint32_t W_FT = 0;
constexpr uint32_t W_FO = 18688;
constexpr uint32_t W_Z = 30720;
constexpr uint32_t W_RS = 49152;
constexpr uint32_t W_ST = 28672;
constexpr int CT_A = 2, CT_B = CTB_V, CT_C = CTC_V;
static_assert(36 * CT_C <= 36 * CT_B + 192, "kv stages");
constexpr uint32_t C_U = 256 + 4096;
constexpr uint32_t C_CH = C_U + 64 + 8192 + 96;
constexpr uint32_t B_FULL = BARS;
constexpr uint32_t B_EMPTY = BARS + 128;
constexpr uint32_t B_FT = BARS + 160;
constexpr uint32_t B_RF = BARS + 176;
constexpr uint32_t B_WT = BARS + 248;
constexpr uint32_t W_K1 = BARS + 240;
constexpr uint32_t SMEM_TOTAL = BARS + 896;

struct Params {
  CUtensorMap tm;
  const __nv_bfloat16 *x0, *wq, *wk, *wv, *wo, *mem0, *ck, *cv, *shift, *ssm_k, *ssm_d;
  __nv_bfloat16* out;
  uint4* memx;
  uint64_t d_x, d_wl, d_ring, d_ws;
};

constexpr uint64_t D_QK = mkdesc(Q_STG, 768, 128, 0), D_WO = mkdesc(Q_WO, 16, 1024, 1), D_OB = mkdesc(Q_OB, 128, 2048, 0), D_PX = mkdesc(Q_PX, 128, 768, 0);
constexpr uint64_t D_V = mkdesc(Q_STG, 128, 768, 0);

#define g_flags (g_flagsets + lds1(sb + Q_SET))

__device__ __forceinline__ int rd_cid() { uint32_t v; asm volatile("mov.u32 %0, %%clusterid.x;" : "=r"(v)); return v; }
__device__ __forceinline__ int rd_rank() { uint32_t v; asm volatile("mov.u32 %0, %%cluster_ctarank;" : "=r"(v)); return v; }
__device__ __forceinline__ int rd_lane() { uint32_t v; asm volatile("mov.u32 %0, %%laneid;" : "=r"(v)); return v; }
__device__ __forceinline__ int rd_warp() { uint32_t v; asm volatile("mov.u32 %0, %%tid.x;" : "=r"(v)); return __shfl_sync(0xffffffffu, v >> 5, 0); }

template <int NA>
__device__ __forceinline__ void proj_step(float (&acc)[NA], const uint32_t* a, uint64_t db, uint64_t dwl, int k) {
  const int ob = (k >> 2) * (Q_CS / 16) + (k & 3) * 16;
  if (k == 0) wg_rs<0, 1>(acc, a, db, ob);
  else if (k % 6 != 5) wg_rs<1, 1>(acc, a + 4 * (k - k / 6), db, ob);
  else wg_ss<1, 1>(acc, dwl, 128 * (k / 6), db, ob);
}
__device__ __forceinline__ void stage_groups(uint32_t stl, const uint32_t (&pk)[14]) {
#pragma unroll
  for (int h = 0; h < 2; h++) {
    stsm4(stl + h * 768 + 256, pk[h], pk[2 + h], pk[4 + h], 0);
    stsm4(stl + h * 768 + 6144 + 128, pk[6 + h], pk[8 + h], pk[10 + h], pk[12 + h]);
  }
}
__device__ __forceinline__ void head_main(uint32_t sb, const Params& P) {
  const int lane = threadIdx.x & 31, warp = rd_warp(), w = warp & 3, wg = warp >> 2, rank = rd_rank();
  uint32_t a[4 * Q_KR];
  {
    const int tid = threadIdx.x & 127;
    const __nv_bfloat16* src = (rank == 2 ? P.wv + wg * 64 : (wg ? P.wk : P.wq) + rank * 64) + rd_cid() * 128 + (size_t)(tid >> 3) * 4096 + (tid & 7) * 8;
    const uint32_t so = (tid >> 3) * 128 + (((tid & 7) ^ ((tid >> 3) & 7)) << 4), st = sb + Q_X + wg * (Q_KR * 2048);
    uint4 v[36];
#pragma unroll
    for (int k = 0; k < 36; k++) v[k] = __ldg((const uint4*)(src + (size_t)k * 65536));
#pragma unroll
    for (int k = 0; k < 36; k++) sts4(so + (k % 6 == 5 ? sb + Q_WL + wg * 12288 + (k / 6) * 2048 : st + (k - k / 6) * 2048), v[k]);
    bar_sync_r(9 + wg, wg ? 128 : 224);
    PROF_G(7);
    load_afrags<Q_KR>(a, st, w, lane);
    fence_async_smem();
    bar_arrive<11, 384>();
  }
  cluster_sync();
  PROF_G(8);
  const uint64_t dwl = P.d_wl + wg * 768, dq = D_QK + wg * 384;
  const uint32_t stg = sb + Q_STG + wg * 12288 + 2 * w * 768;
  const uint32_t stm = pin(stg + (lane >> 4) * 6144 + ((lane >> 3) & 1) * 768 + (lane & 7) * 16), stl = pin(stg + lane * 16);
  const uint32_t rel = mapa(sb + B_E, 0), rev = mapa(sb + B_E, 2), sel = pin(threadIdx.x & 127), arm = pin(threadIdx.x - 128 > 8), xfa = pin(sb + B_XF + 8 * lane);
  const uint32_t sx = sb + (wg == rank ? Q_SIN + rank * 4096 : Q_SOUT + 2048), s0 = w ? sx + (2 * w - 1) * 512 : sb + Q_SOUT + wg * 1024, s1 = sx + 2 * w * 512;
  const uint32_t sd0 = pin(s0 + lane * 16), sd1 = pin(s1 + lane * 16), sr = sb + Q_SIN + rank * 4096;
  const int kp = rank == 2 ? KP_V : rank ? KP_1 : KP_0;
  const uint32_t selq = pin(sel | rank >> 1);
    const uint32_t pz = sb + (rank == 2 ? B_SM : B_PZ);
  uint32_t pk[14] = {};
#pragma unroll 1
  for (int t = 0;; t++) {
    const uint32_t par = t & 1;
    uint32_t paused = 0;
    if (t == 0) {
      mbar_wait(sb + B_XF, 0);
    } else {
      float m[12];
#pragma unroll
      for (int c = 0; c < 9; c++) {
        mbar_spin(sb + B_OK + 8 * c, par ^ 1);
        if (c == 0 || c == 3 || c == 8) PROF_W(warp == 0, c == 0 ? 0 : c == 3 ? 1 : 3);
        if (c == 8) mbar_rarrive_if0(selq, rev + 24);
        wg_fence();
#pragma unroll
        for (int k = 4 * c; k < 4 * c + 4; k++) proj_step(m, a, P.d_x, dwl, k);
        if (c == 0) { mbar_expect_if0(arm, xfa, 7168); mbar_rarrive_if0(sel | (rank ^ 2), rel); }
        if (c == XA_V) mbar_rarrive_if0(selq, rel);
        if (c == MG_V) mbar_rarrive_if0(sel, rev);
        if (c == ST_V && rank == 2) {
          if (t > 1) bar_sync<3, 384>();
          stage_groups(stl, pk);
        }
      }
      wg_commit();
      if (rank == 2 && t < NT) { mbar_wait(sb + B_XF, par); paused = mbar_test(pz, par ^ 1); }
      wg_wait<0>();
      reg_fence(m);
      PROF_W(warp == 0, 2);
      stsm4(stm, pack_bf16(m[0], m[1]), pack_bf16(m[2], m[3]), pack_bf16(m[4], m[5]), pack_bf16(m[6], m[7]));
      stsm2(stm + 128, pack_bf16(m[8], m[9]), pack_bf16(m[10], m[11]));
      if (rank == 2) {
        bar_arrive<1, 384>();
        mbar_rarrive_if0(sel, rel + 16);
        if (t == NT) break;
        if (paused) mbar_wait(sb + B_RES, par ^ 1);
      } else {
        float s[20];
        bar_sync<1, 256>();
        fence_async_smem();
        wg_fence();
        wg_ss<0, 1>(s, dq, 0, dq, 768);
#pragma unroll
        for (int i = 1; i < 4; i++) wg_ss<1, 1>(s, dq, 96 * i, dq, 768 + 96 * i);
        wg_commit();
        mbar_rarrive_if0(sel ^ 96, rel + 16);
        if (t < NT) mbar_wait(sb + B_XF, par);
        wg_wait<0>();
        reg_fence(s);
        if (w < 3) {
          sts4(sd0, make_uint4(pack_bf16(s[0], s[1]), pack_bf16(s[4], s[5]), pack_bf16(s[8], s[9]), pack_bf16(s[12], s[13])));
          if (w != 1) sts1(sd0 + 512, pack_bf16(s[16], s[17]));
          if (w == 0) {
            fence_async_smem();
            __syncwarp();
            if (elect_one()) bulk_s2s(mapa(sr + wg * 1024, 2), s0, 1024, mapa(sb + B_SM, 2));
            __syncwarp();
            PROF_W(wg == 1, 4); PROF_W(wg == 0, 8);
          }
          if (w < 2) sts4(sd1, make_uint4(pack_bf16(s[2], s[3]), pack_bf16(s[6], s[7]), pack_bf16(s[10], s[11]), pack_bf16(s[14], s[15])));
          bar_arrive<8, 224>();
        }
        if (t == NT) break;
      }
    }
    float e[28];
#pragma unroll
    for (int k = 0; k < 36; k++) {
      if (k == 2 && t > 0) {
        mbar_expect_if0(arm, xfa - (B_XF - B_CP), 2048);
        mbar_expect_if0(sel | wg, sb + B_G0, 9216);
      }
      if (k % 4 == 0 && k) mbar_wait(sb + B_XF + 2 * k, par);
      if (k == 0) PROF_W(warp == 0, 5);
      if (k % 2 == 0 && k && k <= KP_MAX) {
        mbar_wait_if(paused, pz, sb + B_RES, par ^ 1, k == kp);
      }
      if (k % 4 == 0 || (k % 2 == 0 && k <= KP_MAX)) wg_fence();
      proj_step(e, a, P.d_x + 192, dwl, k);
    }
    wg_commit();
    mbar_wait(sb + B_G0, par);
    wg_wait<0>();
    reg_fence(e);
    PROF_W(warp == 0, 10);
#pragma unroll
    for (int i = 0; i < 14; i++) pk[i] = pack_bf16(e[2 * i], e[2 * i + 1]);
    if (rank != 2) stage_groups(stl, pk);
    PROF_W(warp == 0, 12);
  }
  cluster_sync();
}

__device__ __forceinline__ uint32_t next_tick() {
  uint64_t g0, g1;
  asm volatile("mov.u64 %0, %%globaltimer;" : "=l"(g0) :: "memory");
#pragma unroll 1
  for (int n = 0; n < 8; n++) {
    asm volatile("mov.u64 %0, %%globaltimer;" : "=l"(g1) :: "memory");
    if (__any_sync(0xffffffffu, (uint32_t)g1 != (uint32_t)g0)) break;
  }
  return (uint32_t)g1;
}
__device__ __forceinline__ void wait_ns(uint32_t when) {
  uint32_t c;
  asm volatile("{\n.reg .pred p;\n.reg .b64 g;\n.reg .s32 lo;\nS_%=:\nmov.u64 g, %%globaltimer;\ncvt.u32.u64 lo, g;\nsub.s32 lo, %1, lo;\n"
               "setp.gt.s32 p, lo, 31;\n@p bra.uni S_%=;\nmov.u64 g, %%clock64;\ncvt.u32.u64 %0, g;\nshl.b32 lo, lo, 1;\nadd.s32 %0, %0, lo;\n}" : "=&r"(c) : "r"(when) : "memory");
  spin_until(c - 30);
}
template <bool TAG>
__device__ __forceinline__ uint32_t poll4(uint4 (&v)[4], const uint4* src, uint32_t tag) {
#pragma unroll
  for (int j = 0; j < 4; j++) v[j] = ld_poll(src + j * 32);
  uint32_t n = 0;
  while (__any_sync(0xffffffffu, TAG ? (((v[0].x ^ tag) | (v[1].x ^ tag) | (v[2].x ^ tag) | (v[3].x ^ tag)) & 1) != 0
                                     : (v[0].x == SENT || v[1].x == SENT || v[2].x == SENT || v[3].x == SENT))) {
#pragma unroll
    for (int j = 0; j < 4; j++) if (TAG ? ((v[j].x ^ tag) & 1) != 0 : v[j].x == SENT) v[j] = ld_poll(src + j * 32);
    if (++n > SPIN_LIMIT) __trap();
  }
  return n;
}

__device__ __forceinline__ void read_reference(uint32_t sb, const Params& P, uint32_t& ref, int rank, int t) {
  const int lane = rd_lane();
  const uint32_t* tms = (const uint32_t*)(P.memx + 9 * 512 + lds1(sb + Q_SEL + 48) / 16 + (rd_cid() >> 4) * 32 + lane) + rank;
  if (t > 1) wait_ns(ref + D_GX + (D_DUE - rank_delay(rank)) * 9 / 16); else ref = next_tick();
  uint32_t d, n = 0;
  do {
    asm volatile("ld.relaxed.gpu.global.u32 %0, [%1];" : "=r"(d) : "l"(tms) : "memory");
    if (++n > SPIN_LIMIT) __trap();
  } while (__any_sync(0xffffffffu, (d ^ t) & 255));
  ref += __reduce_max_sync(0xffffffffu, (int)(d - (ref << 6))) >> 6;
  sts1(sb + Q_REF, ref);
  __syncwarp();
  mbar_arrive_if0(lane, sb + B_REF);
  PROF_A(13, n);
  PROF_T(19);
  PROF_V(true, 11, ref - (D_RED + rank_delay(rank)) * 9 / 16);
}
template <int STEP>
__device__ __forceinline__ void check_tiles(uint32_t sb, const Params& P, int w, int t) {
  const int lane = rd_lane();
  uint32_t chk = sb + Q_X + w * Q_CS + lane * 32 + (lane >> 2) * 4, bad = 0;
#pragma unroll 1
  for (uint32_t bar = sb + B_CP + 8 * w; bar <= sb + B_CP + 64; bar += 8 * STEP, chk += STEP * Q_CS) {
    uint32_t ok;
    asm volatile("{\n.reg .pred p, q;\n.reg .b32 a, b;\nsetp.eq.u32 q, %4, 0;\n"
                 "W_%=:\nmbarrier.try_wait.parity.shared::cta.b64 p, [%1], %2" CHINT ";\n@!p bra W_%=;\n"
                 "ld.shared.u32 a, [%3];\nld.shared.u32 b, [%3 + 1024];\nsetp.ne.u32 p, a, 0x80008000;\nsetp.ne.and.u32 p, b, 0x80008000, p;\n"
                 "vote.sync.all.pred p, p, 0xFFFFFFFF;\nand.pred q, q, p;\n@q mbarrier.arrive.shared::cta.b64 _, [%1 + %5];\nselp.u32 %0, 1, 0, p;\n}"
                 : "=r"(ok) : "r"(bar), "r"(~t & 1), "r"(chk), "r"(lane), "n"(B_OK - B_CP) : "memory");
    const int c = (bar - sb - B_CP) / 8;
    if (!ok) {
      uint4 v[4];
      poll4<false>(v, P.memx + c * 512 + (t & 1) * 128 + lds1(sb + Q_SEL + 4 * c) / 16 + lane, 0);
#pragma unroll
      for (int j = 0; j < 4; j++) sts4(sb + Q_X + c * Q_CS + j * 512 + lane * 16, v[j]);
      fence_async_smem();
      __syncwarp();
      mbar_arrive_if0(lane, bar + B_OK - B_CP);
      PROF_OR(7, 1 << c);
      PROF_A(c, 1);
      bad |= c < 3 * VG_V + 3;
    }
    if (STEP == 3) mbar_arrive_if0(lane | (c / 3 != (bad ? 2 : VG_V)), sb + B_E + 24);
  }
}
__device__ __forceinline__ void load_scores(float (&s)[10], uint32_t sa) {
  const uint4 a = lds4(sa), b = lds4(sa + 4096);
  const uint32_t a4 = lds1(sa + 512), b4 = lds1(sa + 4608);
  const uint32_t e[5] = {bf2_add(a.x, b.x), bf2_add(a.y, b.y), bf2_add(a.z, b.z), bf2_add(a.w, b.w), bf2_add(a4, b4)};
#pragma unroll
  for (int i = 0; i < 5; i++) { s[2 * i] = bf_lo(e[i]); s[2 * i + 1] = bf_hi(e[i]); }
}
__device__ __forceinline__ void softmax_num(float (&s)[10]) {
  float mx = fmaxf(fmaxf(fmaxf(s[0], s[1]), fmaxf(s[2], s[3])), fmaxf(fmaxf(s[4], s[5]), fmaxf(s[6], s[7])));
  mx = fmaxf(mx, fmaxf(s[8], s[9]));
  const float m1 = __shfl_xor_sync(0xffffffffu, mx, 1), m2 = __shfl_xor_sync(0xffffffffu, mx, 2), m3 = __shfl_xor_sync(0xffffffffu, mx, 3);
  mx = fmaxf(fmaxf(mx, m1), fmaxf(m2, m3));
  mx *= -SM_SCALE;
#pragma unroll
  for (int i = 0; i < 10; i++) s[i] = ex2(fmaf(s[i], SM_SCALE, mx));
}

template <int NF>
__device__ __forceinline__ void wo_tiles(uint32_t sb, const uint32_t (&f)[76], char* d0, uint32_t pg, uint32_t rs, int t) {
  float d[2][8];
  auto mma = [&](int i, int k0, int k1) {
#pragma unroll
    for (int k = k0; k < k1; k++) {
      if (8 * i + k >= NF && k == 0) wg_ss<0, 0>(d[i & 1], D_WO, 1024 * i, D_OB, 0);
      else if (8 * i + k >= NF || (i == 2 && ((k & 1) || k == 6))) wg_ss<1, 0>(d[i & 1], D_WO, 1024 * i + 128 * k, D_OB, 16 * k);
      else if (k == 0) wg_rs<0, 0>(d[i & 1], f + 32 * i, D_OB, 0);
      else wg_rs<1, 0>(d[i & 1], f + (i < 2 ? 32 * i + 4 * k : 64 + 2 * k), D_OB, 16 * k);
    }
    wg_commit();
  };
  auto put = [&](float (&q)[8]) {
    reg_fence(q);
    st_gpu4((uint4*)d0, (pack_bf16(q[0], q[1]) & ~1u) | ((t - 1) >> 1 & 1), pack_bf16(q[4], q[5]), pack_bf16(q[2], q[3]), pack_bf16(q[6], q[7]));
    __syncwarp();
  };
  wg_fence();
  mma(0, 0, 8);
  mma(1, 0, 8);
  wg_wait<1>();
  put(d[0]);
  PROF_W(threadIdx.x < 288, 14);
  wg_fence();
  mma(2, 0, RS_V);
  d0 += pg & 0xFFFF;
  wg_wait<1>();
  put(d[1]);
  PROF_W(threadIdx.x < 288, 15);
  mma(2, RS_V, 8);
  d0 += pg >> 16;
  wg_wait<1>();
  mbar_arrive_if0(rs, sb + B_RES);
  PROF_W(threadIdx.x < 288, 17);
  wg_wait<0>();
  put(d[0]);
  PROF_W(threadIdx.x < 288, 16);
}
__device__ __forceinline__ void probe_pages(uint32_t sb, const Params& P, int own) {
  const int lane = threadIdx.x & 31;
  const uint32_t first = own ? part_of(blockIdx.x) : 0;
  const uint32_t sel = __shfl_sync(0xffffffffu, near_page(P.memx + first / 16 + (own ? 0 : (blockIdx.x & 63) * 2), own ? 1 : SENT), 0);
  if (lane < (own ? 3 : 10))
    sts1(sb + Q_SEL + 4 * (own ? 9 + lane : lane == 9 ? 12 : lane), ((sel ^ __popc(((first + lane * 8192) ^ first) & 0xB2000)) & 1) * 4096);
}
__device__ __forceinline__ void head_aux(uint32_t sb, const Params& P) {
  const int tid = threadIdx.x & 127, w = rd_warp() & 3, rank = rd_rank(), head = __shfl_sync(0xffffffffu, rd_cid(), 0);
  uint32_t m0[20];
  {
    uint4 a[12], b[12];
#pragma unroll
    for (int j = 0; j < 12; j++) {
      const int u = j;
      const int r = (u & 3) * 32 + (tid >> 2);
      const uint4* src = (const uint4*)(P.wo + (size_t)(head * 128 + (r & 64) + (r & 7) * 8 + ((r >> 3) & 7)) * DM + tile_of(rank, u >> 2) * 64) + (tid & 3) * 2;
      a[j] = __ldg(src); b[j] = __ldg(src + 1);
    }
#pragma unroll
    for (int j = 0; j < 12; j++) {
      const int u = j;
      const int r = (u & 3) * 32 + (tid >> 2);
      const uint32_t dst = sb + Q_WO + (u >> 2) * 16384 + r * 128 + ((((tid & 3) * 2) ^ (r & 7) ^ ((head >> 2) & 1)) << 4);
      sts4(dst, make_uint4(__byte_perm(a[j].x, a[j].y, 0x5410), __byte_perm(a[j].z, a[j].w, 0x5410), __byte_perm(b[j].x, b[j].y, 0x5410), __byte_perm(b[j].z, b[j].w, 0x5410)));
      sts4(dst ^ 16, make_uint4(__byte_perm(a[j].x, a[j].y, 0x7632), __byte_perm(a[j].z, a[j].w, 0x7632), __byte_perm(b[j].x, b[j].y, 0x7632), __byte_perm(b[j].z, b[j].w, 0x7632)));
    }
  }
#pragma unroll
  for (int j = 0; j < 20; j++) {
    const int k = min(tid + (j >> 2) * 128, DM - 1);
    m0[j] = bf2_add(__bfloat16_as_ushort(P.mem0[2 * (j & 3) * DM + k]) | (uint32_t)__bfloat16_as_ushort(P.mem0[(2 * (j & 3) + 1) * DM + k]) << 16, 0);
  }
#pragma unroll
  for (int i = 0; i < 6; i++) sts4(sb + Q_PX + (i * 128 + tid) * 16, make_uint4(0, 0, 0, 0));
  bar_sync<11, 384>();
#pragma unroll
  for (int j = 0; j < 5; j++) {
    const int k = min(tid + j * 128, DM - 1);
    sts4(sb + Q_X + (k >> 6) * Q_CS + (k & 63) * 16, make_uint4(m0[4 * j], m0[4 * j + 1], m0[4 * j + 2], m0[4 * j + 3]));
    sts4(sb + Q_X + (k >> 6) * Q_CS + (k & 63) * 16 + 1024, make_uint4(m0[4 * j], m0[4 * j + 1], m0[4 * j + 2], m0[4 * j + 3]));
  }
#pragma unroll
  for (int i = 0; i < 2; i++) sts4(sb + Q_STG + (i * 16 + (tid >> 3)) * 768 + 640 + (tid & 7) * 16, make_uint4(0, 0, 0, 0));
  fence_async_smem();
  PROF_G(2);
  const uint32_t wa = pin(sb + Q_WO + ((tid >> 4 & 1) * 8 + (tid & 7)) * 128 + (((2 * w + ((tid >> 3) & 1)) ^ (tid & 7)) << 4));
  char* pd = nullptr;
  uint32_t pg = 0;
  auto find_pieces = [&]() {
    const int lane = tid & 31, dcta = (w * 8 + (lane >> 2)) * 3 + rank;
    uint4 f;
    uint32_t n = 0;
    do {
      f = ld_poll((const uint4*)(g_flags + FL_SEL) + dcta);
      if (++n > SPIN_LIMIT) __trap();
    } while (__any_sync(0xffffffffu, !f.x || !f.y || !f.z));
    pd = (char*)P.memx + part_of(dcta) + (head * 4 + (lane & 3) + (f.x - 1) * 256) * 16;
    pg = (8192 + (f.y - f.x) * 4096) | (8192 + (f.z - f.y) * 4096) << 16;
  };
  auto load_group0 = [&](int t) {
    mbar_wait(sb + B_XF, t & 1);
    if (t > 0) mbar_wait(sb + B_E + 16, (t - 1) & 1);
    fence_async_global();
    if (elect_one()) {
#pragma unroll
      for (int k = 0; k < 9; k++) bulk_g2s_mc(sb + Q_X + 2048 + k * Q_CS, (const char*)g_xs + (size_t)t * 73728 + k * 8192, 1024, sb + B_G0, 7);
    }
    __syncwarp();
  };
  uint32_t f[76];
  if (rank != 2) {
#pragma unroll
    for (int k = 0; k < 19; k++) ldsm4t(f[4 * k], f[4 * k + 1], f[4 * k + 2], f[4 * k + 3], wa + (k < 16 ? k : 2 * k - 16) * 2048);
    const uint32_t rs = pin(tid);
    cluster_sync();
    if (w == 3 && rank == 0) load_group0(0);
#pragma unroll 1
    for (int t = 1;; t++) {
      if (t > 1) check_tiles<4>(sb, P, w, t);
      if (w == 0) {
        bar_sync<8, 224>();
        fence_async_smem();
        if (elect_one()) {
          bulk_s2s(mapa(sb + Q_SIN + rank * 4096, rank ^ 1), sb + Q_SOUT + 2048, SX_BYTES, mapa(sb + B_SM, rank ^ 1));
          mbar_arrive(sb + B_SM);
        }
        __syncwarp();
      }
      if (t == NT) break;
      if (t == 1) find_pieces();
      pd = (char*)((uintptr_t)pd ^ 2048);
      if (w == 3 && rank == 0) load_group0(t);
      if (w == 2) { uint32_t ref = lds1(sb + Q_REF); read_reference(sb, P, ref, rank, t); }
      if (w == 1) {
        mbar_wait(sb + B_AN, (t - 1) & 1);
        spin_until(rd_clock() + (rank ? PA1_V : PA0_V));
        mbar_arrive_if0(rs - 32, sb + B_PZ);
      }
      mbar_spin(sb + B_O, (t - 1) & 1);
      PROF_W(w == 0, 13);
      wo_tiles<24>(sb, f, pd, pg, rs, t);
      mbar_expect_if0(rs, sb + B_O, 4096);
    }
  } else {
#pragma unroll
    for (int k = 0; k < 8; k++) ldsm4t(f[4 * k], f[4 * k + 1], f[4 * k + 2], f[4 * k + 3], wa + k * 2048);
    cluster_sync();
    find_pieces();
    const int l = w & 1, tile = w >> 1;
    const uint32_t ob = pin(sb + Q_OB + (l ^ ((head >> 1) & 1)) * 2048 + tile * 1024 + (tid >> 2 & 7) * 128 + (tid & 3) * 16);
    const uint32_t ob0 = sb + Q_OB + ((head >> 1) & 1) * 2048;
    const uint32_t sa = pin(sb + Q_SIN + l * 1024 + (tid & 31) * 16);
#pragma unroll 1
    for (int t = 1; t <= NT; t++) {
      const uint32_t par = (t - 1) & 1;
      {
        uint32_t vf[4][10], p[5];
        float s[10], o[4][4];
        const int lane = rd_lane();
        const uint32_t vb = sb + Q_STG + tile * 12288 + l * 6144 + (lane & 7) * 16;
        const uint32_t ax = vb + ((lane >> 3) & 1) * 768 + (lane >> 4) * 128;
        pd = (char*)((uintptr_t)pd ^ 2048);
        bar_sync<1, 384>();
#pragma unroll
        for (int i = 0; i < 4; i++) ldsm4(vf[i][4], vf[i][5], vf[i][6], vf[i][7], ax + i * 1536 + 256);
        ldsm4(vf[0][8], vf[0][9], vf[1][8], vf[1][9], vb + (lane >> 3) * 768 + 512);
        ldsm4(vf[2][8], vf[2][9], vf[3][8], vf[3][9], vb + (lane >> 3) * 768 + 512 + 3072);
#pragma unroll
        for (int i = 0; i < 4; i++) ldsm4(vf[i][0], vf[i][1], vf[i][2], vf[i][3], ax + i * 1536);
        mbar_spin(sb + B_SM, par);
        PROF_W(w == 0, 20);
        if (t < NT) {
          load_scores(s, sa);
          __syncwarp();
          softmax_num(s);
#pragma unroll
          for (int j = 0; j < 5; j++) p[j] = pack_bf16(s[2 * j], s[2 * j + 1]);
          __syncwarp();
          PROF_W(w == 0, 9);
          float z[4] = {0.f, 0.f, 0.f, 0.f};
          const uint32_t ONE = 0x3F803F80u;
          mma16816(z, ONE, ONE, ONE, ONE, p[0], p[1]);
#pragma unroll
          for (int i = 0; i < 4; i++) { o[i][0] = o[i][1] = o[i][2] = o[i][3] = 0.f; mma16816(o[i], vf[i][0], vf[i][1], vf[i][2], vf[i][3], p[0], p[1]); }
#pragma unroll
          for (int k = 8; k < (NFV_V < 12 ? NFV_V : 12); k++) ldsm4t(f[4 * k], f[4 * k + 1], f[4 * k + 2], f[4 * k + 3], wa + k * 2048);
          mma16816(z, ONE, ONE, ONE, ONE, p[2], p[3]);
#pragma unroll
          for (int i = 0; i < 4; i++) mma16816(o[i], vf[i][4], vf[i][5], vf[i][6], vf[i][7], p[2], p[3]);
#pragma unroll
          for (int k = 12; k < (NFV_V < 16 ? NFV_V : 16); k++) ldsm4t(f[4 * k], f[4 * k + 1], f[4 * k + 2], f[4 * k + 3], wa + k * 2048);
          mma1688(z, ONE, ONE, p[4]);
#pragma unroll
          for (int i = 0; i < 4; i++) mma1688(o[i], vf[i][8], vf[i][9], p[4]);
#pragma unroll
          for (int k = 16; k < 19 && 2 * k - 16 < NFV_V; k++) ldsm4t(f[4 * k], f[4 * k + 1], f[4 * k + 2], f[4 * k + 3], wa + (2 * k - 16) * 2048);
          const float r0 = rcp(z[0]), r1 = rcp(z[1]);
          const uint4 u0 = make_uint4(pack_bf16(o[0][0] * r0, o[0][2] * r0), pack_bf16(o[1][0] * r0, o[1][2] * r0),
                                      pack_bf16(o[2][0] * r0, o[2][2] * r0), pack_bf16(o[3][0] * r0, o[3][2] * r0));
          const uint4 u1 = make_uint4(pack_bf16(o[0][1] * r1, o[0][3] * r1), pack_bf16(o[1][1] * r1, o[1][3] * r1),
                                      pack_bf16(o[2][1] * r1, o[2][3] * r1), pack_bf16(o[3][1] * r1, o[3][3] * r1));
          PROF_W(w == 0, 8);
          sts4(ob, u0);
          sts4(ob + 64, u1);
          bar_sync<5, 160>();
          fence_async_smem();
          PROF_W(w == 0, 13);
          wo_tiles<NFV_V>(sb, f, pd, pg, ob ^ ob0, t);
        }
      }
      const int lane = rd_lane();
      mbar_expect_if0(lane | w, sb + B_SM, SM_BYTES);
      if (t == NT) fence_async_smem();
      {
        float o[2][16];
        uint32_t px[16];
        const uint32_t ox = sb + Q_OX + 2 * w * 512 + lane * 16, pb = sb + B_P + 8 * (t & 1);
        const uint64_t dp = D_PX + (t & 1) * 384;
        mbar_wait(pb, ((t - 1) >> 1) & 1);
        PROF_W(w == 0, 7);
#pragma unroll
        for (int l2 = 0; l2 < 3; l2++) {
          if (l2 == 1) {
            if (t < NT) bar_sync<12, 160>();
            mbar_wait(sb + B_OXFREE, par ^ 1);
          }
          if (l2 < 2) {
            wg_fence();
#pragma unroll
            for (int i = 0; i < 2; i++) {
              wg_sskk<0>(o[i], D_V, l2 * 384 + i * 768, dp, l2 * 192);
              wg_sskk<1>(o[i], D_V, l2 * 384 + i * 768 + 16, dp, l2 * 192 + 16);
              wg_sskk<1>(o[i], D_V, l2 * 384 + i * 768 + 32, dp, l2 * 192 + 32);
            }
            wg_commit();
          }
          if (l2 > 0) {
#pragma unroll
            for (int i = 0; i < 4; i++)
              stsm4(ox + (l2 - 1) * 8192 + (i >> 1) * 4096 + (i & 1) * 512, px[(i >> 1) * 8 + (i & 1)], px[(i >> 1) * 8 + 2 + (i & 1)], px[(i >> 1) * 8 + 4 + (i & 1)], px[(i >> 1) * 8 + 6 + (i & 1)]);
          }
          if (l2 < 2) {
            wg_wait<0>();
            if (l2 == 1 && t < NT) bar_arrive<3, 384>();
            reg_fence(o[0]); reg_fence(o[1]);
#pragma unroll
            for (int i = 0; i < 16; i++) px[i] = pack_bf16(o[i >> 3][2 * (i & 7)], o[i >> 3][2 * (i & 7) + 1]);
          }
        }
        mbar_expect_if0(lane | w, pb, PX_BYTES);
      }
      fence_async_smem();
      __syncwarp();
      mbar_arrive_if0(lane, sb + B_OXREADY);
      PROF_W(w == 0, 23);
    }
  }
  cluster_sync();
}

__device__ __forceinline__ void softmax_x(uint32_t sb, int w, int rank, int t) {
  float s[10];
  const int lane = rd_lane();
  mbar_wait(sb + B_SM, (t - 1) & 1);
  PROF_W(w == 3, 20);
  load_scores(s, sb + Q_SIN + w * 512 + lane * 16);
  const int last = 8 + 8 * w + (lane >> 2) - 2 * (lane & 3);
#pragma unroll
  for (int i = 2; i < 10; i++) s[i] = (8 * (i >> 1) + (i & 1) <= last) ? s[i] : -INFINITY;
  softmax_num(s);
  float sum = ((s[0] + s[1]) + (s[2] + s[3])) + ((s[4] + s[5]) + (s[6] + s[7])) + (s[8] + s[9]);
  sum = (sum + __shfl_xor_sync(0xffffffffu, sum, 1)) + (__shfl_xor_sync(0xffffffffu, sum, 2) + __shfl_xor_sync(0xffffffffu, sum, 3));
  const float r = rcp(sum);
  const uint32_t po = sb + Q_SOUT + 6144 + w * 768;
#pragma unroll
  for (int j = 0; j < 5; j++) sts1(po + lane * 4 + j * 128, pack_bf16(s[2 * j] * r, s[2 * j + 1] * r));
  fence_async_smem();
  __syncwarp();
  if (elect_one()) bulk_s2s(mapa(sb + Q_PX + ((t & 1) * 2 + rank) * 3072 + w * 768, 2), po, 128 * (w + 2), mapa(sb + B_P + 8 * (t & 1), 2));
  __syncwarp();
  PROF_W(w == 3, 22);
}

__device__ __forceinline__ uint32_t word_of(int lane, int head) {
  return (lane & 4) * 1024 + (lane & 8) * 128 + head * 32 + (lane & 16) + (lane & 3) * 4;
}
__device__ __forceinline__ uint32_t service_setup(uint32_t sb, const Params& P, int rank, int w, uint32_t& sof) {
  uint32_t gof = 0;
  sof = part_of(blockIdx.x) + (w - 1) * 8192;
  asm volatile("barrier.cluster.arrive.aligned;" ::: "memory");
  if (w) {
    const int lane = rd_lane(), c = tile_of(rank, w - 1);
    char* word = (char*)P.memx + c * 8192 + word_of(lane, rd_cid());
#pragma unroll 1
    for (int j = 0; j < 16; j++) st_gpu4((uint4*)((char*)P.memx + sof) + j * 32 + lane, 1, 1, 1, 1);
    const __nv_bfloat16* m0 = P.mem0 + (lane & 3) * 2 * DM + c * 64 + rd_cid() * 2 + (lane >> 4);
    sts1(sb + Q_M0 + w * 128 + lane * 4, bf2_add(__bfloat16_as_ushort(m0[0]) | (uint32_t)__bfloat16_as_ushort(m0[DM]) << 16, 0));
    st_gpu1((uint32_t*)word, SENT);
    st_gpu1((uint32_t*)(word + 2048), SENT);
    if (w == 2 && lane < 4) st_gpu4(P.memx + (blockIdx.x & 63) * 2 + (lane & 2) * 128 + (lane & 1), SENT, SENT, SENT, SENT);
    bar_sync<9, 224>();
    if (w < 3) probe_pages(sb, P, w == 1);
    bar_sync<12, 96>();
    if (w == 1) PROF_G(0);
    sof += __shfl_sync(0xffffffffu, lds1(sb + Q_SEL + 32 + 4 * w), 0);
    asm volatile("st.release.gpu.global.u32 [%0], %1;" :: "l"(g_flags + FL_SEL + blockIdx.x * 4 + w - 1), "r"(((sof >> 12) & 1) + 1) : "memory");
    if (w == 1) PROF_G(1);
    gof = c * 8192 + lds1(sb + Q_SEL + 4 * c);
  }
  asm volatile("barrier.cluster.wait.aligned;" ::: "memory");
  return __shfl_sync(0xffffffffu, gof, 0);
}
template <bool ISV>
__device__ __forceinline__ void next_state(uint32_t sb, const Params& P, uint32_t sof, uint32_t gof, uint32_t dly, int w, int t) {
  const int lane = rd_lane(), c = gof >> 13;
  const uint4* src = (const uint4*)((char*)P.memx + (sof ^ (t & 1) * 2048)) + lane;
  uint32_t* dst = (uint32_t*)((char*)P.memx + c * 8192 + word_of(lane, rd_cid()) + (~t & 1) * 2048);
  const bool inj = t == LAG && (lane & 8);
  st_gpu1_if(inj, dst, lds1(sb + Q_M0 + w * 128 + lane * 4));
  asm volatile("" : "+l"(dst), "+l"(src));
  mbar_wait(sb + B_REF, (t - 1) & 1);
  uint32_t when = lds1(sb + Q_REF) + dly;
  uint4 v[4];
  wait_ns(when - (CALIB == 1 ? t % 10 * 28 : 0));
  PROF_W(w == 1, 18);
  const uint32_t nr = poll4<true>(v, src, (t - 1) >> 1);
  PROF_T(25 + w);
  const uint32_t z = bf2_add(bf2_add(v[0].z, v[1].z), bf2_add(v[2].z, v[3].z)), u = bf2_add(bf2_add(v[0].w, v[1].w), bf2_add(v[2].w, v[3].w));
  const uint32_t x = bf2_add(bf2_add(v[0].x, v[1].x), bf2_add(v[2].x, v[3].x)), y = bf2_add(bf2_add(v[0].y, v[1].y), bf2_add(v[2].y, v[3].y));
  const uint32_t x2 = bf2_add(bf2_add(x, 0), __shfl_xor_sync(0xffffffffu, z, 16)), y2 = bf2_add(y, __shfl_xor_sync(0xffffffffu, u, 16));
  const uint32_t x3 = bf2_add(x2, __shfl_xor_sync(0xffffffffu, y2, 8));
  st_gpu1_if(!inj, dst, bf2_add(x3, __shfl_xor_sync(0xffffffffu, x3, 4)));
  if (ISV && w == 3) bar_arrive<12, 160>();
  PROF_T(28 + w);
  PROF_A(9 + w, nr);
  if (!ISV && w == 3) bar_sync<7, 64>();
  wait_ns(when + D_GX + (t == 1 ? GS_V : 0) - (CALIB == 2 ? t % 10 * 28 : 0));
  if (elect_one()) bulk_g2s_mc(sb + Q_X + c * Q_CS, (const char*)P.memx + gof + (~t & 1) * 2048, 2048, sb + B_CP + 8 * c, 7);
  __syncwarp();
  if (w == 1) PROF_T(21);
  st_gpu1((uint32_t*)((uintptr_t)dst ^ 2048), SENT);
}
__device__ __forceinline__ void service_v(uint32_t sb, const Params& P) {
  const int w = rd_warp() & 3, head = __shfl_sync(0xffffffffu, rd_cid(), 0);
  uint32_t sof, g0 = 0, c0 = 0, ref = 0;
  const uint32_t gof = service_setup(sb, P, 2, w, sof);
#pragma unroll 1
  for (int t = 1; t <= NT; t++) {
    const int lane = rd_lane();
    if (w == 0) {
      if (t < NT) mbar_wait(sb + B_XF, t & 1); else warp_flag_wait(g_flags + FL_XS + NT * 32 + 16, 4);
      mbar_wait(sb + B_OXREADY, (t - 1) & 1);
      if (t < NT) bar_sync<13, 64>();
      if (elect_one()) {
        uint4* od = g_ox + (size_t)(t & (OXRING - 1)) * 32768 + head * 512;
        if (t <= NSEG) bulk_s2g(od, sb + Q_OX, 8192);
        if (t > LAG) bulk_s2g(od + 16384, sb + Q_OX + 8192, 8192);
        bulk_commit_wait();
        mbar_arrive(sb + B_OXFREE);
        flag_add(g_flags + FL_OX + t * 32 + head);
      }
      __syncwarp();
      PROF_T(25);
      continue;
    }
    if (t > 1) check_tiles<3>(sb, P, w - 1, t); else mbar_arrive_if0(lane, sb + B_E + 24);
    if (t == NT) break;
    if (w == 1) {
      const uint32_t due = ref + D_GX + D_DUE * 9 / 16;
      const uint32_t g1 = next_tick(), c1 = rd_clock();
      const uint32_t rate = t > 1 ? __float2uint_rn(65536.f * (g1 - g0) * rcp(c1 - c0)) : 36400;
      g0 = g1; c0 = c1;
      uint4* pub = P.memx + 9 * 512 + (lane & 1) * 256 + (lane & 2) * 16 + head;
      const uint32_t lead = D_RED * rate >> 16, late = D_LATE * rate >> 16, r1 = rank_delay(1) * rate >> 10, r0 = rank_delay(0) * rate >> 10;
      mbar_wait(sb + B_E, (t - 1) & 1);
      PROF_T(4);
      mbar_spin(sb + B_E + 24, (t - 1) & 1);
      uint32_t now = g0 + ((rd_clock() - c0) * rate >> 16);
      now = (now + (t < 3 ? lead + (t == 1 ? ST1_V : ST0_V) : (int)(now + 90 - due) > 0 ? late : lead)) << 6;
      st_gpu4(pub, ((now + r0) & ~255u) | t, ((now + r1) & ~255u) | t, (now & ~255u) | t, 0);
      PROF_T(22);
      PROF_V(true, 1, now >> 6);
      read_reference(sb, P, ref, 2, t);
    }
    if (w == 2) {
      mbar_wait(sb + B_SM, (t - 1) & 1);
      mbar_rarrive_if0(lane >> 1, mapa(sb + B_AN, lane & 1));
      bar_sync<5, 160>();
      fence_async_smem();
      if (elect_one()) {
        bulk_s2s(mapa(sb + Q_OB, 1), sb + Q_OB, 4096, mapa(sb + B_O, 1));
        bulk_s2s(mapa(sb + Q_OB, 0), sb + Q_OB, 4096, mapa(sb + B_O, 0));
      }
      __syncwarp();
    }
    if (w == 3) PROF_MID();
    next_state<true>(sb, P, sof, gof, tile_delay(2, w - 1), w, t);
    if (w == 3) bar_arrive<13, 64>();
  }
  cluster_sync();
}
__device__ __forceinline__ void service_qk(uint32_t sb, const Params& P) {
  const int rank = rd_rank(), w = rd_warp() & 3;
  uint32_t sof;
  const uint32_t gof = service_setup(sb, P, rank, w, sof);
#pragma unroll 1
  for (int t = 0;; t++) {
    const int lane = rd_lane();
    if (w == 0 && rank == 0 && t < NT) {
      const uint32_t* fl = g_flags + FL_XS + t * 32;
      warp_flag_wait(fl + (lane & 1 ? (t >= LAG ? 16 : 0) : (t <= NSEG ? 0 : 16)), 4);
      fence_async_global();
      const char* src = (const char*)g_xs + (size_t)t * 73728;
      if (t > 0) mbar_wait(sb + B_E, (t - 1) & 1);
      PROF_T(24);
      uint32_t at = rd_clock();
#pragma unroll 1
      for (int k = 0; k < 9; k++) {
        if (elect_one()) bulk_g2s_mc(sb + Q_X + 3072 + k * Q_CS, src + 1024 + k * 8192, 7168, sb + B_XF + 8 * k, 7);
        __syncwarp();
        at += t ? XP_V : 0;
        spin_until(at);
      }
      if (t == 0) PROF_G(31);
    }
    if (t == 0) continue;
    softmax_x(sb, w, rank, t);
    if (t == NT) break;
    if (w == 0) bar_arrive<7, 64>();
    mbar_expect_if0(lane | (w - 1), sb + B_SM, SX_BYTES);
    if (w == 3) PROF_MID();
    if (w) next_state<false>(sb, P, sof, gof, tile_delay(rank, w - 1), w, t);
  }
  cluster_sync();
}

__global__ void __cluster_dims__(3, 1, 1) __launch_bounds__(512, 1) head_kernel(const __grid_constant__ Params P) {
  extern __shared__ uint8_t smem_raw[];
  const uint32_t sb = (uint32_t)__cvta_generic_to_shared(smem_raw);
  if ((sb & 0xFFFFFFu) != SB0) __trap();
  asm volatile("griddepcontrol.launch_dependents;");
  if (threadIdx.x < 96) {
    const int i = blockIdx.x * 24 + threadIdx.x % 24, m = threadIdx.x / 24;
    const __nv_bfloat16* p = m == 3 ? P.ssm_k + (size_t)(i >> 2) * SEQ + (i & 3) * 64 : (m == 0 ? P.ck : m == 1 ? P.cv : P.x0) + (size_t)i * 64;
    asm volatile("prefetch.global.L2 [%0];" :: "l"(p));
  } else if (threadIdx.x == 96 && blockIdx.x < 45) {
    asm volatile("prefetch.global.L2 [%0];" :: "l"(blockIdx.x < 36 ? P.shift + blockIdx.x * 64 : P.ssm_d + (blockIdx.x - 36) * 64));
  } else if (threadIdx.x == 97 && blockIdx.x < 72) {
    asm volatile("prefetch.global.L2 [%0];" :: "l"(P.mem0 + blockIdx.x * 64));
  }
  PROF_BEGIN();
  if (threadIdx.x == 416) sts1(sb + Q_SET, (__ldcg(&g_epoch) & 1) * FL_TOTAL);
  const int rank = rd_rank(), wg = rd_warp() >> 2;
  if (threadIdx.x == 448) {
    for (int c = 0; c < 9; c++) { mbar_init(sb + B_CP + 8 * c, 1); mbar_arrive(sb + B_CP + 8 * c); mbar_init(sb + B_OK + 8 * c, 1); mbar_arrive(sb + B_OK + 8 * c); mbar_init(sb + B_XF + 8 * c, 1); mbar_expect(sb + B_XF + 8 * c, 7168); }
    mbar_init(sb + B_E, 6); mbar_init(sb + B_G0, 1); mbar_expect(sb + B_G0, 9216); mbar_init(sb + B_E + 16, 6); mbar_init(sb + B_E + 24, 7);
    mbar_init(sb + B_SM, rank == 2 ? 1 : 2); mbar_init(sb + B_O, 1); mbar_init(sb + B_P, 1); mbar_init(sb + B_P + 8, 1);
    mbar_init(sb + B_REF, 1); mbar_init(sb + B_RES, 1); mbar_init(sb + B_PZ, 1); mbar_init(sb + B_AN, 1); mbar_init(sb + B_OXREADY, 4); mbar_init(sb + B_OXFREE, 1);
    mbar_expect(sb + B_SM, rank == 2 ? SM_BYTES : SX_BYTES); mbar_expect(sb + B_P, PX_BYTES); mbar_expect(sb + B_P + 8, PX_BYTES);
    mbar_expect(sb + B_O, 4096);
    sts1(sb + Q_SEL + 48, 0);
    asm volatile("fence.mbarrier_init.release.cluster;" ::: "memory");
  }
  __syncthreads();
  PROF_G(6);
  if (wg < 2) {
    asm volatile("setmaxnreg.inc.sync.aligned.u32 176;");
    head_main(sb, P);
    PROF_END();
  } else if (wg == 2) {
    asm volatile("setmaxnreg.dec.sync.aligned.u32 120;");
    head_aux(sb, P);
    PROF_END();
  } else {
    asm volatile("setmaxnreg.dec.sync.aligned.u32 40;");
    if (rank == 2) service_v(sb, P); else service_qk(sb, P);
    PROF_END();
  }
}

__device__ __forceinline__ void tail_gemm(uint32_t sb, const Params& P) {
  const int lane = threadIdx.x & 31, warp = rd_warp(), w = warp & 3, wg = warp >> 2, tid = threadIdx.x & 127;
  uint32_t a[4 * W_KR];
  fence_async_smem();
  if (elect_one()) {
#pragma unroll 1
    for (int k = w; k < 32; k += 4)
      tma_box(k < W_KR ? sb + wg * 65536 + k * 2048 : sb + W_WS + wg * 6144 + (k - W_KR) * 2048, &P.tm, (blockIdx.x % 3) * 192 + wg * 64, (blockIdx.x / 3) * 512 + k * 16, sb + B_WT + 8 * wg);
  }
  __syncwarp();
  mbar_wait(sb + B_WT + 8 * wg, 0);
  load_afrags<W_KR>(a, sb + wg * 65536, w, lane);
  fence_async_smem();
  bar_sync<1, 416>();
  PROF_G(26);
  if (wg == 2) bar_arrive<2, 256>();
  const uint64_t dw = P.d_ws + wg * 384;
  float4* dst0 = g_acc + ((blockIdx.x % 3) * 12 + warp) * 32 + lane;
#pragma unroll 1
  for (int t = 1; t <= NT; t++) {
#pragma unroll 1
    for (int l = t > NSEG; l <= (t > LAG); l++) {
      const int seg = t - 1 - l * LAG, grp = (seg & 1) * 2 + l;
      const uint64_t db = P.d_ring + grp * 2048;
      float acc[16];
      bar_sync_r(2 + wg, 256);
#pragma unroll
      for (int c = 0; c < 4; c++) {
        if (wg == 0) mbar_wait(sb + B_FULL + 32 * grp + 8 * c, (seg >> 1) & 1);
        if (c == 0) PROF_T(6 * l + wg);
        wg_fence();
#pragma unroll
        for (int i = 0; i < 8; i++) {
          if (c == 0 && i == 0) wg_rs<0, 1>(acc, a, db, 0);
          else if (8 * c + i < W_KR) wg_rs<1, 1>(acc, a + 32 * c + 4 * i, db, 512 * c + 64 * i);
          else wg_ss<1, 1>(acc, dw, 128 * (8 * c + i - W_KR), db, 512 * c + 64 * i);
        }
      }
      wg_commit();
      bar_arrive_r(wg == 2 ? 2 : 3 + wg, 256);
      wg_wait<0>();
      reg_fence(acc);
      mbar_arrive_if0(tid, sb + B_EMPTY + 8 * grp);
      float4* dst = dst0 + (size_t)(l * 256 + seg * 4) * 1152;
#pragma unroll
      for (int j = 0; j < 4; j++)
        asm volatile("red.relaxed.gpu.global.add.v4.f32 [%0], {%1,%2,%3,%4};" :: "l"(dst + j * 1152),
                     "f"(acc[4 * j]), "f"(acc[4 * j + 1]), "f"(acc[4 * j + 2]), "f"(acc[4 * j + 3]) : "memory");
      bar_sync_r(5 + wg, 160);
    }
  }
}
__device__ __forceinline__ void tail_service(uint32_t sb) {
  const int lane = threadIdx.x & 31, warp = rd_warp();
  if (warp == 12) bar_sync<1, 416>();
#pragma unroll 1
  for (int t = 1; t <= NT; t++) {
    if (warp == 12) {
      const int h0 = (blockIdx.x / 3) * 4;
      warp_flag_wait(g_flags + FL_OX + t * 32 + h0 + (lane & 3), 1);
      fence_async_global();
#pragma unroll 1
      for (int l = t > NSEG; l <= (t > LAG); l++) {
        const int seg = t - 1 - l * LAG, grp = (seg & 1) * 2 + l;
        const uint4* src = g_ox + (size_t)(t % OXRING) * 32768 + l * 16384 + h0 * 512;
        const uint32_t bar = sb + B_FULL + 32 * grp;
        mbar_wait_lim(sb + B_EMPTY + 8 * grp, ((seg >> 1) & 1) ^ 1);
        mbar_expect_if0(lane > 3, bar + 8 * lane, 8192);
        if (elect_one()) {
#pragma unroll
          for (int j = 0; j < 4; j++) bulk_g2s(sb + W_RING + (grp * 4 + j) * 8192, src + j * 512, 8192, bar + 8 * j);
        }
        __syncwarp();
      }
      PROF_T(12);
      PROF_MID();
    } else {
#pragma unroll 1
      for (int l = t > NSEG; l <= (t > LAG); l++) {
        bar_sync_r(warp - 8, 160);
        if (lane == 0) flag_add(g_flags + FL_ACC + (l * 64 + t - 1 - l * LAG) * 32);
        __syncwarp();
        PROF_T(6 * l + warp - 10);
      }
    }
  }
}

__device__ __forceinline__ void wait_k1(uint32_t sb, int n) {
  uint32_t c = 0;
  while ((int)lds1(sb + W_K1) < n) {
    __nanosleep(64);
    if (++c > SPIN_LIMIT) __trap();
  }
}
__device__ __forceinline__ void tail_finisher(uint32_t sb, const Params& P) {
  const int lane = threadIdx.x & 31, warp = rd_warp(), kind = warp < 12 ? warp / 6 : warp & 1, f = warp - 6 * kind, tg = blockIdx.x & 3;
  if (warp >= 14) {
    const uint32_t set = lds1(sb + Q_SET), ft = sb + W_FO + kind * 576;
    if (tg == 0) for (int i = kind * 32 + lane; i < FL_TOTAL; i += 64) g_flagsets[FL_TOTAL - set + i] = 0;
#pragma unroll 1
    for (int t = 0; t < NSEG; t++) {
      warp_flag_wait(g_flags + FL_ACC + (64 + t) * 32, 72);
      PROF_T(17);
      if (t == 0 && tg == 0 && threadIdx.x == 448) g_epoch = set ? 0 : 1;
      const float4* ac = g_acc + ((size_t)(256 + t * 4 + tg) * 36 + kind * 18) * 32 + lane;
      float4 v[18];
#pragma unroll
      for (int i = 0; i < 18; i++) v[i] = __ldcg(ac + i * 32);
#pragma unroll
      for (int i = 0; i < 9; i++) {
        const uint4 r = lds4(sb + W_RS + (8 + (t & 7)) * 9216 + (kind * 9 + i) * 512 + lane * 16);
        stsm4t(ft + (lane & 7) * 1168 + (lane >> 3) * 16 + 64 * i, bf2_add(r.x, pack_bf16(v[2 * i].x, v[2 * i].y)), bf2_add(r.y, pack_bf16(v[2 * i].z, v[2 * i].w)),
               bf2_add(r.z, pack_bf16(v[2 * i + 1].x, v[2 * i + 1].y)), bf2_add(r.w, pack_bf16(v[2 * i + 1].z, v[2 * i + 1].w)));
      }
      fence_async_smem();
      __syncwarp();
      mbar_arrive_if0(lane, sb + B_RF + 8 * (t & 7));
      wait_k1(sb, min(t + LAG + 1, NSEG));
      if (lane < 8) {
        bulk_s2g(P.out + (size_t)((t * 4 + tg) * 8 + lane) * DM + kind * 288, ft + lane * 1168, 576);
        bulk_commit_wait();
      }
      __syncwarp();
      PROF_T(18);
    }
    return;
  }
  if (warp >= 12) {
    for (int i = kind * 32 + lane; i < 1152; i += 64) sts4(sb + W_Z + i * 16, make_uint4(0, 0, 0, 0));
    fence_async_smem();
    bar_sync<12, 64>();
#pragma unroll 1
    for (int t = -1; t <= NSEG; t++) {
      if (kind == 0 && t + 1 < NSEG) {
        const uint32_t bar = sb + B_FT + 8 * ((t + 1) & 1);
        mbar_expect_if0(lane, bar, 9216);
        __syncwarp();
        if (lane < 8) bulk_g2s(sb + W_FT + ((t + 1) & 1) * 9344 + lane * 1168, P.x0 + (size_t)(((t + 1) * 4 + tg) * 8 + lane) * DM, 1152, bar);
      }
      if (t < 0) continue;
      if (t < NSEG) bar_sync_r(9 + 2 * kind, 224);
      if (lane == 0) {
        flag_add(g_flags + FL_XS + (t + kind * LAG) * 32 + kind * 16);
        if (kind) { sts1(sb + W_K1, t + 1); PROF_T(14); }
        if (kind ? t < NSEG : t < LAG) bulk_s2g(g_acc + (size_t)(kind * 256 + t * 4 + tg) * 1152, sb + W_Z, 18432);
        if (kind && t + LAG < NSEG) bulk_s2g(g_acc + (size_t)((t + LAG) * 4 + tg) * 1152, sb + W_Z, 18432);
        bulk_commit_wait();
      }
      __syncwarp();
      if (kind) PROF_MID();
    }
    return;
  }
  const uint32_t BF_1 = 0x3F803F80u;
  const uint32_t* ys = (const uint32_t*)(g_y + ((tg >> 1) * DM + f * 96 + (lane >> 2)) * 2 + (tg & 1)) + (lane & 3);
  const uint32_t rs = sb + W_RS + f * 1536 + lane * 16;
  uint32_t y[12] = {};
#pragma unroll 1
  for (int t = 0; t < NSEG; t++) {
    uint32_t x[12];
    if (kind == 0) {
      wait_k1(sb, t - 6);
      mbar_wait(sb + B_FT + 8 * (t & 1), (t >> 1) & 1);
#pragma unroll
      for (int i = 0; i < 3; i++)
        ldsm4t(x[4 * i], x[4 * i + 1], x[4 * i + 2], x[4 * i + 3], sb + W_FT + (t & 1) * 9344 + (lane & 7) * 1168 + f * 192 + (lane >> 3) * 16 + 64 * i);
    } else {
      warp_flag_wait(g_flags + FL_ACC + t * 32, 72);
      PROF_T(13);
#pragma unroll
      for (int i = 0; i < 6; i++) {
        const float4 v = __ldcg(g_acc + ((size_t)(t * 4 + tg) * 36 + f * 6 + i) * 32 + lane);
        x[2 * i] = pack_bf16(v.x, v.y); x[2 * i + 1] = pack_bf16(v.z, v.w);
      }
#pragma unroll
      for (int i = 0; i < 3; i++) {
        const uint4 r = lds4(rs + (t & 7) * 9216 + i * 512);
        x[4 * i] = bf2_add(x[4 * i], r.x); x[4 * i + 1] = bf2_add(x[4 * i + 1], r.y); x[4 * i + 2] = bf2_add(x[4 * i + 2], r.z); x[4 * i + 3] = bf2_add(x[4 * i + 3], r.w);
      }
      mbar_wait(sb + B_RF + 8 * (t & 7), ((t >> 3) & 1) ^ 1);
      PROF_T(15);
    }
    {
      if (t == 0) PROF_G(27);
#pragma unroll 1
      for (int pass = 0; pass < 2; pass++) {
        float g[2][4] = {};
#pragma unroll
        for (int i = 0; i < 12; i++) {
          uint32_t u;
          asm volatile("movmatrix.sync.aligned.m8n8.trans.b16 %0, %1;" : "=r"(u) : "r"(x[i]));
          mma1688(g[i & 1], u, BF_1, u);
        }
        const uint32_t st = sb + W_ST + kind * 1024 + pass * 512 + (lane & 3) * 16;
        if ((lane >> 3) == (lane & 3))
          asm volatile("st.shared.v2.f32 [%0], {%1,%2};" :: "r"(st + f * 64 + (lane & 4) * 2), "f"(lane & 4 ? g[0][3] + g[1][3] : g[0][2] + g[1][2]),
                       "f"(lane & 4 ? g[0][1] + g[1][1] : g[0][0] + g[1][0]) : "memory");
        bar_sync_r(8 + 2 * kind, 192);
        float s0 = 0.f, s1 = 0.f, q0 = 0.f, q1 = 0.f;
        if (kind && pass == 0) PROF_T(19);
        if (kind && pass == 1) PROF_T(21);
#pragma unroll
        for (int i = 0; i < 6; i++) {
          const float4 e = lds4f(st + i * 64);
          s0 += e.x; q0 += e.y; s1 += e.z; q1 += e.w;
        }
        s0 *= 1.f / 576.f; s1 *= 1.f / 576.f;
        const float v0 = fmaf(q0, 1.f / 576.f, -s0 * s0), v1 = fmaf(q1, 1.f / 576.f, -s1 * s1);
        const uint32_t nmean = pack_bf16(-s0, -s1), vb = pack_bf16(fmaxf(v0, 0.f), fmaxf(v1, 0.f));
        const uint32_t ve = pack_bf16(bf_lo(vb) + 1e-5f, bf_hi(vb) + 1e-5f), sd = pack_bf16(sqr(bf_lo(ve)), sqr(bf_hi(ve)));
        const float r0 = rcp(bf_lo(sd)), r1 = rcp(bf_hi(sd));
        const uint32_t rh = pack_bf16(r0, r1), rl = pack_bf16(r0 - bf_lo(rh), r1 - bf_hi(rh));
        if (pass == 0 && (t == 0 || t == 4 * CT_A || t == 4 * CT_B || t == 4 * CT_C)) {
          if (t == 0) PROF_G(25);
          warp_flag_wait(g_flags + FL_Y + t * 8, t < 4 * CT_B ? 32 : DM);
          if (t == 0) PROF_G(26);
#pragma unroll
          for (int i = 0; i < 12; i++) y[i] = __ldcg(ys + t * (DM * 16) + i * 64);
        }
        uint32_t* xd = (uint32_t*)(g_xs + (size_t)(t + kind * LAG) * 4608 + (kind * 4 + tg) * 64 + (f * 3 >> 1) * 512 + (f & 1) * 32) + lane;
#pragma unroll
        for (int i = 0; i < 12; i++) {
          const uint32_t d = bf2_add(x[i], nmean), q = bf2_op(d, rh, bf2_mul(d, rl));
          if (pass == 0) x[i] = bf2_add(x[i], bf2_mul(q, y[i]));
          else xd[i < 4 ? i * 32 : i < 8 ? i * 32 + (f & 1) * 1792 : i * 32 + 1792] = q;
        }
        if (pass == 0) {
#pragma unroll
          for (int i = 0; i < 3; i++) sts4(rs + (kind * 8 + (t & 7)) * 9216 + i * 512, make_uint4(x[4 * i], x[4 * i + 1], x[4 * i + 2], x[4 * i + 3]));
        }
        if (kind && pass == 0) PROF_T(20);
        if (kind && pass == 1) PROF_T(22);
      }
      if (kind) PROF_T(16);
      if (t < 3) PROF_G(28 + t);
      bar_sync_r(9 + 2 * kind, 224);
#pragma unroll
      for (int i = 0; i < 12; i++) y[i] = __ldcg(ys + ((t + 1) & 63) * (DM * 16) + i * 64);
    }
  }
}

template <int NP, typename V>
__device__ __forceinline__ void kv_block(uint4 (&o)[2 * NP], const Params& P, int r0, int c0) {
  V kk[11], vv[8];
  uint4 sw[NP];
#pragma unroll
  for (int i = 0; i < NP; i++) sw[i] = __ldg((const uint4*)(P.shift + (c0 + 2 * i) * 4));
#pragma unroll
  for (int i = 0; i < 11; i++) kk[i] = r0 + i >= 3 ? __ldg((const V*)(P.ck + (size_t)(r0 + i - 3) * DM + c0)) : V{};
#pragma unroll
  for (int i = 0; i < 8; i++) vv[i] = __ldg((const V*)(P.cv + (size_t)(r0 + i) * DM + c0));
#pragma unroll
  for (int cp = 0; cp < NP; cp++) {
    const uint32_t wt[4] = {__byte_perm(sw[cp].y, sw[cp].w, 0x7632), __byte_perm(sw[cp].y, sw[cp].w, 0x5410),
                            __byte_perm(sw[cp].x, sw[cp].z, 0x7632), __byte_perm(sw[cp].x, sw[cp].z, 0x5410)};
    uint32_t e[8];
#pragma unroll
    for (int i = 0; i < 8; i++) {
      uint32_t a = bf2_mul(((const uint32_t*)&kk[i])[cp], wt[0]);
#pragma unroll
      for (int j = 1; j < 4; j++) a = bf2_add(a, bf2_mul(((const uint32_t*)&kk[i + j])[cp], wt[j]));
      e[i] = bf2_mul(a, ((const uint32_t*)&vv[i])[cp]);
    }
    o[2 * cp] = make_uint4(__byte_perm(e[0], e[1], 0x5410), __byte_perm(e[2], e[3], 0x5410), __byte_perm(e[4], e[5], 0x5410), __byte_perm(e[6], e[7], 0x5410));
    o[2 * cp + 1] = make_uint4(__byte_perm(e[0], e[1], 0x7632), __byte_perm(e[2], e[3], 0x7632), __byte_perm(e[4], e[5], 0x7632), __byte_perm(e[6], e[7], 0x7632));
  }
}
__device__ __forceinline__ void kv_task(const Params& P, int id) {
  const int lane = threadIdx.x & 31, tq = id / 9, c0 = (id % 9) * 64 + (lane >> 2) * 8;
  uint4 o[8];
  kv_block<4, uint4>(o, P, tq * 32 + (lane & 3) * 8, c0);
#pragma unroll
  for (int c = 0; c < 8; c++) g_kv[((size_t)tq * DM + c0 + c) * 4 + (lane & 3)] = o[c];
}
__device__ __forceinline__ int next_job(uint32_t sb) {
  int j = 0;
  if ((threadIdx.x & 31) == 0) j = atomicAdd(g_flags + FL_KV + 96, 1);
  return __shfl_sync(0xffffffffu, j, 0);
}
__device__ __forceinline__ uint2 lds2_ro(uint32_t a) { uint2 v; asm("ld.shared.v2.u32 {%0,%1}, [%2];" : "=r"(v.x), "=r"(v.y) : "r"(a)); return v; }

template <int T0, int T1>
__device__ __forceinline__ void conv_job(uint32_t sb, const Params& P, int ch, int sets = 1) {
  const int lane = threadIdx.x & 31, w = threadIdx.x >> 5;
  uint32_t ub = sb + w * C_CH, zb = ub + C_U;
  constexpr int NL = (T1 + 1) / 2, NS = T0 == 0 ? 2 : 1;
  constexpr bool CTA = T1 <= CT_B;
  static_assert(T0 > 0 || T1 == 2, "second set: buffer offsets, warps");
  PROF_G(13 + 4 * (T0 == 0 ? 0 : T0 == CT_A ? 1 : 2));
  uint2 q[NS][T1];
  uint32_t dd[NS];
#pragma unroll
  for (int n = 0; n < NS; n++) {
    const int c = n < sets ? ch - n * 128 : ch;
#pragma unroll
    for (int u = 0; u < T1; u++) q[n][u] = __ldg((const uint2*)(P.ssm_k + (size_t)c * SEQ) + u * 32 + lane);
    dd[n] = (uint32_t)__bfloat16_as_ushort(P.ssm_d[c]) * 0x10001u;
  }
  if (CTA) {
#pragma unroll
    for (int tq = w; tq < 4 * T1 * sets; tq += 16) {
      uint4 o[2];
      const int n = T0 == 0 ? tq >> 3 : 0, tgp = (tq - 8 * n) * 4 + (lane & 3), c0 = (lane >> 2) * 2;
      kv_block<1, uint32_t>(o, P, tgp * 8, ch - w + c0 - n * 128);
#pragma unroll
      for (int c = 0; c < 2; c++) {
        sts4(sb + (c0 + c) * C_CH + n * 2048 + 256 + tgp * 16, o[c]);
        if (T0) g_kv[((size_t)tq * DM + ch - w + c0 + c) * 4 + (lane & 3)] = o[c];
      }
    }
    __syncwarp();
  } else {
    uint4 o[NL];
#pragma unroll
    for (int u = 0; u < NL; u++) o[u] = __ldcg(g_kv + ((size_t)(u * 8 + (lane >> 2)) * DM + ch) * 4 + (lane & 3));
#pragma unroll
    for (int u = 0; u < NL; u++) sts4(ub + 256 + (u * 32 + lane) * 16, o[u]);
  }
#pragma unroll
  for (int n = 0; n < NS; n++) {
    if (lane < 16) { sts4(ub + n * 2048 + lane * 16, make_uint4(0, 0, 0, 0)); sts1(zb + n * 4096 + lane * 4, 0); }
#pragma unroll
    for (int u = 0; u < T1; u++) {
      const uint2 k = q[n][u];
      const uint32_t pv = __shfl_sync(0xffffffffu, lane == 31 ? (u ? q[n][u ? u - 1 : 0].y : 0u) : k.y, (lane + 31) & 31);
      sts4(zb + n * 4096 + 64 + (u * 32 + lane) * 16, make_uint4(__byte_perm(k.x, pv, 0x7610), __byte_perm(k.x, k.x, 0x1032),
                                                                __byte_perm(k.y, k.x, 0x7610), __byte_perm(k.y, k.y, 0x1032)));
    }
  }
  if (CTA) __syncthreads(); else __syncwarp();
  PROF_G(14 + 4 * (T0 == 0 ? 0 : T0 == CT_A ? 1 : 2));
#pragma unroll 1
  for (int n = 0; n < sets; n++, ub += 2048, zb += 4096) {
    float acc[T1 - T0][4];
#pragma unroll
    for (int i = 0; i < T1 - T0; i++) acc[i][0] = acc[i][1] = acc[i][2] = acc[i][3] = 0.f;
#pragma unroll(T0 == 0 ? 4 : 1)
    for (int r = 0; r < 8; r++) {
      uint2 b[T1];
      uint32_t ba = ub + 256 - r * 32 + lane * 8, zp = zb + 64 + (16 * r + 2 * (lane >> 2) - 4 * (lane & 3)) * 4;
      asm volatile("" : "+r"(zp), "+r"(ba) :: "memory");
#pragma unroll
      for (int i = 0; i < T1; i++) b[i] = lds2_ro(ba + i * 256);
#pragma unroll
      for (int mu = 0; mu < T1; mu++) {
        const uint2 a01 = lds2_ro(zp + 512 * mu), a23 = lds2_ro(zp + 512 * mu - 8);
#pragma unroll
        for (int i = (mu > T0 ? mu : T0); i < T1; i++) mma16816(acc[i - T0], a01.x, a01.y, a23.x, a23.y, b[i - mu].x, b[i - mu].y);
      }
    }
    PROF_G(15 + 4 * (T0 == 0 ? 0 : T0 == CT_A ? 1 : 2));
#pragma unroll
    for (int i = 0; i < T1 - T0; i++)
#pragma unroll
      for (int e = 0; e < 2; e++) {
        const int col = (T0 + i) * 8 + 2 * (lane & 3) + e;
        ((uint32_t*)g_y)[((size_t)col * DM + ch - n * 128) * 8 + (lane >> 2)] =
            bf2_add(pack_bf16(acc[i][e], acc[i][2 + e]), bf2_mul(lds1(ub + 256 + col * 32 + (lane >> 2) * 4), n ? dd[NS - 1] : dd[0]));
      }
  }
  if (CTA) __syncthreads(); else __syncwarp();
  PROF_G(16 + 4 * (T0 == 0 ? 0 : T0 == CT_A ? 1 : 2));
  if (CTA ? threadIdx.x == 480 && (T0 == 0 || ch < 512) : lane == 0) flag_add(g_flags + FL_Y + T0 * 32);
  __syncwarp();
}

__global__ void __launch_bounds__(512, 1) tail_kernel(const __grid_constant__ Params P) {
  extern __shared__ uint8_t smem_raw[];
  const uint32_t sb = (uint32_t)__cvta_generic_to_shared(smem_raw);
  if (sb != SB0) __trap();
  PROF_BEGIN();
  if (threadIdx.x == 0) {
    for (int c = 0; c < 16; c++) mbar_init(sb + B_FULL + 8 * c, 1);
    for (int c = 0; c < 4; c++) mbar_init(sb + B_EMPTY + 8 * c, 3);
    for (int c = 0; c < 2; c++) mbar_init(sb + B_FT + 8 * c, 1);
    for (int c = 0; c < 8; c++) mbar_init(sb + B_RF + 8 * c, 2);
    for (int c = 0; c < 3; c++) { mbar_init(sb + B_WT + 8 * c, 1); mbar_expect(sb + B_WT + 8 * c, 65536); }
    sts1(sb + W_K1, 0);
    sts1(sb + Q_SET, (__ldcg(&g_epoch) & 1) * FL_TOTAL);
    fence_async_smem();
  }
  const int b = blockIdx.x, w = threadIdx.x >> 5;
  if ((b >> 2) == 6) {
    __syncthreads();
  } else {
    conv_job<0, CT_A>(sb, P, b * 16 + w, b < 32 ? 1 : 2);
    PROF_G(3);
#pragma unroll 1
    for (int g = b; g == b || (g >> 2) == 6; g -= 8) conv_job<CT_A, CT_B>(sb, P, g * 16 + w);
    PROF_G(4);
    if (b >= 28) {
      constexpr int KV0 = 36 * CT_B, KV1 = KV0 + 192, NK = 576 - KV1;
      const int lane = threadIdx.x & 31;
      auto draw = [&]() {
        const int j = next_job(sb), ch = j < DM ? j : j - DM - NK;
        if (ch >= 0 && ch < DM && lane < (j < DM ? 2 * CT_C : 32)) asm volatile("prefetch.global.L2 [%0];" :: "l"(P.ssm_k + (size_t)ch * SEQ + lane * 64));
        return j;
      };
      int job = draw();
#pragma unroll 1
      for (int k = KV0 + (b - 28) * 16 + w; b < 32 && k < KV1; k += 64) {
        kv_task(P, k);
        __syncwarp();
        if (lane == 0) flag_add(g_flags + FL_KV);
      }
      warp_flag_wait(g_flags + FL_Y + CT_A * 32, 32);
      warp_flag_wait(g_flags + FL_KV, 192);
      spin_until(rd_clock() + (w >> 2) * DP_V);
#pragma unroll 1
      while (job < DM) { const int nx = draw(); conv_job<CT_B, CT_C>(sb, P, job); job = nx; }
      PROF_G(6);
#pragma unroll 1
      while (job < DM + NK) {
        const int nx = draw();
        kv_task(P, job - DM + KV1);
        __syncwarp();
        if (lane == 0) flag_add(g_flags + FL_KV + 32);
        job = nx;
      }
      warp_flag_wait(g_flags + FL_KV + 32, NK);
#pragma unroll 1
      while (job < 2 * DM + NK) { const int nx = draw(); conv_job<CT_C, 16>(sb, P, job - DM - NK); job = nx; }
      PROF_G(5);
      PROF_END();
      return;
    }
    __syncwarp();
  }
  if (blockIdx.x >= 24) {
    PROF_G(24);
    tail_finisher(sb, P);
    PROF_END();
    asm volatile("griddepcontrol.wait;" ::: "memory");
  } else if (rd_warp() < 12) {
    asm volatile("setmaxnreg.inc.sync.aligned.u32 160;");
    tail_gemm(sb, P);
    PROF_END();
  } else {
    asm volatile("setmaxnreg.dec.sync.aligned.u32 32;");
    tail_service(sb);
    PROF_END();
  }
}

}

extern "C" void kernel_launch(void* const* d_in, const int* in_sizes, int n_in, void* d_out, int out_size) {
  typedef const __nv_bfloat16* bp;
  Params P;
  P.x0 = (bp)d_in[0]; P.ck = (bp)d_in[1]; P.cv = (bp)d_in[2]; P.shift = (bp)d_in[3]; P.ssm_k = (bp)d_in[4]; P.ssm_d = (bp)d_in[5];
  P.mem0 = (bp)d_in[7]; P.wq = (bp)d_in[8]; P.wk = (bp)d_in[9]; P.wv = (bp)d_in[10]; P.wo = (bp)d_in[11];
  P.out = (__nv_bfloat16*)d_out;
  typedef CUresult (*Encode)(CUtensorMap*, CUtensorMapDataType, cuuint32_t, void*, const cuuint64_t*, const cuuint64_t*, const cuuint32_t*, const cuuint32_t*,
                             CUtensorMapInterleave, CUtensorMapSwizzle, CUtensorMapL2promotion, CUtensorMapFloatOOBfill);
  static Encode encode = nullptr;
  if (!encode) {
    cudaDriverEntryPointQueryResult qr;
    cudaGetDriverEntryPoint("cuTensorMapEncodeTiled", (void**)&encode, cudaEnableDefault, &qr);
  }
  const cuuint64_t dims[2] = {DM, 4096}, pitch[1] = {DM * 2};
  const cuuint32_t box[2] = {64, 16}, es[2] = {1, 1};
  encode(&P.tm, CU_TENSOR_MAP_DATA_TYPE_BFLOAT16, 2, d_in[11], dims, pitch, box, es, CU_TENSOR_MAP_INTERLEAVE_NONE,
         CU_TENSOR_MAP_SWIZZLE_128B, CU_TENSOR_MAP_L2_PROMOTION_NONE, CU_TENSOR_MAP_FLOAT_OOB_FILL_NONE);
  void* xc = nullptr;
  cudaGetSymbolAddress(&xc, g_xchg);
  P.memx = (uint4*)(((uintptr_t)xc + 0x1FFFFF) & ~(uintptr_t)0x1FFFFF);
  P.d_x = mkdesc(Q_X, 128, 1024, 0); P.d_wl = mkdesc(Q_WL, 16, 1024, 1);
  P.d_ring = mkdesc(W_RING, 512, 128, 0); P.d_ws = mkdesc(W_WS, 16, 1024, 1);
  cudaFuncSetAttribute(head_kernel, cudaFuncAttributeMaxDynamicSharedMemorySize, SMEM_TOTAL);
  cudaFuncSetAttribute(tail_kernel, cudaFuncAttributeMaxDynamicSharedMemorySize, SMEM_TOTAL);
  head_kernel<<<96, 512, SMEM_TOTAL>>>(P);
  cudaLaunchConfig_t cfg = {};
  cfg.gridDim = dim3(36); cfg.blockDim = dim3(512); cfg.dynamicSmemBytes = SMEM_TOTAL; cfg.stream = 0;
  cudaLaunchAttribute attr[1];
  attr[0].id = cudaLaunchAttributeProgrammaticStreamSerialization;
  attr[0].val.programmaticStreamSerializationAllowed = 1;
  cfg.attrs = attr; cfg.numAttrs = 1;
  cudaLaunchKernelEx(&cfg, tail_kernel, P);
}
```

```cpp
#include <cuda.h>
#include <cuda_runtime.h>
#include <cuda_bf16.h>
#include <stdint.h>

namespace {

constexpr int SEQ = 2048, DM = 576, NSEG = 64;
#define LAG_V 5
#define RV_V 1950
#define R1_V 380
#define R0_V 590
#define V1_V 80
#define V2_V 200
#define Q1_V 150
#define Q2_V 290
#define SWAP_V 1
#define ST0_V 200
#define GX_V 1130
#define RS_V 5
#define CALIB 0
#define RF_V 2350
#define RL_V 2000
#define PA1_V 500
#define PA0_V 700
#define XA_V 1
#define XP_V 160
#define CTB_V 6
#define CTC_V 11
#define DP_V 2000
#define NFV_V 24
#define ST_V 5
#define VG_V 0
#define MG_V 3
#define ST1_V 200
#define GS_V 400
#define KPV_V 16
#define KP1_V 24
#define KP0_V 28
constexpr int LAG = LAG_V;
constexpr int NT = NSEG + LAG;
constexpr int OXRING = 8;
static_assert(LAG >= 3 && LAG < OXRING, "pipeline lag");
constexpr uint32_t D_RED = RV_V;
__host__ __device__ constexpr uint32_t rank_delay(int r) { return r == 2 ? 0 : r ? R1_V : R0_V; }
__host__ __device__ constexpr int tile_of(int r, int i) { return r == 2 ? i : SWAP_V ? (r ? 3 + i + (i >> 1) : 5 + i + (i > 0)) : 6 - 3 * r + i; }
__host__ __device__ constexpr uint32_t tile_delay(int r, int i) { return (i == 0 ? 0 : r == 2 ? (i == 1 ? V1_V : V2_V) : i == 1 ? Q1_V : Q2_V) * 9 / 16; }
constexpr uint32_t D_DUE = RF_V, D_LATE = RL_V;
constexpr uint32_t D_GX = GX_V * 9 / 16;
constexpr int KP_V = KPV_V, KP_1 = KP1_V, KP_0 = KP0_V;
constexpr int KP_MAX = KP_0 > KP_1 ? KP_0 : KP_1;
constexpr uint32_t SB0 = 1024;
constexpr float SM_SCALE = 0.08838834764831845f * 1.4426950408889634f;
constexpr uint32_t SENT = 0x80008000u;
constexpr uint32_t SPIN_LIMIT = 1u << 21;

constexpr int FL_XS = 0;
constexpr int FL_ACC = (NT + 2) * 32;
constexpr int FL_OX = FL_ACC + 128 * 32;
constexpr int FL_SEL = FL_OX + (NT + 1) * 32;
constexpr int FL_Y = FL_SEL + 96 * 4;
constexpr int FL_KV = FL_Y + 512;
constexpr int FL_TOTAL = FL_KV + 128;

__device__ __align__(1024) uint4 g_y[256 * DM];
__device__ __align__(1024) uint4 g_kv[256 * DM];
__device__ __align__(1024) uint2 g_acc[2 * 256 * 36 * 32];
__device__ __align__(1024) uint4 g_xs[NT * 4608];
__device__ __align__(1024) uint4 g_ox[OXRING * 512 * 8 * 8];
__device__ __align__(1024) uint4 g_xchg[(256 + 256 + 45) * 512];
__host__ __device__ constexpr uint32_t part_of(int cta) { return (cta < 81 ? 12 + cta * 3 : 13 + cta * 3) * 8192; }
__device__ __align__(1024) uint32_t g_flagsets[2 * FL_TOTAL];
__device__ uint32_t g_epoch;
#define PROF_T(slot) do {} while (0)
#define PROF_END() do {} while (0)
#define PROF_W(cond, slot) do {} while (0)
#define PROF_V(cond, slot, val) do { (void)(val); } while (0)
#define PROF_G(slot) do {} while (0)
#define PROF_OR(slot, val) do {} while (0)
#define PROF_A(idx, val) do { (void)(val); } while (0)
#define PROF_BEGIN() do {} while (0)
#define PROF_MID() do {} while (0)

#define CHINT ""
#define HINT ", 100000"
__device__ __forceinline__ uint32_t pack_bf16(float lo, float hi) {
  uint32_t r; asm("cvt.rn.bf16x2.f32 %0, %1, %2;" : "=r"(r) : "f"(hi), "f"(lo)); return r;
}
__device__ __forceinline__ float bf_lo(uint32_t w) { return __uint_as_float(__byte_perm(w, 0, 0x1044)); }
__device__ __forceinline__ float bf_hi(uint32_t w) { return __uint_as_float(w & 0xFFFF0000u); }
__device__ __forceinline__ uint32_t mapa(uint32_t a, uint32_t r) {
  uint32_t o; asm("mapa.shared::cluster.u32 %0, %1, %2;" : "=r"(o) : "r"(a), "r"(r)); return o;
}
__device__ __forceinline__ void mbar_init(uint32_t bar, uint32_t cnt) {
  asm volatile("mbarrier.init.shared::cta.b64 [%0], %1;" :: "r"(bar), "r"(cnt) : "memory");
}
__device__ __forceinline__ void mbar_expect(uint32_t bar, uint32_t bytes) {
  asm volatile("mbarrier.arrive.expect_tx.shared::cta.b64 _, [%0], %1;" :: "r"(bar), "r"(bytes) : "memory");
}
__device__ __forceinline__ void mbar_arrive(uint32_t bar) {
  asm volatile("mbarrier.arrive.shared::cta.b64 _, [%0];" :: "r"(bar) : "memory");
}
__device__ __forceinline__ void mbar_arrive_if0(uint32_t sel, uint32_t bar) {
  asm volatile("{\n.reg .pred p;\nsetp.eq.u32 p, %1, 0;\n@p mbarrier.arrive.shared::cta.b64 _, [%0];\n}" :: "r"(bar), "r"(sel) : "memory");
}
__device__ __forceinline__ void mbar_expect_if0(uint32_t sel, uint32_t bar, uint32_t bytes) {
  asm volatile("{\n.reg .pred p;\nsetp.eq.u32 p, %1, 0;\n@p mbarrier.arrive.expect_tx.shared::cta.b64 _, [%0], %2;\n}" :: "r"(bar), "r"(sel), "r"(bytes) : "memory");
}
__device__ __forceinline__ void mbar_rarrive_if0(uint32_t sel, uint32_t bar) {
  asm volatile("{\n.reg .pred p;\nsetp.eq.u32 p, %1, 0;\n@p mbarrier.arrive.relaxed.cluster.shared::cluster.b64 _, [%0];\n}" :: "r"(bar), "r"(sel) : "memory");
}
__device__ __forceinline__ void mbar_wait_lim(uint32_t bar, uint32_t par) {
  asm volatile(
    "{\n.reg .pred p;\n.reg .u32 c;\nmov.u32 c, 0;\n"
    "W_%=:\n"
    "mbarrier.try_wait.parity.shared::cta.b64 p, [%0], %1;\n"
    "@p bra D_%=;\n"
    "add.u32 c, c, 1;\nsetp.lt.u32 p, c, %2;\n@p bra W_%=;\ntrap;\n"
    "D_%=:\n}\n" :: "r"(bar), "r"(par), "n"(SPIN_LIMIT) : "memory");
}
__device__ __forceinline__ void mbar_wait(uint32_t bar, uint32_t par) {
  asm volatile(
    "{\n.reg .pred p;\n"
    "W_%=:\n"
    "mbarrier.try_wait.parity.shared::cta.b64 p, [%0], %1" HINT ";\n"
    "@!p bra W_%=;\n}\n" :: "r"(bar), "r"(par) : "memory");
}
__device__ __forceinline__ void mbar_spin(uint32_t bar, uint32_t par) {
  asm volatile("{\n.reg .pred p;\nW_%=:\nmbarrier.try_wait.parity.shared::cta.b64 p, [%0], %1;\n@!p bra W_%=;\n}\n" :: "r"(bar), "r"(par) : "memory");
}
__device__ __forceinline__ uint32_t mbar_test(uint32_t bar, uint32_t par) {
  uint32_t r;
  asm volatile("{\n.reg .pred p;\nmbarrier.test_wait.parity.shared::cta.b64 p, [%1], %2;\nselp.u32 %0, 1, 0, p;\n}" : "=r"(r) : "r"(bar), "r"(par) : "memory");
  return __shfl_sync(0xffffffffu, r, 0);
}
__device__ __forceinline__ void mbar_wait_if(uint32_t& done, uint32_t test, uint32_t bar, uint32_t par, bool force) {
  asm volatile(
    "{\n.reg .pred p, q;\nsetp.ne.u32 p, %0, 0;\n@p bra.uni D_%=;\nsetp.ne.u32 q, %4, 0;\n"
    "mbarrier.test_wait.parity.shared::cta.b64 p, [%1], %3;\n"
    "or.pred p, p, q;\n@!p bra D_%=;\n"
    "W_%=:\n"
    "mbarrier.try_wait.parity.shared::cta.b64 p, [%2], %3, 100000;\n"
    "@!p bra W_%=;\nmov.u32 %0, 1;\nD_%=:\n}\n" : "+r"(done) : "r"(test), "r"(bar), "r"(par), "r"((uint32_t)force) : "memory");
}
template <int ID, int N> __device__ __forceinline__ void bar_sync() { asm volatile("bar.sync %0, %1;" :: "n"(ID), "n"(N) : "memory"); }
template <int ID, int N> __device__ __forceinline__ void bar_arrive() { asm volatile("bar.arrive %0, %1;" :: "n"(ID), "n"(N) : "memory"); }
__device__ __forceinline__ void bar_sync_r(int id, int n) { asm volatile("bar.sync %0, %1;" :: "r"(id), "r"(n) : "memory"); }
__device__ __forceinline__ void bar_arrive_r(int id, int n) { asm volatile("bar.arrive %0, %1;" :: "r"(id), "r"(n) : "memory"); }
__device__ __forceinline__ uint32_t pin(uint32_t x) { return __shfl_sync(0xffffffffu, x, threadIdx.x); }
__device__ __forceinline__ void cluster_sync() {
  asm volatile("barrier.cluster.arrive.aligned;\nbarrier.cluster.wait.aligned;" ::: "memory");
}
__device__ __forceinline__ void fence_async_smem() { asm volatile("fence.proxy.async.shared::cta;" ::: "memory"); }
__device__ __forceinline__ void fence_async_global() { asm volatile("fence.proxy.async.global;" ::: "memory"); }
__device__ __forceinline__ uint4 ld_poll(const uint4* p) {
  uint4 v;
  asm volatile("ld.relaxed.gpu.global.v4.u32 {%0,%1,%2,%3}, [%4];" : "=r"(v.x), "=r"(v.y), "=r"(v.z), "=r"(v.w) : "l"(p) : "memory");
  return v;
}
__device__ __forceinline__ uint32_t rd_clock() { uint64_t c; asm volatile("mov.u64 %0, %%clock64;" : "=l"(c) :: "memory"); return (uint32_t)c; }
__device__ __forceinline__ void spin_until(uint32_t when) {
  asm volatile("{\n.reg .pred p;\n.reg .b64 c;\n.reg .s32 lo;\nS_%=:\nmov.u64 c, %%clock64;\ncvt.u32.u64 lo, c;\nsub.s32 lo, lo, %0;\n"
               "setp.lt.s32 p, lo, 0;\n@p bra.uni S_%=;\n}" :: "r"(when) : "memory");
}
__device__ __forceinline__ uint32_t near_page(uint4* pair, uint32_t mark) {
  uint32_t best0 = ~0u, best1 = ~0u;
  const int lane = threadIdx.x & 31;
#pragma unroll 1
  for (int r = 0; r < 8; r++) {
    if (r >= 4 && !(r & 1) && __all_sync(0xffffffffu, max(best0, best1) - min(best0, best1) > 110u && min(best0, best1) < 420u)) break;
    uint32_t t0, t1, v;
    asm volatile("mov.u32 %0, %%clock;" : "=r"(t0) :: "memory");
    asm volatile("{\n.reg .pred p;\nsetp.eq.u32 p, %2, 0;\nmov.u32 %0, 0;\n@p atom.relaxed.gpu.global.exch.b32 %0, [%1], %3;\n}"
                 : "=&r"(v) : "l"(pair + (r & 1) * 256), "r"(lane), "r"(mark) : "memory");
    asm volatile("{\n.reg .pred p;\nsetp.ne.u32 p, %1, 0x9E3779B9;\nmov.u32 %0, %2;\n@p mov.u32 %0, %%clock;\n}" : "=&r"(t1) : "r"(v), "r"(t0 - 1) : "memory");
    if (r & 1) best1 = min(best1, t1 - t0); else best0 = min(best0, t1 - t0);
  }
  return best1 < best0;
}
__device__ __forceinline__ void st_gpu4(uint4* p, uint32_t a, uint32_t b, uint32_t c, uint32_t d) {
  asm volatile("st.relaxed.gpu.global.v4.u32 [%0], {%1,%2,%3,%4};" :: "l"(p), "r"(a), "r"(b), "r"(c), "r"(d) : "memory");
}
__device__ __forceinline__ void st_gpu1(uint32_t* p, uint32_t a) {
  asm volatile("st.relaxed.gpu.global.u32 [%0], %1;" :: "l"(p), "r"(a) : "memory");
}
__device__ __forceinline__ void st_gpu1_if(bool c, uint32_t* p, uint32_t a) {
  asm volatile("{\n.reg .pred p;\nsetp.ne.u32 p, %2, 0;\n@p st.relaxed.gpu.global.u32 [%0], %1;\n}" :: "l"(p), "r"(a), "r"((uint32_t)c) : "memory");
}
__device__ __forceinline__ void warp_flag_wait(const uint32_t* p, uint32_t target) {
  uint32_t v, n = 0;
  do {
    asm volatile("ld.relaxed.gpu.global.u32 %0, [%1];" : "=r"(v) : "l"(p) : "memory");
    if (++n > SPIN_LIMIT) __trap();
  } while (__any_sync(0xffffffffu, v < target));
}
__device__ __forceinline__ void flag_add_done(uint32_t* p) {
  asm volatile("red.relaxed.gpu.global.add.u32 [%0], 1;" :: "l"(p) : "memory");
}
__device__ __forceinline__ void flag_add(uint32_t* p) {
  asm volatile("red.release.gpu.global.add.u32 [%0], 1;" :: "l"(p) : "memory");
}
__device__ __forceinline__ void bulk_g2s(uint32_t dst, const void* src, uint32_t bytes, uint32_t bar) {
  asm volatile("cp.async.bulk.shared::cluster.global.mbarrier::complete_tx::bytes [%0], [%1], %2, [%3];"
               :: "r"(dst), "l"(src), "r"(bytes), "r"(bar) : "memory");
}
__device__ __forceinline__ void bulk_g2s_mc(uint32_t dst, const void* src, uint32_t bytes, uint32_t bar, uint16_t mask) {
  asm volatile("cp.async.bulk.shared::cluster.global.mbarrier::complete_tx::bytes.multicast::cluster [%0], [%1], %2, [%3], %4;"
               :: "r"(dst), "l"(src), "r"(bytes), "r"(bar), "h"(mask) : "memory");
}
__device__ __forceinline__ void tma_box(uint32_t dst, const CUtensorMap* tm, int col, int row, uint32_t bar) {
  asm volatile("cp.async.bulk.tensor.2d.shared::cluster.global.mbarrier::complete_tx::bytes [%0], [%1, {%2, %3}], [%4];"
               :: "r"(dst), "l"(tm), "r"(col), "r"(row), "r"(bar) : "memory");
}
__device__ __forceinline__ void bulk_s2s(uint32_t dst, uint32_t src, uint32_t bytes, uint32_t bar) {
  asm volatile("cp.async.bulk.shared::cluster.shared::cta.mbarrier::complete_tx::bytes [%0], [%1], %2, [%3];"
               :: "r"(dst), "r"(src), "r"(bytes), "r"(bar) : "memory");
}
__device__ __forceinline__ void bulk_s2g(void* dst, uint32_t src, uint32_t bytes) {
  asm volatile("cp.async.bulk.global.shared::cta.bulk_group [%0], [%1], %2;" :: "l"(dst), "r"(src), "r"(bytes) : "memory");
}
__device__ __forceinline__ void bulk_commit_wait() {
  asm volatile("cp.async.bulk.commit_group;\ncp.async.bulk.wait_group 0;" ::: "memory");
}
__device__ __forceinline__ bool elect_one() {
  uint32_t p; asm volatile("{\n.reg .pred p;\nelect.sync _|p, 0xffffffff;\nselp.u32 %0, 1, 0, p;\n}" : "=r"(p)); return p;
}
__device__ __forceinline__ void ldsm4(uint32_t& r0, uint32_t& r1, uint32_t& r2, uint32_t& r3, uint32_t a) {
  asm volatile("ldmatrix.sync.aligned.m8n8.x4.shared.b16 {%0,%1,%2,%3}, [%4];" : "=r"(r0), "=r"(r1), "=r"(r2), "=r"(r3) : "r"(a) : "memory");
}
__device__ __forceinline__ void ldsm4t(uint32_t& r0, uint32_t& r1, uint32_t& r2, uint32_t& r3, uint32_t a) {
  asm volatile("ldmatrix.sync.aligned.m8n8.x4.trans.shared.b16 {%0,%1,%2,%3}, [%4];" : "=r"(r0), "=r"(r1), "=r"(r2), "=r"(r3) : "r"(a) : "memory");
}
__device__ __forceinline__ void stsm4(uint32_t a, uint32_t r0, uint32_t r1, uint32_t r2, uint32_t r3) {
  asm volatile("stmatrix.sync.aligned.m8n8.x4.shared.b16 [%0], {%1,%2,%3,%4};" :: "r"(a), "r"(r0), "r"(r1), "r"(r2), "r"(r3) : "memory");
}
__device__ __forceinline__ void stsm2(uint32_t a, uint32_t r0, uint32_t r1) {
  asm volatile("stmatrix.sync.aligned.m8n8.x2.shared.b16 [%0], {%1,%2};" :: "r"(a), "r"(r0), "r"(r1) : "memory");
}
__device__ __forceinline__ void stsm4t(uint32_t a, uint32_t r0, uint32_t r1, uint32_t r2, uint32_t r3) {
  asm volatile("stmatrix.sync.aligned.m8n8.x4.trans.shared.b16 [%0], {%1,%2,%3,%4};" :: "r"(a), "r"(r0), "r"(r1), "r"(r2), "r"(r3) : "memory");
}
__device__ __forceinline__ float4 lds4f(uint32_t a) {
  float4 v; asm volatile("ld.shared.v4.f32 {%0,%1,%2,%3}, [%4];" : "=f"(v.x), "=f"(v.y), "=f"(v.z), "=f"(v.w) : "r"(a) : "memory"); return v;
}
__device__ __forceinline__ uint4 lds4(uint32_t a) {
  uint4 v; asm volatile("ld.shared.v4.u32 {%0,%1,%2,%3}, [%4];" : "=r"(v.x), "=r"(v.y), "=r"(v.z), "=r"(v.w) : "r"(a) : "memory"); return v;
}
__device__ __forceinline__ uint32_t lds1(uint32_t a) {
  uint32_t v; asm volatile("ld.shared.u32 %0, [%1];" : "=r"(v) : "r"(a) : "memory"); return v;
}
__device__ __forceinline__ void sts4(uint32_t a, uint4 v) {
  asm volatile("st.shared.v4.u32 [%0], {%1,%2,%3,%4};" :: "r"(a), "r"(v.x), "r"(v.y), "r"(v.z), "r"(v.w) : "memory");
}
__device__ __forceinline__ void sts1(uint32_t a, uint32_t v) { asm volatile("st.shared.u32 [%0], %1;" :: "r"(a), "r"(v) : "memory"); }
__device__ __forceinline__ void mma16816(float (&d)[4], uint32_t a0, uint32_t a1, uint32_t a2, uint32_t a3, uint32_t b0, uint32_t b1) {
  asm volatile("mma.sync.aligned.m16n8k16.row.col.f32.bf16.bf16.f32 {%0,%1,%2,%3}, {%4,%5,%6,%7}, {%8,%9}, {%0,%1,%2,%3};"
               : "+f"(d[0]), "+f"(d[1]), "+f"(d[2]), "+f"(d[3]) : "r"(a0), "r"(a1), "r"(a2), "r"(a3), "r"(b0), "r"(b1));
}
__device__ __forceinline__ void mma1688(float (&d)[4], uint32_t a0, uint32_t a1, uint32_t b0) {
  asm volatile("mma.sync.aligned.m16n8k8.row.col.f32.bf16.bf16.f32 {%0,%1,%2,%3}, {%4,%5}, {%6}, {%0,%1,%2,%3};"
               : "+f"(d[0]), "+f"(d[1]), "+f"(d[2]), "+f"(d[3]) : "r"(a0), "r"(a1), "r"(b0));
}
__device__ __forceinline__ float rcp(float x) { float r; asm("rcp.approx.ftz.f32 %0, %1;" : "=f"(r) : "f"(x)); return r; }
__device__ __forceinline__ float sqr(float x) { float r; asm("sqrt.approx.f32 %0, %1;" : "=f"(r) : "f"(x)); return r; }
__device__ __forceinline__ float ex2(float x) { float r; asm("ex2.approx.ftz.f32 %0, %1;" : "=f"(r) : "f"(x)); return r; }

__device__ __forceinline__ uint32_t bf2_op(uint32_t a, uint32_t b, uint32_t c) {
  uint32_t r; asm("fma.rn.bf16x2 %0, %1, %2, %3;" : "=r"(r) : "r"(a), "r"(b), "r"(c)); return r;
}
__device__ __forceinline__ uint32_t bf2_mul(uint32_t a, uint32_t b) {
  uint32_t r; asm("mul.rn.bf16x2 %0, %1, %2;" : "=r"(r) : "r"(a), "r"(b)); return r;
}
__device__ __forceinline__ uint32_t bf2_add(uint32_t a, uint32_t b) {
  uint32_t r; asm("add.rn.bf16x2 %0, %1, %2;" : "=r"(r) : "r"(a), "r"(b)); return r;
}

__host__ __device__ constexpr uint64_t mkdesc(uint32_t off, uint32_t lbo, uint32_t sbo, uint32_t sw) {
  return (uint64_t)((SB0 + off) >> 4) | ((uint64_t)(lbo >> 4) << 16) | ((uint64_t)(sbo >> 4) << 32) | ((uint64_t)sw << 62);
}
__device__ __forceinline__ void wg_fence() { asm volatile("wgmma.fence.sync.aligned;" ::: "memory"); }
__device__ __forceinline__ void wg_commit() { asm volatile("wgmma.commit_group.sync.aligned;" ::: "memory"); }
template <int N> __device__ __forceinline__ void wg_wait() { asm volatile("wgmma.wait_group.sync.aligned %0;" :: "n"(N) : "memory"); }
template <int N> __device__ __forceinline__ void reg_fence(float (&d)[N]) {
#pragma unroll
  for (int i = 0; i < N; i++) asm volatile("" : "+f"(d[i]) :: "memory");
}

#define F4(d, o) "+f"(d[o]), "+f"(d[o + 1]), "+f"(d[o + 2]), "+f"(d[o + 3])
template <int SC, int TB> __device__ __forceinline__ void wg_rs(float (&d)[8], const uint32_t* a, uint64_t db, int ob) {
  asm volatile("{\n.reg .pred p;\n.reg .b64 b;\nsetp.ne.b32 p, %13, 0;\nadd.s64 b, %12, %15;\n"
    "wgmma.mma_async.sync.aligned.m64n16k16.f32.bf16.bf16 {%0,%1,%2,%3,%4,%5,%6,%7}, {%8,%9,%10,%11}, b, p, 1, 1, %14;\n}\n"
    : F4(d, 0), F4(d, 4) : "r"(a[0]), "r"(a[1]), "r"(a[2]), "r"(a[3]), "l"(db), "n"(SC), "n"(TB), "l"((uint64_t)ob));
}
template <int SC, int TB> __device__ __forceinline__ void wg_rs(float (&d)[12], const uint32_t* a, uint64_t db, int ob) {
  asm volatile("{\n.reg .pred p;\n.reg .b64 b;\nsetp.ne.b32 p, %17, 0;\nadd.s64 b, %16, %19;\n"
    "wgmma.mma_async.sync.aligned.m64n24k16.f32.bf16.bf16 {%0,%1,%2,%3,%4,%5,%6,%7,%8,%9,%10,%11}, {%12,%13,%14,%15}, b, p, 1, 1, %18;\n}\n"
    : F4(d, 0), F4(d, 4), F4(d, 8) : "r"(a[0]), "r"(a[1]), "r"(a[2]), "r"(a[3]), "l"(db), "n"(SC), "n"(TB), "l"((uint64_t)ob));
}
template <int SC, int TB> __device__ __forceinline__ void wg_rs(float (&d)[16], const uint32_t* a, uint64_t db, int ob) {
  asm volatile("{\n.reg .pred p;\n.reg .b64 b;\nsetp.ne.b32 p, %21, 0;\nadd.s64 b, %20, %23;\n"
    "wgmma.mma_async.sync.aligned.m64n32k16.f32.bf16.bf16 {%0,%1,%2,%3,%4,%5,%6,%7,%8,%9,%10,%11,%12,%13,%14,%15}, {%16,%17,%18,%19}, b, p, 1, 1, %22;\n}\n"
    : F4(d, 0), F4(d, 4), F4(d, 8), F4(d, 12) : "r"(a[0]), "r"(a[1]), "r"(a[2]), "r"(a[3]), "l"(db), "n"(SC), "n"(TB), "l"((uint64_t)ob));
}
template <int SC, int TB> __device__ __forceinline__ void wg_rs(float (&d)[28], const uint32_t* a, uint64_t db, int ob) {
  asm volatile("{\n.reg .pred p;\n.reg .b64 b;\nsetp.ne.b32 p, %33, 0;\nadd.s64 b, %32, %35;\n"
    "wgmma.mma_async.sync.aligned.m64n56k16.f32.bf16.bf16 {%0,%1,%2,%3,%4,%5,%6,%7,%8,%9,%10,%11,%12,%13,%14,%15,%16,%17,%18,%19,%20,%21,%22,%23,%24,%25,%26,%27}, {%28,%29,%30,%31}, b, p, 1, 1, %34;\n}\n"
    : F4(d, 0), F4(d, 4), F4(d, 8), F4(d, 12), F4(d, 16), F4(d, 20), F4(d, 24) : "r"(a[0]), "r"(a[1]), "r"(a[2]), "r"(a[3]), "l"(db), "n"(SC), "n"(TB), "l"((uint64_t)ob));
}
template <int SC, int TB> __device__ __forceinline__ void wg_ss(float (&d)[8], uint64_t da, int oa, uint64_t db, int ob) {
  asm volatile("{\n.reg .pred p;\n.reg .b64 a, b;\nsetp.ne.b32 p, %10, 0;\nadd.s64 a, %8, %12;\nadd.s64 b, %9, %13;\n"
    "wgmma.mma_async.sync.aligned.m64n16k16.f32.bf16.bf16 {%0,%1,%2,%3,%4,%5,%6,%7}, a, b, p, 1, 1, 1, %11;\n}\n"
    : F4(d, 0), F4(d, 4) : "l"(da), "l"(db), "n"(SC), "n"(TB), "l"((uint64_t)oa), "l"((uint64_t)ob));
}
template <int SC, int TB> __device__ __forceinline__ void wg_ss(float (&d)[12], uint64_t da, int oa, uint64_t db, int ob) {
  asm volatile("{\n.reg .pred p;\n.reg .b64 a, b;\nsetp.ne.b32 p, %14, 0;\nadd.s64 a, %12, %16;\nadd.s64 b, %13, %17;\n"
    "wgmma.mma_async.sync.aligned.m64n24k16.f32.bf16.bf16 {%0,%1,%2,%3,%4,%5,%6,%7,%8,%9,%10,%11}, a, b, p, 1, 1, 1, %15;\n}\n"
    : F4(d, 0), F4(d, 4), F4(d, 8) : "l"(da), "l"(db), "n"(SC), "n"(TB), "l"((uint64_t)oa), "l"((uint64_t)ob));
}
template <int SC, int TB> __device__ __forceinline__ void wg_ss(float (&d)[16], uint64_t da, int oa, uint64_t db, int ob) {
  asm volatile("{\n.reg .pred p;\n.reg .b64 a, b;\nsetp.ne.b32 p, %18, 0;\nadd.s64 a, %16, %20;\nadd.s64 b, %17, %21;\n"
    "wgmma.mma_async.sync.aligned.m64n32k16.f32.bf16.bf16 {%0,%1,%2,%3,%4,%5,%6,%7,%8,%9,%10,%11,%12,%13,%14,%15}, a, b, p, 1, 1, 1, %19;\n}\n"
    : F4(d, 0), F4(d, 4), F4(d, 8), F4(d, 12) : "l"(da), "l"(db), "n"(SC), "n"(TB), "l"((uint64_t)oa), "l"((uint64_t)ob));
}
template <int SC, int TB> __device__ __forceinline__ void wg_ss(float (&d)[20], uint64_t da, int oa, uint64_t db, int ob) {
  asm volatile("{\n.reg .pred p;\n.reg .b64 a, b;\nsetp.ne.b32 p, %22, 0;\nadd.s64 a, %20, %24;\nadd.s64 b, %21, %25;\n"
    "wgmma.mma_async.sync.aligned.m64n40k16.f32.bf16.bf16 {%0,%1,%2,%3,%4,%5,%6,%7,%8,%9,%10,%11,%12,%13,%14,%15,%16,%17,%18,%19}, a, b, p, 1, 1, 1, %23;\n}\n"
    : F4(d, 0), F4(d, 4), F4(d, 8), F4(d, 12), F4(d, 16) : "l"(da), "l"(db), "n"(SC), "n"(TB), "l"((uint64_t)oa), "l"((uint64_t)ob));
}
template <int SC, int TB> __device__ __forceinline__ void wg_ss(float (&d)[28], uint64_t da, int oa, uint64_t db, int ob) {
  asm volatile("{\n.reg .pred p;\n.reg .b64 a, b;\nsetp.ne.b32 p, %30, 0;\nadd.s64 a, %28, %32;\nadd.s64 b, %29, %33;\n"
    "wgmma.mma_async.sync.aligned.m64n56k16.f32.bf16.bf16 {%0,%1,%2,%3,%4,%5,%6,%7,%8,%9,%10,%11,%12,%13,%14,%15,%16,%17,%18,%19,%20,%21,%22,%23,%24,%25,%26,%27}, a, b, p, 1, 1, 1, %31;\n}\n"
    : F4(d, 0), F4(d, 4), F4(d, 8), F4(d, 12), F4(d, 16), F4(d, 20), F4(d, 24) : "l"(da), "l"(db), "n"(SC), "n"(TB), "l"((uint64_t)oa), "l"((uint64_t)ob));
}

template <int SC> __device__ __forceinline__ void wg_sskk(float (&d)[16], uint64_t da, int oa, uint64_t db, int ob) {
  asm volatile("{\n.reg .pred p;\n.reg .b64 a, b;\nsetp.ne.b32 p, %18, 0;\nadd.s64 a, %16, %19;\nadd.s64 b, %17, %20;\n"
    "wgmma.mma_async.sync.aligned.m64n32k16.f32.bf16.bf16 {%0,%1,%2,%3,%4,%5,%6,%7,%8,%9,%10,%11,%12,%13,%14,%15}, a, b, p, 1, 1, 0, 0;\n}\n"
    : F4(d, 0), F4(d, 4), F4(d, 8), F4(d, 12) : "l"(da), "l"(db), "n"(SC), "l"((uint64_t)oa), "l"((uint64_t)ob));
}

template <int NK> __device__ __forceinline__ void load_afrags(uint32_t* a, uint32_t tile, int w, int lane) {
  int i = lane >> 3, r = lane & 7;
  uint32_t base = tile + ((i >> 1) * 8 + r) * 128 + (((2 * w + (i & 1)) ^ r) << 4);
#pragma unroll
  for (int kk = 0; kk < NK; kk++) ldsm4t(a[4 * kk], a[4 * kk + 1], a[4 * kk + 2], a[4 * kk + 3], base + kk * 2048);
}

constexpr uint32_t Q_WL = 0;
constexpr uint32_t Q_WO = 24576;
constexpr uint32_t Q_OX = Q_WO;
constexpr uint32_t Q_X = 73728;
constexpr uint32_t Q_CS = 10240;
constexpr uint32_t Q_STG = 165888;
constexpr uint32_t Q_OB = 190464;
constexpr uint32_t Q_SIN = 194560;
constexpr uint32_t Q_PX = 204800;
constexpr uint32_t Q_SOUT = Q_PX;
constexpr int Q_KR = 30;
constexpr uint32_t BARS = 228352;
constexpr uint32_t B_CP = BARS;
constexpr uint32_t B_OK = BARS + 408;
constexpr uint32_t B_G0 = BARS + 272;
constexpr uint32_t B_XF = BARS + 72;
constexpr uint32_t B_E = BARS + 224;
constexpr uint32_t B_SM = BARS + 160;
constexpr uint32_t B_O = BARS + 168;
constexpr uint32_t B_P = BARS + 176;
constexpr uint32_t B_OXREADY = BARS + 192;
constexpr uint32_t B_OXFREE = BARS + 200;
constexpr uint32_t B_REF = BARS + 208;
constexpr uint32_t B_AN = BARS + 264;
constexpr uint32_t B_PZ = BARS + 256;
constexpr uint32_t B_RES = BARS + 216;
constexpr uint32_t Q_REF = BARS + 288;
constexpr uint32_t Q_SEL = BARS + 304;
constexpr uint32_t Q_M0 = BARS + 384;
constexpr uint32_t Q_SET = BARS + 360;
constexpr uint32_t SM_BYTES = 4 * 1024, SX_BYTES = 2560, PX_BYTES = 2 * 14 * 128;
constexpr int W_KR = 29;
constexpr uint32_t W_RING = 0;
constexpr uint32_t W_WS = 196608;
constexpr uint32_t W_FT = 0;
constexpr uint32_t W_FO = 18688;
constexpr uint32_t W_Z = 30720;
constexpr uint32_t W_RS = 49152;
constexpr uint32_t W_ST = 28672;
constexpr int CT_A = 2, CT_B = CTB_V, CT_C = CTC_V;
static_assert(36 * CT_C <= 36 * CT_B + 192, "kv stages");
constexpr uint32_t C_U = 256 + 4096;
constexpr uint32_t C_CH = C_U + 64 + 8192 + 96;
constexpr uint32_t B_FULL = BARS;
constexpr uint32_t B_EMPTY = BARS + 128;
constexpr uint32_t B_FT = BARS + 160;
constexpr uint32_t B_RF = BARS + 176;
constexpr uint32_t B_WT = BARS + 248;
constexpr uint32_t W_K1 = BARS + 240;
constexpr uint32_t SMEM_TOTAL = BARS + 896;

struct Params {
  CUtensorMap tm;
  const __nv_bfloat16 *x0, *wq, *wk, *wv, *wo, *mem0, *ck, *cv, *shift, *ssm_k, *ssm_d;
  __nv_bfloat16* out;
  uint4* memx;
  uint64_t d_x, d_wl, d_ring, d_ws;
};

constexpr uint64_t D_QK = mkdesc(Q_STG, 768, 128, 0), D_WO = mkdesc(Q_WO, 16, 1024, 1), D_OB = mkdesc(Q_OB, 128, 2048, 0), D_PX = mkdesc(Q_PX, 128, 768, 0);
constexpr uint64_t D_V = mkdesc(Q_STG, 128, 768, 0);

#define g_flags (g_flagsets + lds1(sb + Q_SET))

__device__ __forceinline__ int rd_cid() { uint32_t v; asm volatile("mov.u32 %0, %%clusterid.x;" : "=r"(v)); return v; }
__device__ __forceinline__ int rd_rank() { uint32_t v; asm volatile("mov.u32 %0, %%cluster_ctarank;" : "=r"(v)); return v; }
__device__ __forceinline__ int rd_lane() { uint32_t v; asm volatile("mov.u32 %0, %%laneid;" : "=r"(v)); return v; }
__device__ __forceinline__ int rd_warp() { uint32_t v; asm volatile("mov.u32 %0, %%tid.x;" : "=r"(v)); return __shfl_sync(0xffffffffu, v >> 5, 0); }

template <int NA>
__device__ __forceinline__ void proj_step(float (&acc)[NA], const uint32_t* a, uint64_t db, uint64_t dwl, int k) {
  const int ob = (k >> 2) * (Q_CS / 16) + (k & 3) * 16;
  if (k == 0) wg_rs<0, 1>(acc, a, db, ob);
  else if (k % 6 != 5) wg_rs<1, 1>(acc, a + 4 * (k - k / 6), db, ob);
  else wg_ss<1, 1>(acc, dwl, 128 * (k / 6), db, ob);
}
__device__ __forceinline__ void stage_groups(uint32_t stl, const uint32_t (&pk)[14]) {
#pragma unroll
  for (int h = 0; h < 2; h++) {
    stsm4(stl + h * 768 + 256, pk[h], pk[2 + h], pk[4 + h], 0);
    stsm4(stl + h * 768 + 6144 + 128, pk[6 + h], pk[8 + h], pk[10 + h], pk[12 + h]);
  }
}
__device__ __forceinline__ void head_main(uint32_t sb, const Params& P) {
  const int lane = threadIdx.x & 31, warp = rd_warp(), w = warp & 3, wg = warp >> 2, rank = rd_rank();
  uint32_t a[4 * Q_KR];
  {
    const int tid = threadIdx.x & 127;
    const __nv_bfloat16* src = (rank == 2 ? P.wv + wg * 64 : (wg ? P.wk : P.wq) + rank * 64) + rd_cid() * 128 + (size_t)(tid >> 3) * 4096 + (tid & 7) * 8;
    const uint32_t so = (tid >> 3) * 128 + (((tid & 7) ^ ((tid >> 3) & 7)) << 4), st = sb + Q_X + wg * (Q_KR * 2048);
    uint4 v[36];
#pragma unroll
    for (int k = 0; k < 36; k++) v[k] = __ldg((const uint4*)(src + (size_t)k * 65536));
#pragma unroll
    for (int k = 0; k < 36; k++) sts4(so + (k % 6 == 5 ? sb + Q_WL + wg * 12288 + (k / 6) * 2048 : st + (k - k / 6) * 2048), v[k]);
    bar_sync_r(9 + wg, wg ? 128 : 224);
    PROF_G(7);
    load_afrags<Q_KR>(a, st, w, lane);
    fence_async_smem();
    bar_arrive<11, 384>();
  }
  cluster_sync();
  PROF_G(8);
  const uint64_t dwl = P.d_wl + wg * 768, dq = D_QK + wg * 384;
  const uint32_t stg = sb + Q_STG + wg * 12288 + 2 * w * 768;
  const uint32_t stm = pin(stg + (lane >> 4) * 6144 + ((lane >> 3) & 1) * 768 + (lane & 7) * 16), stl = pin(stg + lane * 16);
  const uint32_t rel = mapa(sb + B_E, 0), rev = mapa(sb + B_E, 2), sel = pin(threadIdx.x & 127), arm = pin(threadIdx.x - 128 > 8), xfa = pin(sb + B_XF + 8 * lane);
  const uint32_t sx = sb + (wg == rank ? Q_SIN + rank * 4096 : Q_SOUT + 2048), s0 = w ? sx + (2 * w - 1) * 512 : sb + Q_SOUT + wg * 1024, s1 = sx + 2 * w * 512;
  const uint32_t sd0 = pin(s0 + lane * 16), sd1 = pin(s1 + lane * 16), sr = sb + Q_SIN + rank * 4096;
  const int kp = rank == 2 ? KP_V : rank ? KP_1 : KP_0;
  const uint32_t selq = pin(sel | rank >> 1);
    const uint32_t pz = sb + (rank == 2 ? B_SM : B_PZ);
  uint32_t pk[14] = {};
#pragma unroll 1
  for (int t = 0;; t++) {
    const uint32_t par = t & 1;
    uint32_t paused = 0;
    if (t == 0) {
      mbar_wait(sb + B_XF, 0);
    } else {
      float m[12];
#pragma unroll
      for (int c = 0; c < 9; c++) {
        mbar_spin(sb + B_OK + 8 * c, par ^ 1);
        if (c == 0 || c == 3 || c == 8) PROF_W(warp == 0, c == 0 ? 0 : c == 3 ? 1 : 3);
        if (c == 8) mbar_rarrive_if0(selq, rev + 24);
        wg_fence();
#pragma unroll
        for (int k = 4 * c; k < 4 * c + 4; k++) proj_step(m, a, P.d_x, dwl, k);
        if (c == 0) { mbar_expect_if0(arm, xfa, 7168); mbar_rarrive_if0(sel | (rank ^ 2), rel); }
        if (c == XA_V) mbar_rarrive_if0(selq, rel);
        if (c == MG_V) mbar_rarrive_if0(sel, rev);
        if (c == ST_V && rank == 2) {
          if (t > 1) bar_sync<3, 384>();
          stage_groups(stl, pk);
        }
      }
      wg_commit();
      if (rank == 2 && t < NT) { mbar_wait(sb + B_XF, par); paused = mbar_test(pz, par ^ 1); }
      wg_wait<0>();
      reg_fence(m);
      PROF_W(warp == 0, 2);
      stsm4(stm, pack_bf16(m[0], m[1]), pack_bf16(m[2], m[3]), pack_bf16(m[4], m[5]), pack_bf16(m[6], m[7]));
      stsm2(stm + 128, pack_bf16(m[8], m[9]), pack_bf16(m[10], m[11]));
      if (rank == 2) {
        bar_arrive<1, 384>();
        mbar_rarrive_if0(sel, rel + 16);
        if (t == NT) break;
        if (paused) mbar_wait(sb + B_RES, par ^ 1);
      } else {
        float s[20];
        bar_sync<1, 256>();
        fence_async_smem();
        wg_fence();
        wg_ss<0, 1>(s, dq, 0, dq, 768);
#pragma unroll
        for (int i = 1; i < 4; i++) wg_ss<1, 1>(s, dq, 96 * i, dq, 768 + 96 * i);
        wg_commit();
        mbar_rarrive_if0(sel ^ 96, rel + 16);
        if (t < NT) mbar_wait(sb + B_XF, par);
        wg_wait<0>();
        reg_fence(s);
        if (w < 3) {
          sts4(sd0, make_uint4(pack_bf16(s[0], s[1]), pack_bf16(s[4], s[5]), pack_bf16(s[8], s[9]), pack_bf16(s[12], s[13])));
          if (w != 1) sts1(sd0 + 512, pack_bf16(s[16], s[17]));
          if (w == 0) {
            fence_async_smem();
            __syncwarp();
            if (elect_one()) bulk_s2s(mapa(sr + wg * 1024, 2), s0, 1024, mapa(sb + B_SM, 2));
            __syncwarp();
            PROF_W(wg == 1, 4); PROF_W(wg == 0, 8);
          }
          if (w < 2) sts4(sd1, make_uint4(pack_bf16(s[2], s[3]), pack_bf16(s[6], s[7]), pack_bf16(s[10], s[11]), pack_bf16(s[14], s[15])));
          bar_arrive<8, 224>();
        }
        if (t == NT) break;
      }
    }
    float e[28];
#pragma unroll
    for (int k = 0; k < 36; k++) {
      if (k == 2 && t > 0) {
        mbar_expect_if0(arm, xfa - (B_XF - B_CP), 2048);
        mbar_expect_if0(sel | wg, sb + B_G0, 9216);
      }
      if (k % 4 == 0 && k) mbar_wait(sb + B_XF + 2 * k, par);
      if (k == 0) PROF_W(warp == 0, 5);
      if (k % 2 == 0 && k && k <= KP_MAX) {
        mbar_wait_if(paused, pz, sb + B_RES, par ^ 1, k == kp);
      }
      if (k % 4 == 0 || (k % 2 == 0 && k <= KP_MAX)) wg_fence();
      proj_step(e, a, P.d_x + 192, dwl, k);
    }
    wg_commit();
    mbar_wait(sb + B_G0, par);
    wg_wait<0>();
    reg_fence(e);
    PROF_W(warp == 0, 10);
#pragma unroll
    for (int i = 0; i < 14; i++) pk[i] = pack_bf16(e[2 * i], e[2 * i + 1]);
    if (rank != 2) stage_groups(stl, pk);
    PROF_W(warp == 0, 12);
  }
  cluster_sync();
}

__device__ __forceinline__ uint32_t next_tick() {
  uint64_t g0, g1;
  asm volatile("mov.u64 %0, %%globaltimer;" : "=l"(g0) :: "memory");
#pragma unroll 1
  for (int n = 0; n < 8; n++) {
    asm volatile("mov.u64 %0, %%globaltimer;" : "=l"(g1) :: "memory");
    if (__any_sync(0xffffffffu, (uint32_t)g1 != (uint32_t)g0)) break;
  }
  return (uint32_t)g1;
}
__device__ __forceinline__ void wait_ns(uint32_t when) {
  uint32_t c;
  asm volatile("{\n.reg .pred p;\n.reg .b64 g;\n.reg .s32 lo;\nS_%=:\nmov.u64 g, %%globaltimer;\ncvt.u32.u64 lo, g;\nsub.s32 lo, %1, lo;\n"
               "setp.gt.s32 p, lo, 31;\n@p bra.uni S_%=;\nmov.u64 g, %%clock64;\ncvt.u32.u64 %0, g;\nshl.b32 lo, lo, 1;\nadd.s32 %0, %0, lo;\n}" : "=&r"(c) : "r"(when) : "memory");
  spin_until(c - 30);
}
template <bool TAG>
__device__ __forceinline__ uint32_t poll4(uint4 (&v)[4], const uint4* src, uint32_t tag) {
#pragma unroll
  for (int j = 0; j < 4; j++) v[j] = ld_poll(src + j * 32);
  uint32_t n = 0;
  while (__any_sync(0xffffffffu, TAG ? (((v[0].x ^ tag) | (v[1].x ^ tag) | (v[2].x ^ tag) | (v[3].x ^ tag)) & 1) != 0
                                     : (v[0].x == SENT || v[1].x == SENT || v[2].x == SENT || v[3].x == SENT))) {
#pragma unroll
    for (int j = 0; j < 4; j++) if (TAG ? ((v[j].x ^ tag) & 1) != 0 : v[j].x == SENT) v[j] = ld_poll(src + j * 32);
    if (++n > SPIN_LIMIT) __trap();
  }
  return n;
}

__device__ __forceinline__ void read_reference(uint32_t sb, const Params& P, uint32_t& ref, int rank, int t) {
  const int lane = rd_lane();
  const uint32_t* tms = (const uint32_t*)(P.memx + 9 * 512 + lds1(sb + Q_SEL + 48) / 16 + (rd_cid() >> 4) * 32 + lane) + rank;
  if (t > 1) wait_ns(ref + D_GX + (D_DUE - rank_delay(rank)) * 9 / 16); else ref = next_tick();
  uint32_t d, n = 0;
  do {
    asm volatile("ld.relaxed.gpu.global.u32 %0, [%1];" : "=r"(d) : "l"(tms) : "memory");
    if (++n > SPIN_LIMIT) __trap();
  } while (__any_sync(0xffffffffu, (d ^ t) & 255));
  ref += __reduce_max_sync(0xffffffffu, (int)(d - (ref << 6))) >> 6;
  sts1(sb + Q_REF, ref);
  __syncwarp();
  mbar_arrive_if0(lane, sb + B_REF);
  PROF_A(13, n);
  PROF_T(19);
  PROF_V(true, 11, ref - (D_RED + rank_delay(rank)) * 9 / 16);
}
template <int STEP>
__device__ __forceinline__ void check_tiles(uint32_t sb, const Params& P, int w, int t) {
  const int lane = rd_lane();
  uint32_t chk = sb + Q_X + w * Q_CS + lane * 32 + (lane >> 2) * 4, bad = 0;
#pragma unroll 1
  for (uint32_t bar = sb + B_CP + 8 * w; bar <= sb + B_CP + 64; bar += 8 * STEP, chk += STEP * Q_CS) {
    uint32_t ok;
    asm volatile("{\n.reg .pred p, q;\n.reg .b32 a, b;\nsetp.eq.u32 q, %4, 0;\n"
                 "W_%=:\nmbarrier.try_wait.parity.shared::cta.b64 p, [%1], %2" CHINT ";\n@!p bra W_%=;\n"
                 "ld.shared.u32 a, [%3];\nld.shared.u32 b, [%3 + 1024];\nsetp.ne.u32 p, a, 0x80008000;\nsetp.ne.and.u32 p, b, 0x80008000, p;\n"
                 "vote.sync.all.pred p, p, 0xFFFFFFFF;\nand.pred q, q, p;\n@q mbarrier.arrive.shared::cta.b64 _, [%1 + %5];\nselp.u32 %0, 1, 0, p;\n}"
                 : "=r"(ok) : "r"(bar), "r"(~t & 1), "r"(chk), "r"(lane), "n"(B_OK - B_CP) : "memory");
    const int c = (bar - sb - B_CP) / 8;
    if (!ok) {
      uint4 v[4];
      poll4<false>(v, P.memx + c * 512 + (t & 1) * 128 + lds1(sb + Q_SEL + 4 * c) / 16 + lane, 0);
#pragma unroll
      for (int j = 0; j < 4; j++) sts4(sb + Q_X + c * Q_CS + j * 512 + lane * 16, v[j]);
      fence_async_smem();
      __syncwarp();
      mbar_arrive_if0(lane, bar + B_OK - B_CP);
      PROF_OR(7, 1 << c);
      PROF_A(c, 1);
      bad |= c < 3 * VG_V + 3;
    }
    if (STEP == 3) mbar_arrive_if0(lane | (c / 3 != (bad ? 2 : VG_V)), sb + B_E + 24);
  }
}
__device__ __forceinline__ void load_scores(float (&s)[10], uint32_t sa) {
  const uint4 a = lds4(sa), b = lds4(sa + 4096);
  const uint32_t a4 = lds1(sa + 512), b4 = lds1(sa + 4608);
  const uint32_t e[5] = {bf2_add(a.x, b.x), bf2_add(a.y, b.y), bf2_add(a.z, b.z), bf2_add(a.w, b.w), bf2_add(a4, b4)};
#pragma unroll
  for (int i = 0; i < 5; i++) { s[2 * i] = bf_lo(e[i]); s[2 * i + 1] = bf_hi(e[i]); }
}
__device__ __forceinline__ void softmax_num(float (&s)[10]) {
  float mx = fmaxf(fmaxf(fmaxf(s[0], s[1]), fmaxf(s[2], s[3])), fmaxf(fmaxf(s[4], s[5]), fmaxf(s[6], s[7])));
  mx = fmaxf(mx, fmaxf(s[8], s[9]));
  const float m1 = __shfl_xor_sync(0xffffffffu, mx, 1), m2 = __shfl_xor_sync(0xffffffffu, mx, 2), m3 = __shfl_xor_sync(0xffffffffu, mx, 3);
  mx = fmaxf(fmaxf(mx, m1), fmaxf(m2, m3));
  mx *= -SM_SCALE;
#pragma unroll
  for (int i = 0; i < 10; i++) s[i] = ex2(fmaf(s[i], SM_SCALE, mx));
}

template <int NF>
__device__ __forceinline__ void wo_tiles(uint32_t sb, const uint32_t (&f)[76], char* d0, uint32_t pg, uint32_t rs, int t) {
  float d[2][8];
  auto mma = [&](int i, int k0, int k1) {
#pragma unroll
    for (int k = k0; k < k1; k++) {
      if (8 * i + k >= NF && k == 0) wg_ss<0, 0>(d[i & 1], D_WO, 1024 * i, D_OB, 0);
      else if (8 * i + k >= NF || (i == 2 && ((k & 1) || k == 6))) wg_ss<1, 0>(d[i & 1], D_WO, 1024 * i + 128 * k, D_OB, 16 * k);
      else if (k == 0) wg_rs<0, 0>(d[i & 1], f + 32 * i, D_OB, 0);
      else wg_rs<1, 0>(d[i & 1], f + (i < 2 ? 32 * i + 4 * k : 64 + 2 * k), D_OB, 16 * k);
    }
    wg_commit();
  };
  auto put = [&](float (&q)[8]) {
    reg_fence(q);
    st_gpu4((uint4*)d0, (pack_bf16(q[0], q[1]) & ~1u) | ((t - 1) >> 1 & 1), pack_bf16(q[4], q[5]), pack_bf16(q[2], q[3]), pack_bf16(q[6], q[7]));
    __syncwarp();
  };
  wg_fence();
  mma(0, 0, 8);
  mma(1, 0, 8);
  wg_wait<1>();
  put(d[0]);
  PROF_W(threadIdx.x < 288, 14);
  wg_fence();
  mma(2, 0, RS_V);
  d0 += pg & 0xFFFF;
  wg_wait<1>();
  put(d[1]);
  PROF_W(threadIdx.x < 288, 15);
  mma(2, RS_V, 8);
  d0 += pg >> 16;
  wg_wait<1>();
  mbar_arrive_if0(rs, sb + B_RES);
  PROF_W(threadIdx.x < 288, 17);
  wg_wait<0>();
  put(d[0]);
  PROF_W(threadIdx.x < 288, 16);
}
__device__ __forceinline__ void probe_pages(uint32_t sb, const Params& P, int own) {
  const int lane = threadIdx.x & 31;
  const uint32_t first = own ? part_of(blockIdx.x) : 0;
  const uint32_t sel = __shfl_sync(0xffffffffu, near_page(P.memx + first / 16 + (own ? 0 : (blockIdx.x & 63) * 2), own ? 1 : SENT), 0);
  if (lane < (own ? 3 : 10))
    sts1(sb + Q_SEL + 4 * (own ? 9 + lane : lane == 9 ? 12 : lane), ((sel ^ __popc(((first + lane * 8192) ^ first) & 0xB2000)) & 1) * 4096);
}
__device__ __forceinline__ void head_aux(uint32_t sb, const Params& P) {
  const int tid = threadIdx.x & 127, w = rd_warp() & 3, rank = rd_rank(), head = __shfl_sync(0xffffffffu, rd_cid(), 0);
  uint32_t m0[20];
  {
    uint4 a[12], b[12];
#pragma unroll
    for (int j = 0; j < 12; j++) {
      const int u = j;
      const int r = (u & 3) * 32 + (tid >> 2);
      const uint4* src = (const uint4*)(P.wo + (size_t)(head * 128 + (r & 64) + (r & 7) * 8 + ((r >> 3) & 7)) * DM + tile_of(rank, u >> 2) * 64) + (tid & 3) * 2;
      a[j] = __ldg(src); b[j] = __ldg(src + 1);
    }
#pragma unroll
    for (int j = 0; j < 12; j++) {
      const int u = j;
      const int r = (u & 3) * 32 + (tid >> 2);
      const uint32_t dst = sb + Q_WO + (u >> 2) * 16384 + r * 128 + ((((tid & 3) * 2) ^ (r & 7) ^ ((head >> 2) & 1)) << 4);
      sts4(dst, make_uint4(__byte_perm(a[j].x, a[j].y, 0x5410), __byte_perm(a[j].z, a[j].w, 0x5410), __byte_perm(b[j].x, b[j].y, 0x5410), __byte_perm(b[j].z, b[j].w, 0x5410)));
      sts4(dst ^ 16, make_uint4(__byte_perm(a[j].x, a[j].y, 0x7632), __byte_perm(a[j].z, a[j].w, 0x7632), __byte_perm(b[j].x, b[j].y, 0x7632), __byte_perm(b[j].z, b[j].w, 0x7632)));
    }
  }
#pragma unroll
  for (int j = 0; j < 20; j++) {
    const int k = min(tid + (j >> 2) * 128, DM - 1);
    m0[j] = bf2_add(__bfloat16_as_ushort(P.mem0[2 * (j & 3) * DM + k]) | (uint32_t)__bfloat16_as_ushort(P.mem0[(2 * (j & 3) + 1) * DM + k]) << 16, 0);
  }
#pragma unroll
  for (int i = 0; i < 6; i++) sts4(sb + Q_PX + (i * 128 + tid) * 16, make_uint4(0, 0, 0, 0));
  bar_sync<11, 384>();
#pragma unroll
  for (int j = 0; j < 5; j++) {
    const int k = min(tid + j * 128, DM - 1);
    sts4(sb + Q_X + (k >> 6) * Q_CS + (k & 63) * 16, make_uint4(m0[4 * j], m0[4 * j + 1], m0[4 * j + 2], m0[4 * j + 3]));
    sts4(sb + Q_X + (k >> 6) * Q_CS + (k & 63) * 16 + 1024, make_uint4(m0[4 * j], m0[4 * j + 1], m0[4 * j + 2], m0[4 * j + 3]));
  }
#pragma unroll
  for (int i = 0; i < 2; i++) sts4(sb + Q_STG + (i * 16 + (tid >> 3)) * 768 + 640 + (tid & 7) * 16, make_uint4(0, 0, 0, 0));
  fence_async_smem();
  PROF_G(2);
  const uint32_t wa = pin(sb + Q_WO + ((tid >> 4 & 1) * 8 + (tid & 7)) * 128 + (((2 * w + ((tid >> 3) & 1)) ^ (tid & 7)) << 4));
  char* pd = nullptr;
  uint32_t pg = 0;
  auto find_pieces = [&]() {
    const int lane = tid & 31, dcta = (w * 8 + (lane >> 2)) * 3 + rank;
    uint4 f;
    uint32_t n = 0;
    do {
      f = ld_poll((const uint4*)(g_flags + FL_SEL) + dcta);
      if (++n > SPIN_LIMIT) __trap();
    } while (__any_sync(0xffffffffu, !f.x || !f.y || !f.z));
    pd = (char*)P.memx + part_of(dcta) + (head * 4 + (lane & 3) + (f.x - 1) * 256) * 16;
    pg = (8192 + (f.y - f.x) * 4096) | (8192 + (f.z - f.y) * 4096) << 16;
  };
  auto load_group0 = [&](int t) {
    mbar_wait(sb + B_XF, t & 1);
    if (t > 0) mbar_wait(sb + B_E + 16, (t - 1) & 1);
    fence_async_global();
    if (elect_one()) {
#pragma unroll
      for (int k = 0; k < 9; k++) bulk_g2s_mc(sb + Q_X + 2048 + k * Q_CS, (const char*)g_xs + (size_t)t * 73728 + k * 8192, 1024, sb + B_G0, 7);
    }
    __syncwarp();
  };
  uint32_t f[76];
  if (rank != 2) {
#pragma unroll
    for (int k = 0; k < 19; k++) ldsm4t(f[4 * k], f[4 * k + 1], f[4 * k + 2], f[4 * k + 3], wa + (k < 16 ? k : 2 * k - 16) * 2048);
    const uint32_t rs = pin(tid);
    cluster_sync();
    if (w == 3 && rank == 0) load_group0(0);
#pragma unroll 1
    for (int t = 1;; t++) {
      if (t > 1) check_tiles<4>(sb, P, w, t);
      if (w == 0) {
        bar_sync<8, 224>();
        fence_async_smem();
        if (elect_one()) {
          bulk_s2s(mapa(sb + Q_SIN + rank * 4096, rank ^ 1), sb + Q_SOUT + 2048, SX_BYTES, mapa(sb + B_SM, rank ^ 1));
          mbar_arrive(sb + B_SM);
        }
        __syncwarp();
      }
      if (t == NT) break;
      if (t == 1) find_pieces();
      pd = (char*)((uintptr_t)pd ^ 2048);
      if (w == 3 && rank == 0) load_group0(t);
      if (w == 2) { uint32_t ref = lds1(sb + Q_REF); read_reference(sb, P, ref, rank, t); }
      if (w == 1) {
        mbar_wait(sb + B_AN, (t - 1) & 1);
        spin_until(rd_clock() + (rank ? PA1_V : PA0_V));
        mbar_arrive_if0(rs - 32, sb + B_PZ);
      }
      mbar_spin(sb + B_O, (t - 1) & 1);
      PROF_W(w == 0, 13);
      wo_tiles<24>(sb, f, pd, pg, rs, t);
      mbar_expect_if0(rs, sb + B_O, 4096);
    }
  } else {
#pragma unroll
    for (int k = 0; k < 8; k++) ldsm4t(f[4 * k], f[4 * k + 1], f[4 * k + 2], f[4 * k + 3], wa + k * 2048);
    cluster_sync();
    find_pieces();
    const int l = w & 1, tile = w >> 1;
    const uint32_t ob = pin(sb + Q_OB + (l ^ ((head >> 1) & 1)) * 2048 + tile * 1024 + (tid >> 2 & 7) * 128 + (tid & 3) * 16);
    const uint32_t ob0 = sb + Q_OB + ((head >> 1) & 1) * 2048;
    const uint32_t sa = pin(sb + Q_SIN + l * 1024 + (tid & 31) * 16);
#pragma unroll 1
    for (int t = 1; t <= NT; t++) {
      const uint32_t par = (t - 1) & 1;
      {
        uint32_t vf[4][10], p[5];
        float s[10], o[4][4];
        const int lane = rd_lane();
        const uint32_t vb = sb + Q_STG + tile * 12288 + l * 6144 + (lane & 7) * 16;
        const uint32_t ax = vb + ((lane >> 3) & 1) * 768 + (lane >> 4) * 128;
        pd = (char*)((uintptr_t)pd ^ 2048);
        bar_sync<1, 384>();
#pragma unroll
        for (int i = 0; i < 4; i++) ldsm4(vf[i][4], vf[i][5], vf[i][6], vf[i][7], ax + i * 1536 + 256);
        ldsm4(vf[0][8], vf[0][9], vf[1][8], vf[1][9], vb + (lane >> 3) * 768 + 512);
        ldsm4(vf[2][8], vf[2][9], vf[3][8], vf[3][9], vb + (lane >> 3) * 768 + 512 + 3072);
#pragma unroll
        for (int i = 0; i < 4; i++) ldsm4(vf[i][0], vf[i][1], vf[i][2], vf[i][3], ax + i * 1536);
        mbar_spin(sb + B_SM, par);
        PROF_W(w == 0, 20);
        if (t < NT) {
          load_scores(s, sa);
          __syncwarp();
          softmax_num(s);
#pragma unroll
          for (int j = 0; j < 5; j++) p[j] = pack_bf16(s[2 * j], s[2 * j + 1]);
          __syncwarp();
          PROF_W(w == 0, 9);
          float z[4] = {0.f, 0.f, 0.f, 0.f};
          const uint32_t ONE = 0x3F803F80u;
          mma16816(z, ONE, ONE, ONE, ONE, p[0], p[1]);
#pragma unroll
          for (int i = 0; i < 4; i++) { o[i][0] = o[i][1] = o[i][2] = o[i][3] = 0.f; mma16816(o[i], vf[i][0], vf[i][1], vf[i][2], vf[i][3], p[0], p[1]); }
#pragma unroll
          for (int k = 8; k < (NFV_V < 12 ? NFV_V : 12); k++) ldsm4t(f[4 * k], f[4 * k + 1], f[4 * k + 2], f[4 * k + 3], wa + k * 2048);
          mma16816(z, ONE, ONE, ONE, ONE, p[2], p[3]);
#pragma unroll
          for (int i = 0; i < 4; i++) mma16816(o[i], vf[i][4], vf[i][5], vf[i][6], vf[i][7], p[2], p[3]);
#pragma unroll
          for (int k = 12; k < (NFV_V < 16 ? NFV_V : 16); k++) ldsm4t(f[4 * k], f[4 * k + 1], f[4 * k + 2], f[4 * k + 3], wa + k * 2048);
          mma1688(z, ONE, ONE, p[4]);
#pragma unroll
          for (int i = 0; i < 4; i++) mma1688(o[i], vf[i][8], vf[i][9], p[4]);
#pragma unroll
          for (int k = 16; k < 19 && 2 * k - 16 < NFV_V; k++) ldsm4t(f[4 * k], f[4 * k + 1], f[4 * k + 2], f[4 * k + 3], wa + (2 * k - 16) * 2048);
          const float r0 = rcp(z[0]), r1 = rcp(z[1]);
          const uint4 u0 = make_uint4(pack_bf16(o[0][0] * r0, o[0][2] * r0), pack_bf16(o[1][0] * r0, o[1][2] * r0),
                                      pack_bf16(o[2][0] * r0, o[2][2] * r0), pack_bf16(o[3][0] * r0, o[3][2] * r0));
          const uint4 u1 = make_uint4(pack_bf16(o[0][1] * r1, o[0][3] * r1), pack_bf16(o[1][1] * r1, o[1][3] * r1),
                                      pack_bf16(o[2][1] * r1, o[2][3] * r1), pack_bf16(o[3][1] * r1, o[3][3] * r1));
          PROF_W(w == 0, 8);
          sts4(ob, u0);
          sts4(ob + 64, u1);
          bar_sync<5, 160>();
          fence_async_smem();
          PROF_W(w == 0, 13);
          wo_tiles<NFV_V>(sb, f, pd, pg, ob ^ ob0, t);
        }
      }
      const int lane = rd_lane();
      mbar_expect_if0(lane | w, sb + B_SM, SM_BYTES);
      if (t == NT) fence_async_smem();
      {
        float o[2][16];
        uint32_t px[16];
        const uint32_t ox = sb + Q_OX + 2 * w * 512 + lane * 16, pb = sb + B_P + 8 * (t & 1);
        const uint64_t dp = D_PX + (t & 1) * 384;
        mbar_wait(pb, ((t - 1) >> 1) & 1);
        PROF_W(w == 0, 7);
#pragma unroll
        for (int l2 = 0; l2 < 3; l2++) {
          if (l2 == 1) {
            if (t < NT) bar_sync<12, 160>();
            mbar_wait(sb + B_OXFREE, par ^ 1);
          }
          if (l2 < 2) {
            wg_fence();
#pragma unroll
            for (int i = 0; i < 2; i++) {
              wg_sskk<0>(o[i], D_V, l2 * 384 + i * 768, dp, l2 * 192);
              wg_sskk<1>(o[i], D_V, l2 * 384 + i * 768 + 16, dp, l2 * 192 + 16);
              wg_sskk<1>(o[i], D_V, l2 * 384 + i * 768 + 32, dp, l2 * 192 + 32);
            }
            wg_commit();
          }
          if (l2 > 0) {
#pragma unroll
            for (int i = 0; i < 4; i++)
              stsm4(ox + (l2 - 1) * 8192 + (i >> 1) * 4096 + (i & 1) * 512, px[(i >> 1) * 8 + (i & 1)], px[(i >> 1) * 8 + 2 + (i & 1)], px[(i >> 1) * 8 + 4 + (i & 1)], px[(i >> 1) * 8 + 6 + (i & 1)]);
            fence_async_smem();
            __syncwarp();
            mbar_arrive_if0(lane, sb + B_OXREADY + 88 * (l2 - 1));
          }
          if (l2 < 2) {
            wg_wait<0>();
            if (l2 == 1 && t < NT) bar_arrive<3, 384>();
            reg_fence(o[0]); reg_fence(o[1]);
#pragma unroll
            for (int i = 0; i < 16; i++) px[i] = pack_bf16(o[i >> 3][2 * (i & 7)], o[i >> 3][2 * (i & 7) + 1]);
          }
        }
        mbar_expect_if0(lane | w, pb, PX_BYTES);
      }
      PROF_W(w == 0, 23);
    }
  }
  cluster_sync();
}

__device__ __forceinline__ void softmax_x(uint32_t sb, int w, int rank, int t) {
  float s[10];
  const int lane = rd_lane();
  mbar_wait(sb + B_SM, (t - 1) & 1);
  PROF_W(w == 3, 20);
  load_scores(s, sb + Q_SIN + w * 512 + lane * 16);
  const int last = 8 + 8 * w + (lane >> 2) - 2 * (lane & 3);
#pragma unroll
  for (int i = 2; i < 10; i++) s[i] = (8 * (i >> 1) + (i & 1) <= last) ? s[i] : -INFINITY;
  softmax_num(s);
  float sum = ((s[0] + s[1]) + (s[2] + s[3])) + ((s[4] + s[5]) + (s[6] + s[7])) + (s[8] + s[9]);
  sum = (sum + __shfl_xor_sync(0xffffffffu, sum, 1)) + (__shfl_xor_sync(0xffffffffu, sum, 2) + __shfl_xor_sync(0xffffffffu, sum, 3));
  const float r = rcp(sum);
  const uint32_t po = sb + Q_SOUT + 6144 + w * 768;
#pragma unroll
  for (int j = 0; j < 5; j++) sts1(po + lane * 4 + j * 128, pack_bf16(s[2 * j] * r, s[2 * j + 1] * r));
  fence_async_smem();
  __syncwarp();
  if (elect_one()) bulk_s2s(mapa(sb + Q_PX + ((t & 1) * 2 + rank) * 3072 + w * 768, 2), po, 128 * (w + 2), mapa(sb + B_P + 8 * (t & 1), 2));
  __syncwarp();
  PROF_W(w == 3, 22);
}

__device__ __forceinline__ uint32_t word_of(int lane, int head) {
  return (lane & 4) * 1024 + (lane & 8) * 128 + head * 32 + (lane & 16) + (lane & 3) * 4;
}
__device__ __forceinline__ uint32_t service_setup(uint32_t sb, const Params& P, int rank, int w, uint32_t& sof) {
  uint32_t gof = 0;
  sof = part_of(blockIdx.x) + (w - 1) * 8192;
  asm volatile("barrier.cluster.arrive.aligned;" ::: "memory");
  if (w) {
    const int lane = rd_lane(), c = tile_of(rank, w - 1);
    char* word = (char*)P.memx + c * 8192 + word_of(lane, rd_cid());
#pragma unroll 1
    for (int j = 0; j < 16; j++) st_gpu4((uint4*)((char*)P.memx + sof) + j * 32 + lane, 1, 1, 1, 1);
    const __nv_bfloat16* m0 = P.mem0 + (lane & 3) * 2 * DM + c * 64 + rd_cid() * 2 + (lane >> 4);
    sts1(sb + Q_M0 + w * 128 + lane * 4, bf2_add(__bfloat16_as_ushort(m0[0]) | (uint32_t)__bfloat16_as_ushort(m0[DM]) << 16, 0));
    st_gpu1((uint32_t*)word, SENT);
    st_gpu1((uint32_t*)(word + 2048), SENT);
    if (w == 2 && lane < 4) st_gpu4(P.memx + (blockIdx.x & 63) * 2 + (lane & 2) * 128 + (lane & 1), SENT, SENT, SENT, SENT);
    bar_sync<9, 224>();
    if (w < 3) probe_pages(sb, P, w == 1);
    bar_sync<12, 96>();
    if (w == 1) PROF_G(0);
    sof += __shfl_sync(0xffffffffu, lds1(sb + Q_SEL + 32 + 4 * w), 0);
    asm volatile("st.release.gpu.global.u32 [%0], %1;" :: "l"(g_flags + FL_SEL + blockIdx.x * 4 + w - 1), "r"(((sof >> 12) & 1) + 1) : "memory");
    if (w == 1) PROF_G(1);
    gof = c * 8192 + lds1(sb + Q_SEL + 4 * c);
  }
  asm volatile("barrier.cluster.wait.aligned;" ::: "memory");
  return __shfl_sync(0xffffffffu, gof, 0);
}
template <bool ISV>
__device__ __forceinline__ void next_state(uint32_t sb, const Params& P, uint32_t sof, uint32_t gof, uint32_t dly, int w, int t) {
  const int lane = rd_lane(), c = gof >> 13;
  const uint4* src = (const uint4*)((char*)P.memx + (sof ^ (t & 1) * 2048)) + lane;
  uint32_t* dst = (uint32_t*)((char*)P.memx + c * 8192 + word_of(lane, rd_cid()) + (~t & 1) * 2048);
  const bool inj = t == LAG && (lane & 8);
  st_gpu1_if(inj, dst, lds1(sb + Q_M0 + w * 128 + lane * 4));
  asm volatile("" : "+l"(dst), "+l"(src));
  mbar_wait(sb + B_REF, (t - 1) & 1);
  uint32_t when = lds1(sb + Q_REF) + dly;
  uint4 v[4];
  wait_ns(when - (CALIB == 1 ? t % 10 * 28 : 0));
  PROF_W(w == 1, 18);
  const uint32_t nr = poll4<true>(v, src, (t - 1) >> 1);
  PROF_T(25 + w);
  const uint32_t z = bf2_add(bf2_add(v[0].z, v[1].z), bf2_add(v[2].z, v[3].z)), u = bf2_add(bf2_add(v[0].w, v[1].w), bf2_add(v[2].w, v[3].w));
  const uint32_t x = bf2_add(bf2_add(v[0].x, v[1].x), bf2_add(v[2].x, v[3].x)), y = bf2_add(bf2_add(v[0].y, v[1].y), bf2_add(v[2].y, v[3].y));
  const uint32_t x2 = bf2_add(bf2_add(x, 0), __shfl_xor_sync(0xffffffffu, z, 16)), y2 = bf2_add(y, __shfl_xor_sync(0xffffffffu, u, 16));
  const uint32_t x3 = bf2_add(x2, __shfl_xor_sync(0xffffffffu, y2, 8));
  st_gpu1_if(!inj, dst, bf2_add(x3, __shfl_xor_sync(0xffffffffu, x3, 4)));
  if (ISV && w == 3) bar_arrive<12, 160>();
  PROF_T(28 + w);
  PROF_A(9 + w, nr);
  if (!ISV && w == 3) bar_sync<7, 64>();
  wait_ns(when + D_GX + (t == 1 ? GS_V : 0) - (CALIB == 2 ? t % 10 * 28 : 0));
  if (elect_one()) bulk_g2s_mc(sb + Q_X + c * Q_CS, (const char*)P.memx + gof + (~t & 1) * 2048, 2048, sb + B_CP + 8 * c, 7);
  __syncwarp();
  if (w == 1) PROF_T(21);
  st_gpu1((uint32_t*)((uintptr_t)dst ^ 2048), SENT);
}
__device__ __forceinline__ void service_v(uint32_t sb, const Params& P) {
  const int w = rd_warp() & 3, head = __shfl_sync(0xffffffffu, rd_cid(), 0);
  uint32_t sof, g0 = 0, c0 = 0, ref = 0;
  const uint32_t gof = service_setup(sb, P, 2, w, sof);
#pragma unroll 1
  for (int t = 1; t <= NT; t++) {
    const int lane = rd_lane();
    if (w == 0) {
      if (t < NT) mbar_wait(sb + B_XF, t & 1); else warp_flag_wait(g_flags + FL_XS + NT * 32 + 16, 4);
      if (t < NT) bar_sync<13, 64>();
#pragma unroll 1
      for (int l = 0; l < 2; l++) {
        mbar_wait(sb + B_OXREADY + 88 * l, (t - 1) & 1);
        if (elect_one()) {
          if (l ? t > LAG : t <= NSEG) bulk_s2g(g_ox + (size_t)(t & (OXRING - 1)) * 32768 + l * 16384 + head * 512, sb + Q_OX + l * 8192, 8192);
          bulk_commit_wait();
          flag_add_done(g_flags + FL_OX + t * 32 + head);
        }
        __syncwarp();
        if (l == 0) PROF_T(24);
      }
      mbar_arrive_if0(lane, sb + B_OXFREE);
      PROF_T(25);
      continue;
    }
    if (t > 1) check_tiles<3>(sb, P, w - 1, t); else mbar_arrive_if0(lane, sb + B_E + 24);
    if (t == NT) break;
    if (w == 1) {
      const uint32_t due = ref + D_GX + D_DUE * 9 / 16;
      const uint32_t g1 = next_tick(), c1 = rd_clock();
      const uint32_t rate = t > 1 ? __float2uint_rn(65536.f * (g1 - g0) * rcp(c1 - c0)) : 36400;
      g0 = g1; c0 = c1;
      uint4* pub = P.memx + 9 * 512 + (lane & 1) * 256 + (lane & 2) * 16 + head;
      const uint32_t lead = D_RED * rate >> 16, late = D_LATE * rate >> 16, r1 = rank_delay(1) * rate >> 10, r0 = rank_delay(0) * rate >> 10;
      mbar_wait(sb + B_E, (t - 1) & 1);
      PROF_T(4);
      mbar_spin(sb + B_E + 24, (t - 1) & 1);
      uint32_t now = g0 + ((rd_clock() - c0) * rate >> 16);
      now = (now + (t < 3 ? lead + (t == 1 ? ST1_V : ST0_V) : (int)(now + 90 - due) > 0 ? late : lead)) << 6;
      st_gpu4(pub, ((now + r0) & ~255u) | t, ((now + r1) & ~255u) | t, (now & ~255u) | t, 0);
      PROF_T(22);
      PROF_V(true, 1, now >> 6);
      read_reference(sb, P, ref, 2, t);
    }
    if (w == 2) {
      mbar_wait(sb + B_SM, (t - 1) & 1);
      mbar_rarrive_if0(lane >> 1, mapa(sb + B_AN, lane & 1));
      bar_sync<5, 160>();
      fence_async_smem();
      if (elect_one()) {
        bulk_s2s(mapa(sb + Q_OB, 1), sb + Q_OB, 4096, mapa(sb + B_O, 1));
        bulk_s2s(mapa(sb + Q_OB, 0), sb + Q_OB, 4096, mapa(sb + B_O, 0));
      }
      __syncwarp();
    }
    if (w == 3) PROF_MID();
    next_state<true>(sb, P, sof, gof, tile_delay(2, w - 1), w, t);
    if (w == 3) bar_arrive<13, 64>();
  }
  cluster_sync();
}
__device__ __forceinline__ void service_qk(uint32_t sb, const Params& P) {
  const int rank = rd_rank(), w = rd_warp() & 3;
  uint32_t sof;
  const uint32_t gof = service_setup(sb, P, rank, w, sof);
#pragma unroll 1
  for (int t = 0;; t++) {
    const int lane = rd_lane();
    if (w == 0 && rank == 0 && t < NT) {
      const uint32_t* fl = g_flags + FL_XS + t * 32;
      warp_flag_wait(fl + (lane & 1 ? (t >= LAG ? 16 : 0) : (t <= NSEG ? 0 : 16)), 4);
      fence_async_global();
      const char* src = (const char*)g_xs + (size_t)t * 73728;
      if (t > 0) mbar_wait(sb + B_E, (t - 1) & 1);
      PROF_T(24);
      uint32_t at = rd_clock();
#pragma unroll 1
      for (int k = 0; k < 9; k++) {
        if (elect_one()) bulk_g2s_mc(sb + Q_X + 3072 + k * Q_CS, src + 1024 + k * 8192, 7168, sb + B_XF + 8 * k, 7);
        __syncwarp();
        at += t ? XP_V : 0;
        spin_until(at);
      }
      if (t == 0) PROF_G(31);
    }
    if (t == 0) continue;
    softmax_x(sb, w, rank, t);
    if (t == NT) break;
    if (w == 0) bar_arrive<7, 64>();
    mbar_expect_if0(lane | (w - 1), sb + B_SM, SX_BYTES);
    if (w == 3) PROF_MID();
    if (w) next_state<false>(sb, P, sof, gof, tile_delay(rank, w - 1), w, t);
  }
  cluster_sync();
}

__global__ void __cluster_dims__(3, 1, 1) __launch_bounds__(512, 1) head_kernel(const __grid_constant__ Params P) {
  extern __shared__ uint8_t smem_raw[];
  const uint32_t sb = (uint32_t)__cvta_generic_to_shared(smem_raw);
  if ((sb & 0xFFFFFFu) != SB0) __trap();
  asm volatile("griddepcontrol.launch_dependents;");
  if (threadIdx.x < 96) {
    const int i = blockIdx.x * 24 + threadIdx.x % 24, m = threadIdx.x / 24;
    const __nv_bfloat16* p = m == 3 ? P.ssm_k + (size_t)(i >> 2) * SEQ + (i & 3) * 64 : (m == 0 ? P.ck : m == 1 ? P.cv : P.x0) + (size_t)i * 64;
    asm volatile("prefetch.global.L2 [%0];" :: "l"(p));
  } else if (threadIdx.x == 96 && blockIdx.x < 45) {
    asm volatile("prefetch.global.L2 [%0];" :: "l"(blockIdx.x < 36 ? P.shift + blockIdx.x * 64 : P.ssm_d + (blockIdx.x - 36) * 64));
  } else if (threadIdx.x == 97 && blockIdx.x < 72) {
    asm volatile("prefetch.global.L2 [%0];" :: "l"(P.mem0 + blockIdx.x * 64));
  }
  PROF_BEGIN();
  if (threadIdx.x == 416) sts1(sb + Q_SET, (__ldcg(&g_epoch) & 1) * FL_TOTAL);
  const int rank = rd_rank(), wg = rd_warp() >> 2;
  if (threadIdx.x == 448) {
    for (int c = 0; c < 9; c++) { mbar_init(sb + B_CP + 8 * c, 1); mbar_arrive(sb + B_CP + 8 * c); mbar_init(sb + B_OK + 8 * c, 1); mbar_arrive(sb + B_OK + 8 * c); mbar_init(sb + B_XF + 8 * c, 1); mbar_expect(sb + B_XF + 8 * c, 7168); }
    mbar_init(sb + B_E, 6); mbar_init(sb + B_G0, 1); mbar_expect(sb + B_G0, 9216); mbar_init(sb + B_E + 16, 6); mbar_init(sb + B_E + 24, 7);
    mbar_init(sb + B_SM, rank == 2 ? 1 : 2); mbar_init(sb + B_O, 1); mbar_init(sb + B_P, 1); mbar_init(sb + B_P + 8, 1);
    mbar_init(sb + B_REF, 1); mbar_init(sb + B_RES, 1); mbar_init(sb + B_PZ, 1); mbar_init(sb + B_AN, 1); mbar_init(sb + B_OXREADY, 4); mbar_init(sb + B_OXREADY + 88, 4); mbar_init(sb + B_OXFREE, 1);
    mbar_expect(sb + B_SM, rank == 2 ? SM_BYTES : SX_BYTES); mbar_expect(sb + B_P, PX_BYTES); mbar_expect(sb + B_P + 8, PX_BYTES);
    mbar_expect(sb + B_O, 4096);
    sts1(sb + Q_SEL + 48, 0);
    asm volatile("fence.mbarrier_init.release.cluster;" ::: "memory");
  }
  __syncthreads();
  PROF_G(6);
  if (wg < 2) {
    asm volatile("setmaxnreg.inc.sync.aligned.u32 176;");
    head_main(sb, P);
    PROF_END();
  } else if (wg == 2) {
    asm volatile("setmaxnreg.dec.sync.aligned.u32 120;");
    head_aux(sb, P);
    PROF_END();
  } else {
    asm volatile("setmaxnreg.dec.sync.aligned.u32 40;");
    if (rank == 2) service_v(sb, P); else service_qk(sb, P);
    PROF_END();
  }
}

__device__ __forceinline__ void tail_gemm(uint32_t sb, const Params& P) {
  const int lane = threadIdx.x & 31, warp = rd_warp(), w = warp & 3, wg = warp >> 2, tid = threadIdx.x & 127;
  uint32_t a[4 * W_KR];
  fence_async_smem();
  if (elect_one()) {
#pragma unroll 1
    for (int k = w; k < 32; k += 4)
      tma_box(k < W_KR ? sb + wg * 65536 + k * 2048 : sb + W_WS + wg * 6144 + (k - W_KR) * 2048, &P.tm, (blockIdx.x % 3) * 192 + wg * 64, (blockIdx.x / 3) * 512 + k * 16, sb + B_WT + 8 * wg);
  }
  __syncwarp();
  mbar_wait(sb + B_WT + 8 * wg, 0);
  load_afrags<W_KR>(a, sb + wg * 65536, w, lane);
  fence_async_smem();
  bar_sync<1, 416>();
  PROF_G(26);
  if (wg == 2) bar_arrive<2, 256>();
  const uint64_t dw = P.d_ws + wg * 384;
  uint2* dst0 = g_acc + ((blockIdx.x % 3) * 12 + warp) * 32 + lane;
#pragma unroll 1
  for (int t = 1; t <= NT; t++) {
#pragma unroll 1
    for (int l = t > NSEG; l <= (t > LAG); l++) {
      const int seg = t - 1 - l * LAG, grp = (seg & 1) * 2 + l;
      const uint64_t db = P.d_ring + grp * 2048;
      float acc[16];
      bar_sync_r(2 + wg, 256);
#pragma unroll
      for (int c = 0; c < 4; c++) {
        if (wg == 0) mbar_wait(sb + B_FULL + 32 * grp + 8 * c, (seg >> 1) & 1);
        if (c == 0) PROF_T(6 * l + wg);
        wg_fence();
#pragma unroll
        for (int i = 0; i < 8; i++) {
          if (c == 0 && i == 0) wg_rs<0, 1>(acc, a, db, 0);
          else if (8 * c + i < W_KR) wg_rs<1, 1>(acc, a + 32 * c + 4 * i, db, 512 * c + 64 * i);
          else wg_ss<1, 1>(acc, dw, 128 * (8 * c + i - W_KR), db, 512 * c + 64 * i);
        }
      }
      wg_commit();
      bar_arrive_r(wg == 2 ? 2 : 3 + wg, 256);
      wg_wait<0>();
      reg_fence(acc);
      mbar_arrive_if0(tid, sb + B_EMPTY + 8 * grp);
      uint2* dst = dst0 + (size_t)(l * 256 + seg * 4) * 1152;
#pragma unroll
      for (int j = 0; j < 4; j++)
        asm volatile("red.relaxed.gpu.global.add.noftz.v2.bf16x2 [%0], {%1,%2};" :: "l"(dst + j * 1152),
                     "r"(pack_bf16(acc[4 * j], acc[4 * j + 1])), "r"(pack_bf16(acc[4 * j + 2], acc[4 * j + 3])) : "memory");
      bar_sync_r(5 + wg, 160);
    }
  }
}
__device__ __forceinline__ void tail_service(uint32_t sb) {
  const int lane = threadIdx.x & 31, warp = rd_warp();
  if (warp == 12) bar_sync<1, 416>();
#pragma unroll 1
  for (int t = 1; t <= NT; t++) {
    if (warp == 12) {
      const int h0 = (blockIdx.x / 3) * 4;
#pragma unroll 1
      for (int l = t > NSEG; l <= (t > LAG); l++) {
        warp_flag_wait(g_flags + FL_OX + t * 32 + h0 + (lane & 3), l + 1);
        fence_async_global();
        const int seg = t - 1 - l * LAG, grp = (seg & 1) * 2 + l;
        const uint4* src = g_ox + (size_t)(t % OXRING) * 32768 + l * 16384 + h0 * 512;
        const uint32_t bar = sb + B_FULL + 32 * grp;
        mbar_wait_lim(sb + B_EMPTY + 8 * grp, ((seg >> 1) & 1) ^ 1);
        mbar_expect_if0(lane > 3, bar + 8 * lane, 8192);
        if (elect_one()) {
#pragma unroll
          for (int j = 0; j < 4; j++) bulk_g2s(sb + W_RING + (grp * 4 + j) * 8192, src + j * 512, 8192, bar + 8 * j);
        }
        __syncwarp();
      }
      PROF_T(12);
      PROF_MID();
    } else {
#pragma unroll 1
      for (int l = t > NSEG; l <= (t > LAG); l++) {
        bar_sync_r(warp - 8, 160);
        if (lane == 0) flag_add(g_flags + FL_ACC + (l * 64 + t - 1 - l * LAG) * 32);
        __syncwarp();
        PROF_T(6 * l + warp - 10);
      }
    }
  }
}

__device__ __forceinline__ void wait_k1(uint32_t sb, int n) {
  uint32_t c = 0;
  while ((int)lds1(sb + W_K1) < n) {
    __nanosleep(64);
    if (++c > SPIN_LIMIT) __trap();
  }
}
__device__ __forceinline__ void tail_finisher(uint32_t sb, const Params& P) {
  const int lane = threadIdx.x & 31, warp = rd_warp(), kind = warp < 12 ? warp / 6 : warp & 1, f = warp - 6 * kind, tg = blockIdx.x & 3;
  if (warp >= 14) {
    const uint32_t set = lds1(sb + Q_SET), ft = sb + W_FO + kind * 576;
    if (tg == 0) for (int i = kind * 32 + lane; i < FL_TOTAL; i += 64) g_flagsets[FL_TOTAL - set + i] = 0;
#pragma unroll 1
    for (int t = 0; t < NSEG; t++) {
      warp_flag_wait(g_flags + FL_ACC + (64 + t) * 32, 72);
      PROF_T(17);
      if (t == 0 && tg == 0 && threadIdx.x == 448) g_epoch = set ? 0 : 1;
      const uint2* ac = g_acc + ((size_t)(256 + t * 4 + tg) * 36 + kind * 18) * 32 + lane;
      uint2 v[18];
#pragma unroll
      for (int i = 0; i < 18; i++) v[i] = __ldcg(ac + i * 32);
#pragma unroll
      for (int i = 0; i < 9; i++) {
        const uint4 r = lds4(sb + W_RS + (8 + (t & 7)) * 9216 + (kind * 9 + i) * 512 + lane * 16);
        stsm4t(ft + (lane & 7) * 1168 + (lane >> 3) * 16 + 64 * i, bf2_add(r.x, v[2 * i].x), bf2_add(r.y, v[2 * i].y), bf2_add(r.z, v[2 * i + 1].x), bf2_add(r.w, v[2 * i + 1].y));
      }
      fence_async_smem();
      __syncwarp();
      mbar_arrive_if0(lane, sb + B_RF + 8 * (t & 7));
      wait_k1(sb, min(t + LAG + 1, NSEG));
      if (lane < 8) {
        bulk_s2g(P.out + (size_t)((t * 4 + tg) * 8 + lane) * DM + kind * 288, ft + lane * 1168, 576);
        bulk_commit_wait();
      }
      __syncwarp();
      PROF_T(18);
    }
    return;
  }
  if (warp >= 12) {
    for (int i = kind * 32 + lane; i < 576; i += 64) sts4(sb + W_Z + i * 16, make_uint4(0, 0, 0, 0));
    fence_async_smem();
    bar_sync<12, 64>();
#pragma unroll 1
    for (int t = -1; t <= NSEG; t++) {
      if (kind == 0 && t + 1 < NSEG) {
        const uint32_t bar = sb + B_FT + 8 * ((t + 1) & 1);
        mbar_expect_if0(lane, bar, 9216);
        __syncwarp();
        if (lane < 8) bulk_g2s(sb + W_FT + ((t + 1) & 1) * 9344 + lane * 1168, P.x0 + (size_t)(((t + 1) * 4 + tg) * 8 + lane) * DM, 1152, bar);
      }
      if (t < 0) continue;
      if (t < NSEG) bar_sync_r(9 + 2 * kind, 224);
      if (lane == 0) {
        flag_add(g_flags + FL_XS + (t + kind * LAG) * 32 + kind * 16);
        if (kind) { sts1(sb + W_K1, t + 1); PROF_T(14); }
        if (kind ? t < NSEG : t < LAG) bulk_s2g(g_acc + (size_t)(kind * 256 + t * 4 + tg) * 1152, sb + W_Z, 9216);
        if (kind && t + LAG < NSEG) bulk_s2g(g_acc + (size_t)((t + LAG) * 4 + tg) * 1152, sb + W_Z, 9216);
        bulk_commit_wait();
      }
      __syncwarp();
      if (kind) PROF_MID();
    }
    return;
  }
  const uint32_t BF_1 = 0x3F803F80u;
  const uint32_t* ys = (const uint32_t*)(g_y + ((tg >> 1) * DM + f * 96 + (lane >> 2)) * 2 + (tg & 1)) + (lane & 3);
  const uint32_t rs = sb + W_RS + f * 1536 + lane * 16;
  uint32_t y[12] = {};
#pragma unroll 1
  for (int t = 0; t < NSEG; t++) {
    uint32_t x[12];
    if (kind == 0) {
      wait_k1(sb, t - 6);
      mbar_wait(sb + B_FT + 8 * (t & 1), (t >> 1) & 1);
#pragma unroll
      for (int i = 0; i < 3; i++)
        ldsm4t(x[4 * i], x[4 * i + 1], x[4 * i + 2], x[4 * i + 3], sb + W_FT + (t & 1) * 9344 + (lane & 7) * 1168 + f * 192 + (lane >> 3) * 16 + 64 * i);
    } else {
      warp_flag_wait(g_flags + FL_ACC + t * 32, 72);
      PROF_T(13);
#pragma unroll
      for (int i = 0; i < 6; i++) {
        const uint2 v = __ldcg(g_acc + ((size_t)(t * 4 + tg) * 36 + f * 6 + i) * 32 + lane);
        x[2 * i] = v.x; x[2 * i + 1] = v.y;
      }
#pragma unroll
      for (int i = 0; i < 3; i++) {
        const uint4 r = lds4(rs + (t & 7) * 9216 + i * 512);
        x[4 * i] = bf2_add(x[4 * i], r.x); x[4 * i + 1] = bf2_add(x[4 * i + 1], r.y); x[4 * i + 2] = bf2_add(x[4 * i + 2], r.z); x[4 * i + 3] = bf2_add(x[4 * i + 3], r.w);
      }
      mbar_wait(sb + B_RF + 8 * (t & 7), ((t >> 3) & 1) ^ 1);
      PROF_T(15);
    }
    {
      if (t == 0) PROF_G(27);
#pragma unroll 1
      for (int pass = 0; pass < 2; pass++) {
        float g[2][4] = {};
#pragma unroll
        for (int i = 0; i < 12; i++) {
          uint32_t u;
          asm volatile("movmatrix.sync.aligned.m8n8.trans.b16 %0, %1;" : "=r"(u) : "r"(x[i]));
          mma1688(g[i & 1], u, BF_1, u);
        }
        const uint32_t st = sb + W_ST + kind * 1024 + pass * 512 + (lane & 3) * 16;
        if ((lane >> 3) == (lane & 3))
          asm volatile("st.shared.v2.f32 [%0], {%1,%2};" :: "r"(st + f * 64 + (lane & 4) * 2), "f"(lane & 4 ? g[0][3] + g[1][3] : g[0][2] + g[1][2]),
                       "f"(lane & 4 ? g[0][1] + g[1][1] : g[0][0] + g[1][0]) : "memory");
        bar_sync_r(8 + 2 * kind, 192);
        float s0 = 0.f, s1 = 0.f, q0 = 0.f, q1 = 0.f;
        if (kind && pass == 0) PROF_T(19);
        if (kind && pass == 1) PROF_T(21);
#pragma unroll
        for (int i = 0; i < 6; i++) {
          const float4 e = lds4f(st + i * 64);
          s0 += e.x; q0 += e.y; s1 += e.z; q1 += e.w;
        }
        s0 *= 1.f / 576.f; s1 *= 1.f / 576.f;
        const float v0 = fmaf(q0, 1.f / 576.f, -s0 * s0), v1 = fmaf(q1, 1.f / 576.f, -s1 * s1);
        const uint32_t nmean = pack_bf16(-s0, -s1), vb = pack_bf16(fmaxf(v0, 0.f), fmaxf(v1, 0.f));
        const uint32_t ve = pack_bf16(bf_lo(vb) + 1e-5f, bf_hi(vb) + 1e-5f), sd = pack_bf16(sqr(bf_lo(ve)), sqr(bf_hi(ve)));
        const float r0 = rcp(bf_lo(sd)), r1 = rcp(bf_hi(sd));
        const uint32_t rh = pack_bf16(r0, r1), rl = pack_bf16(r0 - bf_lo(rh), r1 - bf_hi(rh));
        if (pass == 0 && (t == 0 || t == 4 * CT_A || t == 4 * CT_B || t == 4 * CT_C)) {
          if (t == 0) PROF_G(25);
          warp_flag_wait(g_flags + FL_Y + t * 8, t < 4 * CT_B ? 32 : DM);
          if (t == 0) PROF_G(26);
#pragma unroll
          for (int i = 0; i < 12; i++) y[i] = __ldcg(ys + t * (DM * 16) + i * 64);
        }
        uint32_t* xd = (uint32_t*)(g_xs + (size_t)(t + kind * LAG) * 4608 + (kind * 4 + tg) * 64 + (f * 3 >> 1) * 512 + (f & 1) * 32) + lane;
#pragma unroll
        for (int i = 0; i < 12; i++) {
          const uint32_t d = bf2_add(x[i], nmean), q = bf2_op(d, rh, bf2_mul(d, rl));
          if (pass == 0) x[i] = bf2_add(x[i], bf2_mul(q, y[i]));
          else xd[i < 4 ? i * 32 : i < 8 ? i * 32 + (f & 1) * 1792 : i * 32 + 1792] = q;
        }
        if (pass == 0) {
#pragma unroll
          for (int i = 0; i < 3; i++) sts4(rs + (kind * 8 + (t & 7)) * 9216 + i * 512, make_uint4(x[4 * i], x[4 * i + 1], x[4 * i + 2], x[4 * i + 3]));
        }
        if (kind && pass == 0) PROF_T(20);
        if (kind && pass == 1) PROF_T(22);
      }
      if (kind) PROF_T(16);
      if (t < 3) PROF_G(28 + t);
      bar_sync_r(9 + 2 * kind, 224);
#pragma unroll
      for (int i = 0; i < 12; i++) y[i] = __ldcg(ys + ((t + 1) & 63) * (DM * 16) + i * 64);
    }
  }
}

template <int NP, typename V>
__device__ __forceinline__ void kv_block(uint4 (&o)[2 * NP], const Params& P, int r0, int c0) {
  V kk[11], vv[8];
  uint4 sw[NP];
#pragma unroll
  for (int i = 0; i < NP; i++) sw[i] = __ldg((const uint4*)(P.shift + (c0 + 2 * i) * 4));
#pragma unroll
  for (int i = 0; i < 11; i++) kk[i] = r0 + i >= 3 ? __ldg((const V*)(P.ck + (size_t)(r0 + i - 3) * DM + c0)) : V{};
#pragma unroll
  for (int i = 0; i < 8; i++) vv[i] = __ldg((const V*)(P.cv + (size_t)(r0 + i) * DM + c0));
#pragma unroll
  for (int cp = 0; cp < NP; cp++) {
    const uint32_t wt[4] = {__byte_perm(sw[cp].y, sw[cp].w, 0x7632), __byte_perm(sw[cp].y, sw[cp].w, 0x5410),
                            __byte_perm(sw[cp].x, sw[cp].z, 0x7632), __byte_perm(sw[cp].x, sw[cp].z, 0x5410)};
    uint32_t e[8];
#pragma unroll
    for (int i = 0; i < 8; i++) {
      uint32_t a = bf2_mul(((const uint32_t*)&kk[i])[cp], wt[0]);
#pragma unroll
      for (int j = 1; j < 4; j++) a = bf2_add(a, bf2_mul(((const uint32_t*)&kk[i + j])[cp], wt[j]));
      e[i] = bf2_mul(a, ((const uint32_t*)&vv[i])[cp]);
    }
    o[2 * cp] = make_uint4(__byte_perm(e[0], e[1], 0x5410), __byte_perm(e[2], e[3], 0x5410), __byte_perm(e[4], e[5], 0x5410), __byte_perm(e[6], e[7], 0x5410));
    o[2 * cp + 1] = make_uint4(__byte_perm(e[0], e[1], 0x7632), __byte_perm(e[2], e[3], 0x7632), __byte_perm(e[4], e[5], 0x7632), __byte_perm(e[6], e[7], 0x7632));
  }
}
__device__ __forceinline__ void kv_task(const Params& P, int id) {
  const int lane = threadIdx.x & 31, tq = id / 9, c0 = (id % 9) * 64 + (lane >> 2) * 8;
  uint4 o[8];
  kv_block<4, uint4>(o, P, tq * 32 + (lane & 3) * 8, c0);
#pragma unroll
  for (int c = 0; c < 8; c++) g_kv[((size_t)tq * DM + c0 + c) * 4 + (lane & 3)] = o[c];
}
__device__ __forceinline__ int next_job(uint32_t sb) {
  int j = 0;
  if ((threadIdx.x & 31) == 0) j = atomicAdd(g_flags + FL_KV + 96, 1);
  return __shfl_sync(0xffffffffu, j, 0);
}
__device__ __forceinline__ uint2 lds2_ro(uint32_t a) { uint2 v; asm("ld.shared.v2.u32 {%0,%1}, [%2];" : "=r"(v.x), "=r"(v.y) : "r"(a)); return v; }

template <int T0, int T1>
__device__ __forceinline__ void conv_job(uint32_t sb, const Params& P, int ch, int sets = 1) {
  const int lane = threadIdx.x & 31, w = threadIdx.x >> 5;
  uint32_t ub = sb + w * C_CH, zb = ub + C_U;
  constexpr int NL = (T1 + 1) / 2, NS = T0 == 0 ? 2 : 1;
  constexpr bool CTA = T1 <= CT_B;
  static_assert(T0 > 0 || T1 == 2, "second set: buffer offsets, warps");
  PROF_G(13 + 4 * (T0 == 0 ? 0 : T0 == CT_A ? 1 : 2));
  uint2 q[NS][T1];
  uint32_t dd[NS];
#pragma unroll
  for (int n = 0; n < NS; n++) {
    const int c = n < sets ? ch - n * 128 : ch;
#pragma unroll
    for (int u = 0; u < T1; u++) q[n][u] = __ldg((const uint2*)(P.ssm_k + (size_t)c * SEQ) + u * 32 + lane);
    dd[n] = (uint32_t)__bfloat16_as_ushort(P.ssm_d[c]) * 0x10001u;
  }
  if (CTA) {
#pragma unroll
    for (int tq = w; tq < 4 * T1 * sets; tq += 16) {
      uint4 o[2];
      const int n = T0 == 0 ? tq >> 3 : 0, tgp = (tq - 8 * n) * 4 + (lane & 3), c0 = (lane >> 2) * 2;
      kv_block<1, uint32_t>(o, P, tgp * 8, ch - w + c0 - n * 128);
#pragma unroll
      for (int c = 0; c < 2; c++) {
        sts4(sb + (c0 + c) * C_CH + n * 2048 + 256 + tgp * 16, o[c]);
        if (T0) g_kv[((size_t)tq * DM + ch - w + c0 + c) * 4 + (lane & 3)] = o[c];
      }
    }
    __syncwarp();
  } else {
    uint4 o[NL];
#pragma unroll
    for (int u = 0; u < NL; u++) o[u] = __ldcg(g_kv + ((size_t)(u * 8 + (lane >> 2)) * DM + ch) * 4 + (lane & 3));
#pragma unroll
    for (int u = 0; u < NL; u++) sts4(ub + 256 + (u * 32 + lane) * 16, o[u]);
  }
#pragma unroll
  for (int n = 0; n < NS; n++) {
    if (lane < 16) { sts4(ub + n * 2048 + lane * 16, make_uint4(0, 0, 0, 0)); sts1(zb + n * 4096 + lane * 4, 0); }
#pragma unroll
    for (int u = 0; u < T1; u++) {
      const uint2 k = q[n][u];
      const uint32_t pv = __shfl_sync(0xffffffffu, lane == 31 ? (u ? q[n][u ? u - 1 : 0].y : 0u) : k.y, (lane + 31) & 31);
      sts4(zb + n * 4096 + 64 + (u * 32 + lane) * 16, make_uint4(__byte_perm(k.x, pv, 0x7610), __byte_perm(k.x, k.x, 0x1032),
                                                                __byte_perm(k.y, k.x, 0x7610), __byte_perm(k.y, k.y, 0x1032)));
    }
  }
  if (CTA) __syncthreads(); else __syncwarp();
  PROF_G(14 + 4 * (T0 == 0 ? 0 : T0 == CT_A ? 1 : 2));
#pragma unroll 1
  for (int n = 0; n < sets; n++, ub += 2048, zb += 4096) {
    float acc[T1 - T0][4];
#pragma unroll
    for (int i = 0; i < T1 - T0; i++) acc[i][0] = acc[i][1] = acc[i][2] = acc[i][3] = 0.f;
#pragma unroll(T0 == 0 ? 4 : 1)
    for (int r = 0; r < 8; r++) {
      uint2 b[T1];
      uint32_t ba = ub + 256 - r * 32 + lane * 8, zp = zb + 64 + (16 * r + 2 * (lane >> 2) - 4 * (lane & 3)) * 4;
      asm volatile("" : "+r"(zp), "+r"(ba) :: "memory");
#pragma unroll
      for (int i = 0; i < T1; i++) b[i] = lds2_ro(ba + i * 256);
#pragma unroll
      for (int mu = 0; mu < T1; mu++) {
        const uint2 a01 = lds2_ro(zp + 512 * mu), a23 = lds2_ro(zp + 512 * mu - 8);
#pragma unroll
        for (int i = (mu > T0 ? mu : T0); i < T1; i++) mma16816(acc[i - T0], a01.x, a01.y, a23.x, a23.y, b[i - mu].x, b[i - mu].y);
      }
    }
    PROF_G(15 + 4 * (T0 == 0 ? 0 : T0 == CT_A ? 1 : 2));
#pragma unroll
    for (int i = 0; i < T1 - T0; i++)
#pragma unroll
      for (int e = 0; e < 2; e++) {
        const int col = (T0 + i) * 8 + 2 * (lane & 3) + e;
        ((uint32_t*)g_y)[((size_t)col * DM + ch - n * 128) * 8 + (lane >> 2)] =
            bf2_add(pack_bf16(acc[i][e], acc[i][2 + e]), bf2_mul(lds1(ub + 256 + col * 32 + (lane >> 2) * 4), n ? dd[NS - 1] : dd[0]));
      }
  }
  if (CTA) __syncthreads(); else __syncwarp();
  PROF_G(16 + 4 * (T0 == 0 ? 0 : T0 == CT_A ? 1 : 2));
  if (CTA ? threadIdx.x == 480 && (T0 == 0 || ch < 512) : lane == 0) flag_add(g_flags + FL_Y + T0 * 32);
  __syncwarp();
}

__global__ void __launch_bounds__(512, 1) tail_kernel(const __grid_constant__ Params P) {
  extern __shared__ uint8_t smem_raw[];
  const uint32_t sb = (uint32_t)__cvta_generic_to_shared(smem_raw);
  if (sb != SB0) __trap();
  PROF_BEGIN();
  if (threadIdx.x == 0) {
    for (int c = 0; c < 16; c++) mbar_init(sb + B_FULL + 8 * c, 1);
    for (int c = 0; c < 4; c++) mbar_init(sb + B_EMPTY + 8 * c, 3);
    for (int c = 0; c < 2; c++) mbar_init(sb + B_FT + 8 * c, 1);
    for (int c = 0; c < 8; c++) mbar_init(sb + B_RF + 8 * c, 2);
    for (int c = 0; c < 3; c++) { mbar_init(sb + B_WT + 8 * c, 1); mbar_expect(sb + B_WT + 8 * c, 65536); }
    sts1(sb + W_K1, 0);
    sts1(sb + Q_SET, (__ldcg(&g_epoch) & 1) * FL_TOTAL);
    fence_async_smem();
  }
  const int b = blockIdx.x, w = threadIdx.x >> 5;
  if ((b >> 2) == 6) {
    __syncthreads();
  } else {
    conv_job<0, CT_A>(sb, P, b * 16 + w, b < 32 ? 1 : 2);
    PROF_G(3);
#pragma unroll 1
    for (int g = b; g == b || (g >> 2) == 6; g -= 8) conv_job<CT_A, CT_B>(sb, P, g * 16 + w);
    PROF_G(4);
    if (b >= 28) {
      constexpr int KV0 = 36 * CT_B, KV1 = KV0 + 192, NK = 576 - KV1;
      const int lane = threadIdx.x & 31;
      auto draw = [&]() {
        const int j = next_job(sb), ch = j < DM ? j : j - DM - NK;
        if (ch >= 0 && ch < DM && lane < (j < DM ? 2 * CT_C : 32)) asm volatile("prefetch.global.L2 [%0];" :: "l"(P.ssm_k + (size_t)ch * SEQ + lane * 64));
        return j;
      };
      int job = draw();
#pragma unroll 1
      for (int k = KV0 + (b - 28) * 16 + w; b < 32 && k < KV1; k += 64) {
        kv_task(P, k);
        __syncwarp();
        if (lane == 0) flag_add(g_flags + FL_KV);
      }
      warp_flag_wait(g_flags + FL_Y + CT_A * 32, 32);
      warp_flag_wait(g_flags + FL_KV, 192);
      spin_until(rd_clock() + (w >> 2) * DP_V);
#pragma unroll 1
      while (job < DM) { const int nx = draw(); conv_job<CT_B, CT_C>(sb, P, job); job = nx; }
      PROF_G(6);
#pragma unroll 1
      while (job < DM + NK) {
        const int nx = draw();
        kv_task(P, job - DM + KV1);
        __syncwarp();
        if (lane == 0) flag_add(g_flags + FL_KV + 32);
        job = nx;
      }
      warp_flag_wait(g_flags + FL_KV + 32, NK);
#pragma unroll 1
      while (job < 2 * DM + NK) { const int nx = draw(); conv_job<CT_C, 16>(sb, P, job - DM - NK); job = nx; }
      PROF_G(5);
      PROF_END();
      return;
    }
    __syncwarp();
  }
  if (blockIdx.x >= 24) {
    PROF_G(24);
    tail_finisher(sb, P);
    PROF_END();
    asm volatile("griddepcontrol.wait;" ::: "memory");
  } else if (rd_warp() < 12) {
    asm volatile("setmaxnreg.inc.sync.aligned.u32 160;");
    tail_gemm(sb, P);
    PROF_END();
  } else {
    asm volatile("setmaxnreg.dec.sync.aligned.u32 32;");
    tail_service(sb);
    PROF_END();
  }
}

}

extern "C" void kernel_launch(void* const* d_in, const int* in_sizes, int n_in, void* d_out, int out_size) {
  typedef const __nv_bfloat16* bp;
  Params P;
  P.x0 = (bp)d_in[0]; P.ck = (bp)d_in[1]; P.cv = (bp)d_in[2]; P.shift = (bp)d_in[3]; P.ssm_k = (bp)d_in[4]; P.ssm_d = (bp)d_in[5];
  P.mem0 = (bp)d_in[7]; P.wq = (bp)d_in[8]; P.wk = (bp)d_in[9]; P.wv = (bp)d_in[10]; P.wo = (bp)d_in[11];
  P.out = (__nv_bfloat16*)d_out;
  typedef CUresult (*Encode)(CUtensorMap*, CUtensorMapDataType, cuuint32_t, void*, const cuuint64_t*, const cuuint64_t*, const cuuint32_t*, const cuuint32_t*,
                             CUtensorMapInterleave, CUtensorMapSwizzle, CUtensorMapL2promotion, CUtensorMapFloatOOBfill);
  static Encode encode = nullptr;
  if (!encode) {
    cudaDriverEntryPointQueryResult qr;
    cudaGetDriverEntryPoint("cuTensorMapEncodeTiled", (void**)&encode, cudaEnableDefault, &qr);
  }
  const cuuint64_t dims[2] = {DM, 4096}, pitch[1] = {DM * 2};
  const cuuint32_t box[2] = {64, 16}, es[2] = {1, 1};
  encode(&P.tm, CU_TENSOR_MAP_DATA_TYPE_BFLOAT16, 2, d_in[11], dims, pitch, box, es, CU_TENSOR_MAP_INTERLEAVE_NONE,
         CU_TENSOR_MAP_SWIZZLE_128B, CU_TENSOR_MAP_L2_PROMOTION_NONE, CU_TENSOR_MAP_FLOAT_OOB_FILL_NONE);
  void* xc = nullptr;
  cudaGetSymbolAddress(&xc, g_xchg);
  P.memx = (uint4*)(((uintptr_t)xc + 0x1FFFFF) & ~(uintptr_t)0x1FFFFF);
  P.d_x = mkdesc(Q_X, 128, 1024, 0); P.d_wl = mkdesc(Q_WL, 16, 1024, 1);
  P.d_ring = mkdesc(W_RING, 512, 128, 0); P.d_ws = mkdesc(W_WS, 16, 1024, 1);
  cudaFuncSetAttribute(head_kernel, cudaFuncAttributeMaxDynamicSharedMemorySize, SMEM_TOTAL);
  cudaFuncSetAttribute(tail_kernel, cudaFuncAttributeMaxDynamicSharedMemorySize, SMEM_TOTAL);
  head_kernel<<<96, 512, SMEM_TOTAL>>>(P);
  cudaLaunchConfig_t cfg = {};
  cfg.gridDim = dim3(36); cfg.blockDim = dim3(512); cfg.dynamicSmemBytes = SMEM_TOTAL; cfg.stream = 0;
  cudaLaunchAttribute attr[1];
  attr[0].id = cudaLaunchAttributeProgrammaticStreamSerialization;
  attr[0].val.programmaticStreamSerializationAllowed = 1;
  cfg.attrs = attr; cfg.numAttrs = 1;
  cudaLaunchKernelEx(&cfg, tail_kernel, P);
}
```
